```python
import torch

def _softmax(x, axis=-1):
    return torch.softmax(x, dim=axis)

def _gelu(x):
    return torch.nn.functional.gelu(x, approximate='tanh')

def _silu(x):
    return torch.nn.functional.silu(x)

def _sigmoid(x):
    return torch.sigmoid(x)

def _layernorm(x, axis=-1, eps=1e-05):
    m = x.mean(dim=axis, keepdim=True)
    v = x.var(dim=axis, keepdim=True, unbiased=False)
    return (x - m) / torch.sqrt(v + eps)

def _scatter_add(tgt, idx, src, axis=0):
    return tgt.clone().index_add_(axis, idx, src)

def _segment_sum(src, seg, n):
    out = torch.zeros((n,) + src.shape[1:], dtype=src.dtype)
    return out.index_add_(0, seg, src)

def _pad(x, pw):
    flat = tuple((v for pair in reversed(pw) for v in pair))
    return torch.nn.functional.pad(x, flat)
kernel_name = 'adaLN_cond__sliding_block_cached__swiglu_ffn__prompt'

def setup_inputs():

    _w = lambda a: (lambda t: t.to(torch.bfloat16) if t.is_floating_point() else t)(torch.as_tensor(a))

    def _A_setup():
        B, Sq, D = (1, 2048, 640)
        Hq, Hkv, Sk, Dh = (32, 32, 2048, 128)
        assert Hq % Hkv == 0, (Hq, Hkv)
        return {'x': _w((lambda *s: torch.randn(*s, dtype=torch.bfloat16) * 0.05)(B, Sq, D)), 'k_cache': _w((lambda *s: torch.randn(*s, dtype=torch.bfloat16) * 3.2)(B, Hkv, Sk, Dh)), 'v_cache': _w((lambda *s: torch.randn(*s, dtype=torch.bfloat16) * 0.4)(B, Hkv, Sk, Dh)), 'wq': _w((lambda *s: torch.randn(*s, dtype=torch.bfloat16) * 3.2)(D, Hq * Dh) * D ** (-0.5)), 'wo': _w((lambda *s: torch.randn(*s, dtype=torch.bfloat16) * 0.4)(Hq * Dh, D) * (Hq * Dh) ** (-0.5))}
    _A_in = _A_setup()

    def _B_setup():
        B, S, D, F = (1, 2048, 640, 1728)
        return {'x': _w((lambda *s: torch.randn(*s, dtype=torch.bfloat16) * 0.05)(B, S, D)), 'w_gate': _w((lambda *s: torch.randn(*s, dtype=torch.bfloat16) * 0.05)(D, F)), 'w_up': _w((lambda *s: torch.randn(*s, dtype=torch.bfloat16) * 0.05)(D, F)), 'w_down': _w((lambda *s: torch.randn(*s, dtype=torch.bfloat16) * 0.05)(F, D))}
    _B_in = _B_setup()
    return {'A_x': _A_in['x'], 'A_k_cache': _A_in['k_cache'], 'A_v_cache': _A_in['v_cache'], 'A_wq': _A_in['wq'], 'A_wo': _A_in['wo'], 'B_x': _B_in['x'], 'B_w_gate': _B_in['w_gate'], 'B_w_up': _B_in['w_up'], 'B_w_down': _B_in['w_down'], 'c': _w((lambda *s: torch.randn(*s, dtype=torch.bfloat16) * 0.1)(1, 640) * 8.0), 'w_mod': _w((lambda *s: torch.randn(*s, dtype=torch.bfloat16) * 0.1)(640, 6 * 640) * 640 ** (-0.5) * 8.0)}

def reference(A_x, A_k_cache, A_v_cache, A_wq, A_wo, B_x, B_w_gate, B_w_up, B_w_down, c, w_mod):

    def _A_ref(x, k_cache, v_cache, wq, wo):
        B, Sq, D = x.shape
        Hq, Dh = (32, 128)
        Hkv, Sk = (k_cache.shape[1], k_cache.shape[2])
        W = min(4096, max(256, Sk // 4))
        rep = Hq // Hkv
        q = (lambda x, *d: x.permute(*d))((x @ wq).reshape(B, Sq, Hq, Dh), 0, 2, 1, 3)
        k = (lambda x, n, axis: torch.repeat_interleave(x, n, dim=axis))(k_cache[:, :, Sk - W:, :], rep, axis=1)
        v = (lambda x, n, axis: torch.repeat_interleave(x, n, dim=axis))(v_cache[:, :, Sk - W:, :], rep, axis=1)
        scores = torch.einsum('bhqd,bhkd->bhqk', q, k) * Dh ** (-0.5)
        p = _softmax(scores, axis=-1)
        o = torch.einsum('bhqk,bhkd->bhqd', p, v)
        return (lambda x, *d: x.permute(*d))(o, 0, 2, 1, 3).reshape(B, Sq, Hq * Dh) @ wo

    def _B_ref(x, w_gate, w_up, w_down):
        g = _silu(x @ w_gate)
        u = x @ w_up
        return g * u @ w_down
    x = A_x
    mod = (_silu(c) @ w_mod).reshape(c.shape[0], 6, 1, -1)
    sa, ca, ga, sb, cb, gb = (mod[:, 0].clone(), mod[:, 1].clone(), mod[:, 2].clone(), mod[:, 3].clone(), mod[:, 4].clone(), mod[:, 5].clone())
    h = _layernorm(x, axis=-1) * (1 + ca) + sa
    x = x + ga * _A_ref(h, A_k_cache, A_v_cache, A_wq, A_wo)
    h = _layernorm(x, axis=-1) * (1 + cb) + sb
    x = x + gb * _B_ref(h, B_w_gate, B_w_up, B_w_down)
    return x
```

```cpp
#include <cuda_runtime.h>
#include <cuda_bf16.h>
#include <cuda.h>
#include <stdint.h>

__device__ __forceinline__ uint32_t smem_u32(const void* p) { return (uint32_t)__cvta_generic_to_shared(p); }

__device__ __forceinline__ void mbar_init(uint32_t bar, uint32_t count) {
    asm volatile("mbarrier.init.shared::cta.b64 [%0], %1;" ::"r"(bar), "r"(count) : "memory");
}
__device__ __forceinline__ void mbar_expect_tx(uint32_t bar, uint32_t bytes) {
    asm volatile("mbarrier.arrive.expect_tx.shared::cta.b64 _, [%0], %1;" ::"r"(bar), "r"(bytes) : "memory");
}
__device__ __forceinline__ void mbar_arrive(uint32_t bar) {
    asm volatile("mbarrier.arrive.shared::cta.b64 _, [%0];" ::"r"(bar) : "memory");
}
__device__ __forceinline__ void mbar_arrive_cluster(uint32_t bar, uint32_t cta) {
    asm volatile(
        "{\n.reg .b32 ra;\n"
        "mapa.shared::cluster.u32 ra, %0, %1;\n"
        "mbarrier.arrive.shared::cluster.b64 _, [ra];\n}\n" ::"r"(bar), "r"(cta)
        : "memory");
}
__device__ __forceinline__ bool mbar_try_wait(uint32_t bar, uint32_t parity) {
    uint32_t ok;
    asm volatile(
        "{\n.reg .pred p;\n"
        "mbarrier.try_wait.parity.shared::cta.b64 p, [%1], %2;\n"
        "selp.u32 %0, 1, 0, p;\n}\n"
        : "=r"(ok)
        : "r"(bar), "r"(parity)
        : "memory");
    return ok != 0;
}
__device__ __forceinline__ bool mbar_try_wait_cluster(uint32_t bar, uint32_t parity) {
    uint32_t ok;
    asm volatile(
        "{\n.reg .pred p;\n"
        "mbarrier.try_wait.parity.shared::cta.b64 p, [%1], %2;\n"
        "selp.u32 %0, 1, 0, p;\n}\n"
        : "=r"(ok)
        : "r"(bar), "r"(parity)
        : "memory");
    return ok != 0;
}
__device__ volatile int g_abort = 0;
__device__ __forceinline__ void mbar_wait(uint32_t bar, uint32_t parity) {
    if (mbar_try_wait(bar, parity)) return;
    uint32_t n = 0;
    while (!mbar_try_wait(bar, parity)) {
        ++n;
        if (n > (1u << 22)) { g_abort = 1; break; }
        if ((n & 255u) == 0 && g_abort) break;
    }
}
__device__ __forceinline__ void mbar_wait_cluster(uint32_t bar, uint32_t parity) { mbar_wait(bar, parity); }
__device__ __forceinline__ void fence_mbar_init() { asm volatile("fence.mbarrier_init.release.cluster;" ::: "memory"); }
__device__ __forceinline__ void fence_proxy_async() { asm volatile("fence.proxy.async.shared::cta;" ::: "memory"); }
__device__ __forceinline__ void fence_proxy_async_all() { asm volatile("fence.proxy.async;" ::: "memory"); }
__device__ __forceinline__ void cluster_arrive() { asm volatile("barrier.cluster.arrive.release.aligned;" ::: "memory"); }
__device__ __forceinline__ void cluster_wait() { asm volatile("barrier.cluster.wait.acquire.aligned;" ::: "memory"); }
__device__ __forceinline__ void cluster_sync() { cluster_arrive(); cluster_wait(); }
__device__ __forceinline__ uint32_t cluster_ctarank() {
    uint32_t r;
    asm volatile("mov.u32 %0, %%cluster_ctarank;" : "=r"(r));
    return r;
}
__device__ __forceinline__ void bar_sync(int id, int n) { asm volatile("bar.sync %0, %1;" ::"r"(id), "r"(n) : "memory"); }
__device__ __forceinline__ void bar_arrive(int id, int n) { asm volatile("bar.arrive %0, %1;" ::"r"(id), "r"(n) : "memory"); }
__device__ __forceinline__ void pdl_wait() { asm volatile("griddepcontrol.wait;" ::: "memory"); }
__device__ __forceinline__ void pdl_launch() { asm volatile("griddepcontrol.launch_dependents;" ::: "memory"); }

__device__ __forceinline__ void tma_prefetch_desc(const CUtensorMap* m) {
    asm volatile("prefetch.tensormap [%0];" ::"l"(m) : "memory");
}
__device__ __forceinline__ void tma_load_2d(uint32_t dst, const CUtensorMap* m, int c0, int c1, uint32_t bar) {
    asm volatile(
        "cp.async.bulk.tensor.2d.shared::cluster.global.mbarrier::complete_tx::bytes [%0], [%1, {%3, %4}], [%2];"
        ::"r"(dst), "l"(m), "r"(bar), "r"(c0), "r"(c1)
        : "memory");
}
__device__ __forceinline__ void tma_load_2d_mc(uint32_t dst, const CUtensorMap* m, int c0, int c1, uint32_t bar, uint16_t mask) {
    asm volatile(
        "cp.async.bulk.tensor.2d.shared::cluster.global.mbarrier::complete_tx::bytes.multicast::cluster [%0], [%1, {%3, %4}], [%2], %5;"
        ::"r"(dst), "l"(m), "r"(bar), "r"(c0), "r"(c1), "h"(mask)
        : "memory");
}
__device__ __forceinline__ void tma_store_2d(const CUtensorMap* m, uint32_t src, int c0, int c1) {
    asm volatile("cp.async.bulk.tensor.2d.global.shared::cta.bulk_group [%0, {%2, %3}], [%1];"
                 ::"l"(m), "r"(src), "r"(c0), "r"(c1)
                 : "memory");
}
__device__ __forceinline__ void tma_store_commit() { asm volatile("cp.async.bulk.commit_group;" ::: "memory"); }
template <int N> __device__ __forceinline__ void tma_store_wait_read() {
    asm volatile("cp.async.bulk.wait_group.read %0;" ::"n"(N) : "memory");
}
template <int N> __device__ __forceinline__ void tma_store_wait() {
    asm volatile("cp.async.bulk.wait_group %0;" ::"n"(N) : "memory");
}

__device__ __forceinline__ void wgmma_fence() { asm volatile("wgmma.fence.sync.aligned;" ::: "memory"); }
__device__ __forceinline__ void wgmma_commit() { asm volatile("wgmma.commit_group.sync.aligned;" ::: "memory"); }
template <int N> __device__ __forceinline__ void wgmma_wait() {
    asm volatile("wgmma.wait_group.sync.aligned %0;" ::"n"(N) : "memory");
}
template <int R> __device__ __forceinline__ void reg_alloc() { asm volatile("setmaxnreg.inc.sync.aligned.u32 %0;" ::"n"(R)); }
template <int R> __device__ __forceinline__ void reg_dealloc() { asm volatile("setmaxnreg.dec.sync.aligned.u32 %0;" ::"n"(R)); }

template <int N> __device__ __forceinline__ void fence_regs(float (&r)[N]) {
#pragma unroll
    for (int i = 0; i < N; i++) asm volatile("" : "+f"(r[i])::"memory");
}
template <int N> __device__ __forceinline__ void fence_regs_u(uint32_t (&r)[N][4]) {
#pragma unroll
    for (int i = 0; i < N; i++) {
#pragma unroll
        for (int j = 0; j < 4; j++) asm volatile("" : "+r"(r[i][j])::"memory");
    }
}

__device__ __forceinline__ uint64_t make_desc(uint32_t addr, uint32_t lbo_bytes, uint32_t sbo_bytes, uint32_t swz) {
    return (uint64_t)((addr & 0x3FFFF) >> 4) | ((uint64_t)(lbo_bytes >> 4) << 16) | ((uint64_t)(sbo_bytes >> 4) << 32) |
           ((uint64_t)swz << 62);
}

__device__ __forceinline__ uint32_t pack_bf16(float lo, float hi) {
    uint32_t r;
    asm("cvt.rn.bf16x2.f32 %0, %1, %2;" : "=r"(r) : "f"(hi), "f"(lo));
    return r;
}
__device__ __forceinline__ float bf16_round(float x) { return __bfloat162float(__float2bfloat16_rn(x)); }
__device__ __forceinline__ float bf16lo(uint32_t v) { return __uint_as_float(v << 16); }
__device__ __forceinline__ float bf16hi(uint32_t v) { return __uint_as_float(v & 0xffff0000u); }
__device__ __forceinline__ float ex2(float x) {
    float y;
    asm("ex2.approx.ftz.f32 %0, %1;" : "=f"(y) : "f"(x));
    return y;
}
__device__ __forceinline__ void stmatrix_x4(uint32_t addr, uint32_t r0, uint32_t r1, uint32_t r2, uint32_t r3) {
    asm volatile("stmatrix.sync.aligned.m8n8.x4.shared.b16 [%0], {%1, %2, %3, %4};" ::"r"(addr), "r"(r0), "r"(r1), "r"(r2), "r"(r3)
                 : "memory");
}
__device__ __forceinline__ uint32_t mapa(uint32_t addr, uint32_t cta) {
    uint32_t r;
    asm volatile("mapa.shared::cluster.u32 %0, %1, %2;" : "=r"(r) : "r"(addr), "r"(cta));
    return r;
}
__device__ __forceinline__ void st_cluster_v2(uint32_t addr, float a, float b) {
    asm volatile("st.shared::cluster.v2.f32 [%0], {%1, %2};" ::"r"(addr), "f"(a), "f"(b) : "memory");
}
__device__ __forceinline__ void wgmma_ss_n256_t1(float (&d)[128], uint64_t descA, uint64_t descB, int scaleD) {
    asm volatile("{\n.reg .pred p;\n"
        "setp.ne.b32 p, %130, 0;\n"
        "wgmma.mma_async.sync.aligned.m64n256k16.f32.bf16.bf16 "
        "{%0, %1, %2, %3, %4, %5, %6, %7, %8, %9, %10, %11, %12, %13, %14, %15, "
        "%16, %17, %18, %19, %20, %21, %22, %23, %24, %25, %26, %27, %28, %29, %30, %31, "
        "%32, %33, %34, %35, %36, %37, %38, %39, %40, %41, %42, %43, %44, %45, %46, %47, "
        "%48, %49, %50, %51, %52, %53, %54, %55, %56, %57, %58, %59, %60, %61, %62, %63, "
        "%64, %65, %66, %67, %68, %69, %70, %71, %72, %73, %74, %75, %76, %77, %78, %79, "
        "%80, %81, %82, %83, %84, %85, %86, %87, %88, %89, %90, %91, %92, %93, %94, %95, "
        "%96, %97, %98, %99, %100, %101, %102, %103, %104, %105, %106, %107, %108, %109, %110, %111, "
        "%112, %113, %114, %115, %116, %117, %118, %119, %120, %121, %122, %123, %124, %125, %126, %127}, "
        "%128, %129, p, 1, 1, 0, 1;\n}\n"
        :
          "+f"(d[0]), "+f"(d[1]), "+f"(d[2]), "+f"(d[3]), "+f"(d[4]), "+f"(d[5]), "+f"(d[6]), "+f"(d[7]),
          "+f"(d[8]), "+f"(d[9]), "+f"(d[10]), "+f"(d[11]), "+f"(d[12]), "+f"(d[13]), "+f"(d[14]), "+f"(d[15]),
          "+f"(d[16]), "+f"(d[17]), "+f"(d[18]), "+f"(d[19]), "+f"(d[20]), "+f"(d[21]), "+f"(d[22]), "+f"(d[23]),
          "+f"(d[24]), "+f"(d[25]), "+f"(d[26]), "+f"(d[27]), "+f"(d[28]), "+f"(d[29]), "+f"(d[30]), "+f"(d[31]),
          "+f"(d[32]), "+f"(d[33]), "+f"(d[34]), "+f"(d[35]), "+f"(d[36]), "+f"(d[37]), "+f"(d[38]), "+f"(d[39]),
          "+f"(d[40]), "+f"(d[41]), "+f"(d[42]), "+f"(d[43]), "+f"(d[44]), "+f"(d[45]), "+f"(d[46]), "+f"(d[47]),
          "+f"(d[48]), "+f"(d[49]), "+f"(d[50]), "+f"(d[51]), "+f"(d[52]), "+f"(d[53]), "+f"(d[54]), "+f"(d[55]),
          "+f"(d[56]), "+f"(d[57]), "+f"(d[58]), "+f"(d[59]), "+f"(d[60]), "+f"(d[61]), "+f"(d[62]), "+f"(d[63]),
          "+f"(d[64]), "+f"(d[65]), "+f"(d[66]), "+f"(d[67]), "+f"(d[68]), "+f"(d[69]), "+f"(d[70]), "+f"(d[71]),
          "+f"(d[72]), "+f"(d[73]), "+f"(d[74]), "+f"(d[75]), "+f"(d[76]), "+f"(d[77]), "+f"(d[78]), "+f"(d[79]),
          "+f"(d[80]), "+f"(d[81]), "+f"(d[82]), "+f"(d[83]), "+f"(d[84]), "+f"(d[85]), "+f"(d[86]), "+f"(d[87]),
          "+f"(d[88]), "+f"(d[89]), "+f"(d[90]), "+f"(d[91]), "+f"(d[92]), "+f"(d[93]), "+f"(d[94]), "+f"(d[95]),
          "+f"(d[96]), "+f"(d[97]), "+f"(d[98]), "+f"(d[99]), "+f"(d[100]), "+f"(d[101]), "+f"(d[102]), "+f"(d[103]),
          "+f"(d[104]), "+f"(d[105]), "+f"(d[106]), "+f"(d[107]), "+f"(d[108]), "+f"(d[109]), "+f"(d[110]), "+f"(d[111]),
          "+f"(d[112]), "+f"(d[113]), "+f"(d[114]), "+f"(d[115]), "+f"(d[116]), "+f"(d[117]), "+f"(d[118]), "+f"(d[119]),
          "+f"(d[120]), "+f"(d[121]), "+f"(d[122]), "+f"(d[123]), "+f"(d[124]), "+f"(d[125]), "+f"(d[126]), "+f"(d[127])
        : "l"(descA), "l"(descB), "r"(scaleD));
}

__device__ __forceinline__ void wgmma_rs_n128_t0(float (&d)[64], const uint32_t (&a)[4], uint64_t descB, int scaleD) {
    asm volatile("{\n.reg .pred p;\n"
        "setp.ne.b32 p, %69, 0;\n"
        "wgmma.mma_async.sync.aligned.m64n128k16.f32.bf16.bf16 "
        "{%0, %1, %2, %3, %4, %5, %6, %7, %8, %9, %10, %11, %12, %13, %14, %15, "
        "%16, %17, %18, %19, %20, %21, %22, %23, %24, %25, %26, %27, %28, %29, %30, %31, "
        "%32, %33, %34, %35, %36, %37, %38, %39, %40, %41, %42, %43, %44, %45, %46, %47, "
        "%48, %49, %50, %51, %52, %53, %54, %55, %56, %57, %58, %59, %60, %61, %62, %63}, "
        "{%64, %65, %66, %67}, %68, p, 1, 1, 0;\n}\n"
        :
          "+f"(d[0]), "+f"(d[1]), "+f"(d[2]), "+f"(d[3]), "+f"(d[4]), "+f"(d[5]), "+f"(d[6]), "+f"(d[7]),
          "+f"(d[8]), "+f"(d[9]), "+f"(d[10]), "+f"(d[11]), "+f"(d[12]), "+f"(d[13]), "+f"(d[14]), "+f"(d[15]),
          "+f"(d[16]), "+f"(d[17]), "+f"(d[18]), "+f"(d[19]), "+f"(d[20]), "+f"(d[21]), "+f"(d[22]), "+f"(d[23]),
          "+f"(d[24]), "+f"(d[25]), "+f"(d[26]), "+f"(d[27]), "+f"(d[28]), "+f"(d[29]), "+f"(d[30]), "+f"(d[31]),
          "+f"(d[32]), "+f"(d[33]), "+f"(d[34]), "+f"(d[35]), "+f"(d[36]), "+f"(d[37]), "+f"(d[38]), "+f"(d[39]),
          "+f"(d[40]), "+f"(d[41]), "+f"(d[42]), "+f"(d[43]), "+f"(d[44]), "+f"(d[45]), "+f"(d[46]), "+f"(d[47]),
          "+f"(d[48]), "+f"(d[49]), "+f"(d[50]), "+f"(d[51]), "+f"(d[52]), "+f"(d[53]), "+f"(d[54]), "+f"(d[55]),
          "+f"(d[56]), "+f"(d[57]), "+f"(d[58]), "+f"(d[59]), "+f"(d[60]), "+f"(d[61]), "+f"(d[62]), "+f"(d[63])
        : "r"(a[0]), "r"(a[1]), "r"(a[2]), "r"(a[3]), "l"(descB), "r"(scaleD));
}

__device__ __forceinline__ void wgmma_rs_n128_t1(float (&d)[64], const uint32_t (&a)[4], uint64_t descB, int scaleD) {
    asm volatile("{\n.reg .pred p;\n"
        "setp.ne.b32 p, %69, 0;\n"
        "wgmma.mma_async.sync.aligned.m64n128k16.f32.bf16.bf16 "
        "{%0, %1, %2, %3, %4, %5, %6, %7, %8, %9, %10, %11, %12, %13, %14, %15, "
        "%16, %17, %18, %19, %20, %21, %22, %23, %24, %25, %26, %27, %28, %29, %30, %31, "
        "%32, %33, %34, %35, %36, %37, %38, %39, %40, %41, %42, %43, %44, %45, %46, %47, "
        "%48, %49, %50, %51, %52, %53, %54, %55, %56, %57, %58, %59, %60, %61, %62, %63}, "
        "{%64, %65, %66, %67}, %68, p, 1, 1, 1;\n}\n"
        :
          "+f"(d[0]), "+f"(d[1]), "+f"(d[2]), "+f"(d[3]), "+f"(d[4]), "+f"(d[5]), "+f"(d[6]), "+f"(d[7]),
          "+f"(d[8]), "+f"(d[9]), "+f"(d[10]), "+f"(d[11]), "+f"(d[12]), "+f"(d[13]), "+f"(d[14]), "+f"(d[15]),
          "+f"(d[16]), "+f"(d[17]), "+f"(d[18]), "+f"(d[19]), "+f"(d[20]), "+f"(d[21]), "+f"(d[22]), "+f"(d[23]),
          "+f"(d[24]), "+f"(d[25]), "+f"(d[26]), "+f"(d[27]), "+f"(d[28]), "+f"(d[29]), "+f"(d[30]), "+f"(d[31]),
          "+f"(d[32]), "+f"(d[33]), "+f"(d[34]), "+f"(d[35]), "+f"(d[36]), "+f"(d[37]), "+f"(d[38]), "+f"(d[39]),
          "+f"(d[40]), "+f"(d[41]), "+f"(d[42]), "+f"(d[43]), "+f"(d[44]), "+f"(d[45]), "+f"(d[46]), "+f"(d[47]),
          "+f"(d[48]), "+f"(d[49]), "+f"(d[50]), "+f"(d[51]), "+f"(d[52]), "+f"(d[53]), "+f"(d[54]), "+f"(d[55]),
          "+f"(d[56]), "+f"(d[57]), "+f"(d[58]), "+f"(d[59]), "+f"(d[60]), "+f"(d[61]), "+f"(d[62]), "+f"(d[63])
        : "r"(a[0]), "r"(a[1]), "r"(a[2]), "r"(a[3]), "l"(descB), "r"(scaleD));
}

__device__ __forceinline__ void wgmma_ss_n160_t1(float (&d)[80], uint64_t descA, uint64_t descB, int scaleD) {
    asm volatile("{\n.reg .pred p;\n"
        "setp.ne.b32 p, %82, 0;\n"
        "wgmma.mma_async.sync.aligned.m64n160k16.f32.bf16.bf16 "
        "{%0, %1, %2, %3, %4, %5, %6, %7, %8, %9, %10, %11, %12, %13, %14, %15, "
        "%16, %17, %18, %19, %20, %21, %22, %23, %24, %25, %26, %27, %28, %29, %30, %31, "
        "%32, %33, %34, %35, %36, %37, %38, %39, %40, %41, %42, %43, %44, %45, %46, %47, "
        "%48, %49, %50, %51, %52, %53, %54, %55, %56, %57, %58, %59, %60, %61, %62, %63, "
        "%64, %65, %66, %67, %68, %69, %70, %71, %72, %73, %74, %75, %76, %77, %78, %79}, "
        "%80, %81, p, 1, 1, 0, 1;\n}\n"
        :
          "+f"(d[0]), "+f"(d[1]), "+f"(d[2]), "+f"(d[3]), "+f"(d[4]), "+f"(d[5]), "+f"(d[6]), "+f"(d[7]),
          "+f"(d[8]), "+f"(d[9]), "+f"(d[10]), "+f"(d[11]), "+f"(d[12]), "+f"(d[13]), "+f"(d[14]), "+f"(d[15]),
          "+f"(d[16]), "+f"(d[17]), "+f"(d[18]), "+f"(d[19]), "+f"(d[20]), "+f"(d[21]), "+f"(d[22]), "+f"(d[23]),
          "+f"(d[24]), "+f"(d[25]), "+f"(d[26]), "+f"(d[27]), "+f"(d[28]), "+f"(d[29]), "+f"(d[30]), "+f"(d[31]),
          "+f"(d[32]), "+f"(d[33]), "+f"(d[34]), "+f"(d[35]), "+f"(d[36]), "+f"(d[37]), "+f"(d[38]), "+f"(d[39]),
          "+f"(d[40]), "+f"(d[41]), "+f"(d[42]), "+f"(d[43]), "+f"(d[44]), "+f"(d[45]), "+f"(d[46]), "+f"(d[47]),
          "+f"(d[48]), "+f"(d[49]), "+f"(d[50]), "+f"(d[51]), "+f"(d[52]), "+f"(d[53]), "+f"(d[54]), "+f"(d[55]),
          "+f"(d[56]), "+f"(d[57]), "+f"(d[58]), "+f"(d[59]), "+f"(d[60]), "+f"(d[61]), "+f"(d[62]), "+f"(d[63]),
          "+f"(d[64]), "+f"(d[65]), "+f"(d[66]), "+f"(d[67]), "+f"(d[68]), "+f"(d[69]), "+f"(d[70]), "+f"(d[71]),
          "+f"(d[72]), "+f"(d[73]), "+f"(d[74]), "+f"(d[75]), "+f"(d[76]), "+f"(d[77]), "+f"(d[78]), "+f"(d[79])
        : "l"(descA), "l"(descB), "r"(scaleD));
}

__device__ __forceinline__ void wgmma_ss_n184_t1(float (&d)[92], uint64_t descA, uint64_t descB, int scaleD) {
    asm volatile("{\n.reg .pred p;\n"
        "setp.ne.b32 p, %94, 0;\n"
        "wgmma.mma_async.sync.aligned.m64n184k16.f32.bf16.bf16 "
        "{%0, %1, %2, %3, %4, %5, %6, %7, %8, %9, %10, %11, %12, %13, %14, %15, "
        "%16, %17, %18, %19, %20, %21, %22, %23, %24, %25, %26, %27, %28, %29, %30, %31, "
        "%32, %33, %34, %35, %36, %37, %38, %39, %40, %41, %42, %43, %44, %45, %46, %47, "
        "%48, %49, %50, %51, %52, %53, %54, %55, %56, %57, %58, %59, %60, %61, %62, %63, "
        "%64, %65, %66, %67, %68, %69, %70, %71, %72, %73, %74, %75, %76, %77, %78, %79, "
        "%80, %81, %82, %83, %84, %85, %86, %87, %88, %89, %90, %91}, "
        "%92, %93, p, 1, 1, 0, 1;\n}\n"
        :
          "+f"(d[0]), "+f"(d[1]), "+f"(d[2]), "+f"(d[3]), "+f"(d[4]), "+f"(d[5]), "+f"(d[6]), "+f"(d[7]),
          "+f"(d[8]), "+f"(d[9]), "+f"(d[10]), "+f"(d[11]), "+f"(d[12]), "+f"(d[13]), "+f"(d[14]), "+f"(d[15]),
          "+f"(d[16]), "+f"(d[17]), "+f"(d[18]), "+f"(d[19]), "+f"(d[20]), "+f"(d[21]), "+f"(d[22]), "+f"(d[23]),
          "+f"(d[24]), "+f"(d[25]), "+f"(d[26]), "+f"(d[27]), "+f"(d[28]), "+f"(d[29]), "+f"(d[30]), "+f"(d[31]),
          "+f"(d[32]), "+f"(d[33]), "+f"(d[34]), "+f"(d[35]), "+f"(d[36]), "+f"(d[37]), "+f"(d[38]), "+f"(d[39]),
          "+f"(d[40]), "+f"(d[41]), "+f"(d[42]), "+f"(d[43]), "+f"(d[44]), "+f"(d[45]), "+f"(d[46]), "+f"(d[47]),
          "+f"(d[48]), "+f"(d[49]), "+f"(d[50]), "+f"(d[51]), "+f"(d[52]), "+f"(d[53]), "+f"(d[54]), "+f"(d[55]),
          "+f"(d[56]), "+f"(d[57]), "+f"(d[58]), "+f"(d[59]), "+f"(d[60]), "+f"(d[61]), "+f"(d[62]), "+f"(d[63]),
          "+f"(d[64]), "+f"(d[65]), "+f"(d[66]), "+f"(d[67]), "+f"(d[68]), "+f"(d[69]), "+f"(d[70]), "+f"(d[71]),
          "+f"(d[72]), "+f"(d[73]), "+f"(d[74]), "+f"(d[75]), "+f"(d[76]), "+f"(d[77]), "+f"(d[78]), "+f"(d[79]),
          "+f"(d[80]), "+f"(d[81]), "+f"(d[82]), "+f"(d[83]), "+f"(d[84]), "+f"(d[85]), "+f"(d[86]), "+f"(d[87]),
          "+f"(d[88]), "+f"(d[89]), "+f"(d[90]), "+f"(d[91])
        : "l"(descA), "l"(descB), "r"(scaleD));
}

constexpr int S_LEN = 2048;
constexpr int D_MODEL = 640;
constexpr int N_HEADS = 32;
constexpr int D_HEAD = 128;
constexpr int S_KV = 2048;
constexpr int WIN = 512;
constexpr int D_FF = 1728;
constexpr float LN_EPS = 1e-5f;

__device__ float g_mod[6 * D_MODEL];
__device__ __align__(1024) __nv_bfloat16 g_h[S_LEN * D_MODEL];
__device__ __align__(1024) __nv_bfloat16 g_o[S_LEN * N_HEADS * D_HEAD];
__device__ __align__(1024) __nv_bfloat16 g_x1[S_LEN * D_MODEL];
__device__ __align__(1024) __nv_bfloat16 g_h2[S_LEN * D_MODEL];
__device__ __align__(1024) __nv_bfloat16 g_act[S_LEN * D_FF];

__global__ void __launch_bounds__(256) mod_kernel(const __nv_bfloat16* __restrict__ c, const __nv_bfloat16* __restrict__ w_mod) {
    __shared__ float red[8][32];
    pdl_launch();
    const int warp = threadIdx.x >> 5, lane = threadIdx.x & 31;
    const int col0 = blockIdx.x * 32 + (lane & 3) * 8;
    float acc[8];
#pragma unroll
    for (int i = 0; i < 8; i++) acc[i] = 0.f;
    uint4 w[10];
    float s[10];
#pragma unroll
    for (int i = 0; i < 10; i++) {
        int k = warp * 80 + i * 8 + (lane >> 2);
        w[i] = __ldg(reinterpret_cast<const uint4*>(w_mod + (size_t)k * (6 * D_MODEL) + col0));
        float cv = __bfloat162float(c[k]);
        s[i] = bf16_round(cv / (1.f + __expf(-cv)));
    }
#pragma unroll
    for (int i = 0; i < 10; i++) {
        acc[0] += s[i] * bf16lo(w[i].x); acc[1] += s[i] * bf16hi(w[i].x);
        acc[2] += s[i] * bf16lo(w[i].y); acc[3] += s[i] * bf16hi(w[i].y);
        acc[4] += s[i] * bf16lo(w[i].z); acc[5] += s[i] * bf16hi(w[i].z);
        acc[6] += s[i] * bf16lo(w[i].w); acc[7] += s[i] * bf16hi(w[i].w);
    }
#pragma unroll
    for (int i = 0; i < 8; i++) {
        acc[i] += __shfl_xor_sync(0xffffffffu, acc[i], 4);
        acc[i] += __shfl_xor_sync(0xffffffffu, acc[i], 8);
        acc[i] += __shfl_xor_sync(0xffffffffu, acc[i], 16);
    }
    if (lane < 4) {
#pragma unroll
        for (int i = 0; i < 8; i++) red[warp][lane * 8 + i] = acc[i];
    }
    __syncthreads();
    if (threadIdx.x < 32) {
        float v = 0.f;
#pragma unroll
        for (int i = 0; i < 8; i++) v += red[i][threadIdx.x];
        g_mod[blockIdx.x * 32 + threadIdx.x] = bf16_round(v);
    }
}

__global__ void __launch_bounds__(256) ln1_kernel(const __nv_bfloat16* __restrict__ x) {
    pdl_launch();
    const int warp = threadIdx.x >> 5, lane = threadIdx.x & 31;
    const int row = blockIdx.x * 8 + warp;
    float v[20];
#pragma unroll
    for (int i = 0; i < 5; i++) {
        uint2 u = __ldg(reinterpret_cast<const uint2*>(x + (size_t)row * D_MODEL + (lane + 32 * i) * 4));
        v[4 * i] = bf16lo(u.x); v[4 * i + 1] = bf16hi(u.x); v[4 * i + 2] = bf16lo(u.y); v[4 * i + 3] = bf16hi(u.y);
    }
    float s = 0.f;
#pragma unroll
    for (int i = 0; i < 20; i++) s += v[i];
#pragma unroll
    for (int o = 16; o > 0; o >>= 1) s += __shfl_xor_sync(0xffffffffu, s, o);
    const float mean = s * (1.f / D_MODEL);
    float q = 0.f;
#pragma unroll
    for (int i = 0; i < 20; i++) { float d = v[i] - mean; q += d * d; }
#pragma unroll
    for (int o = 16; o > 0; o >>= 1) q += __shfl_xor_sync(0xffffffffu, q, o);
    const float rstd = rsqrtf(q * (1.f / D_MODEL) + LN_EPS);
    pdl_wait();
#pragma unroll
    for (int i = 0; i < 5; i++) {
        int c0 = (lane + 32 * i) * 4;
        float4 sa = *reinterpret_cast<const float4*>(g_mod + c0);
        float4 ca = *reinterpret_cast<const float4*>(g_mod + D_MODEL + c0);
        float o0 = (v[4 * i] - mean) * rstd * bf16_round(1.f + ca.x) + sa.x;
        float o1 = (v[4 * i + 1] - mean) * rstd * bf16_round(1.f + ca.y) + sa.y;
        float o2 = (v[4 * i + 2] - mean) * rstd * bf16_round(1.f + ca.z) + sa.z;
        float o3 = (v[4 * i + 3] - mean) * rstd * bf16_round(1.f + ca.w) + sa.w;
        uint2 u; u.x = pack_bf16(o0, o1); u.y = pack_bf16(o2, o3);
        *reinterpret_cast<uint2*>(g_h + (size_t)row * D_MODEL + c0) = u;
    }
}

constexpr int ATT_STAGES = 6;
constexpr int ATT_STAGE_BYTES = 32768;
constexpr int ATT_SMEM = ATT_STAGES * ATT_STAGE_BYTES + 2 * 16384 + 1024 + 256;

__global__ void __cluster_dims__(2, 1, 1) __launch_bounds__(384, 1)
attn_kernel(const __grid_constant__ CUtensorMap tm_h, const __grid_constant__ CUtensorMap tm_wq,
            const __grid_constant__ CUtensorMap tm_k, const __grid_constant__ CUtensorMap tm_v,
            const __grid_constant__ CUtensorMap tm_o) {
    extern __shared__ uint8_t smem_raw[];
    const uint32_t base = (smem_u32(smem_raw) + 1023u) & ~1023u;
    const uint32_t ring = base;
    const uint32_t park = base + ATT_STAGES * ATT_STAGE_BYTES;
    const uint32_t bars = park + 2 * 16384;
    const uint32_t cta_rank = cluster_ctarank();
    const int cluster_id = blockIdx.x >> 1;
    const int qpair = cluster_id & 7, hgroup = cluster_id >> 3;
    const int q0 = (qpair * 2 + (int)cta_rank) * 128;
    const int wg = threadIdx.x >> 7;

    if (threadIdx.x == 0) {
        for (int i = 0; i < ATT_STAGES; i++) {
            mbar_init(bars + 8 * i, 1);
            mbar_init(bars + 8 * (ATT_STAGES + i), 4);
        }
        fence_mbar_init();
    }
    __syncthreads();
    cluster_sync();
    pdl_launch();

    if (wg == 2) {
        reg_dealloc<24>();
        if (threadIdx.x == 256) {
            tma_prefetch_desc(&tm_h); tma_prefetch_desc(&tm_wq); tma_prefetch_desc(&tm_k); tma_prefetch_desc(&tm_v);
            uint32_t st = 0, ph = 1;
            auto acquire = [&]() -> uint32_t {
                mbar_wait_cluster(bars + 8 * (ATT_STAGES + st), ph);
                mbar_expect_tx(bars + 8 * st, ATT_STAGE_BYTES);
                return ring + st * ATT_STAGE_BYTES;
            };
            auto advance = [&]() { if (++st == ATT_STAGES) { st = 0; ph ^= 1; } };
            pdl_wait();
            for (int hp = 0; hp < 2; hp++) {
                const int head0 = hgroup * 4 + hp * 2;
                for (int kk2 = 0; kk2 < 5; kk2++) {
                    uint32_t dst = acquire();
                    tma_load_2d(dst, &tm_h, (2 * kk2) * 64, q0, bars + 8 * st);
                    tma_load_2d(dst + 16384, &tm_h, (2 * kk2 + 1) * 64, q0, bars + 8 * st);
                    advance();
                    for (int u = 0; u < 2; u++) {
                        dst = acquire();
                        const int kb = 2 * kk2 + u;
#pragma unroll
                        for (int c = 0; c < 2; c++) {
                            const int chunk = 2 * (int)cta_rank + c;
                            tma_load_2d_mc(dst + chunk * 8192, &tm_wq, head0 * 128 + chunk * 64, kb * 64, bars + 8 * st, 3);
                        }
                        advance();
                    }
                }
                for (int t = 0; t <= 8; t++) {
                    if (t < 8) {
                        uint32_t dst = acquire();
                        const int row = (head0 + (t >> 2)) * S_KV + (S_KV - WIN) + (t & 3) * 128;
                        tma_load_2d_mc(dst + cta_rank * 16384, &tm_k, cta_rank * 64, row, bars + 8 * st, 3);
                        advance();
                    }
                    if (t > 0) {
                        uint32_t dst = acquire();
                        const int tv = t - 1;
                        const int row = (head0 + (tv >> 2)) * S_KV + (S_KV - WIN) + (tv & 3) * 128;
                        tma_load_2d_mc(dst + cta_rank * 16384, &tm_v, cta_rank * 64, row, bars + 8 * st, 3);
                        advance();
                    }
                }
            }
        }
        __syncwarp();
        asm volatile("barrier.cluster.arrive.release.aligned; // producer\n barrier.cluster.wait.acquire.aligned;" ::: "memory");
    } else {
        reg_alloc<240>();
        const int tid = threadIdx.x & 127;
        const int warp = tid >> 5, lane = tid & 31;
        const uint32_t mypark = park + wg * 16384;
        const float cscale = 0.08838834764831845f * 1.4426950408889634f;
        uint32_t st = 0, ph = 0;
        auto wait_full = [&]() -> uint32_t {
            mbar_wait(bars + 8 * st, ph);
            return ring + st * ATT_STAGE_BYTES;
        };
        auto release = [&](uint32_t s) {
            if (tid == 0) mbar_arrive_cluster(bars + 8 * (ATT_STAGES + s), 0);
            if (tid == 32) mbar_arrive_cluster(bars + 8 * (ATT_STAGES + s), 1);
        };
        auto advance = [&]() { if (++st == ATT_STAGES) { st = 0; ph ^= 1; } };

        for (int hp = 0; hp < 2; hp++) {
            const int head0 = hgroup * 4 + hp * 2;
            uint32_t q[8][4];
            {
                float acc[128];
#pragma unroll
                for (int i = 0; i < 128; i++) acc[i] = 0.f;
                for (int kk2 = 0; kk2 < 5; kk2++) {
                    const uint32_t hbuf = wait_full();
                    const uint32_t sth = st;
                    advance();
#pragma unroll
                    for (int u = 0; u < 2; u++) {
                        const uint32_t wbuf = wait_full();
                        const uint32_t stw = st;
                        advance();
                        wgmma_fence();
#pragma unroll
                        for (int k = 0; k < 4; k++) {
                            uint64_t da = make_desc(hbuf + u * 16384 + wg * 8192 + k * 32, 16, 1024, 1);
                            uint64_t db = make_desc(wbuf + k * 2048, 8192, 1024, 1);
                            wgmma_ss_n256_t1(acc, da, db, (kk2 | u | k) != 0);
                        }
                        wgmma_commit();
                        wgmma_wait<0>();
                        release(stw);
                    }
                    release(sth);
                }
                fence_regs(acc);
                if (tid == 0) tma_store_wait_read<0>();
                bar_sync(1 + wg, 128);
#pragma unroll
                for (int i = 0; i < 8; i++) {
                    q[i][0] = pack_bf16(acc[8 * i + 0], acc[8 * i + 1]);
                    q[i][1] = pack_bf16(acc[8 * i + 2], acc[8 * i + 3]);
                    q[i][2] = pack_bf16(acc[8 * i + 4], acc[8 * i + 5]);
                    q[i][3] = pack_bf16(acc[8 * i + 6], acc[8 * i + 7]);
                    uint32_t b0 = pack_bf16(acc[64 + 8 * i + 0], acc[64 + 8 * i + 1]);
                    uint32_t b1 = pack_bf16(acc[64 + 8 * i + 2], acc[64 + 8 * i + 3]);
                    uint32_t b2 = pack_bf16(acc[64 + 8 * i + 4], acc[64 + 8 * i + 5]);
                    uint32_t b3 = pack_bf16(acc[64 + 8 * i + 6], acc[64 + 8 * i + 7]);
                    asm volatile("st.shared.v4.b32 [%0], {%1, %2, %3, %4};" ::"r"(mypark + (i * 128 + tid) * 16), "r"(b0), "r"(b1),
                                 "r"(b2), "r"(b3) : "memory");
                }
            }
            float o[64], s[64];
            uint32_t p[8][4];
            float m0, m1, l0, l1, a0, a1, lo0, lo1;
#pragma unroll
            for (int i = 0; i < 64; i++) { o[i] = 0.f; s[i] = 0.f; }

            auto issue_s = [&]() -> uint32_t {
                const uint32_t kbuf = wait_full();
                const uint32_t stk = st;
                advance();
                wgmma_fence();
#pragma unroll
                for (int k = 0; k < 8; k++) {
                    uint64_t db = make_desc(kbuf + (k >> 2) * 16384 + (k & 3) * 32, 16, 1024, 1);
                    wgmma_rs_n128_t0(s, q[k], db, k != 0);
                }
                wgmma_commit();
                return stk;
            };
            auto issue_pv = [&](bool fresh) -> uint32_t {
                const uint32_t vbuf = wait_full();
                const uint32_t stv = st;
                advance();
                wgmma_fence();
#pragma unroll
                for (int k = 0; k < 8; k++) {
                    uint64_t db = make_desc(vbuf + k * 2048, 16384, 1024, 1);
                    wgmma_rs_n128_t1(o, p[k], db, (!fresh) || k != 0);
                }
                wgmma_commit();
                return stv;
            };
            auto softmax = [&](bool first) {
                float mx0 = fmaxf(s[0], s[1]), mx1 = fmaxf(s[2], s[3]);
#pragma unroll
                for (int j = 1; j < 16; j++) {
                    mx0 = fmaxf(mx0, fmaxf(s[4 * j], s[4 * j + 1]));
                    mx1 = fmaxf(mx1, fmaxf(s[4 * j + 2], s[4 * j + 3]));
                }
                mx0 = fmaxf(mx0, __shfl_xor_sync(0xffffffffu, mx0, 1));
                mx0 = fmaxf(mx0, __shfl_xor_sync(0xffffffffu, mx0, 2));
                mx1 = fmaxf(mx1, __shfl_xor_sync(0xffffffffu, mx1, 1));
                mx1 = fmaxf(mx1, __shfl_xor_sync(0xffffffffu, mx1, 2));
                if (first) {
                    lo0 = l0; lo1 = l1;
                    m0 = mx0; m1 = mx1; l0 = 0.f; l1 = 0.f; a0 = 0.f; a1 = 0.f;
                } else {
                    float mn0 = fmaxf(m0, mx0), mn1 = fmaxf(m1, mx1);
                    a0 = ex2((m0 - mn0) * cscale); a1 = ex2((m1 - mn1) * cscale);
                    m0 = mn0; m1 = mn1;
                }
                const float mc0 = m0 * cscale, mc1 = m1 * cscale;
                float r0 = 0.f, r1 = 0.f;
#pragma unroll
                for (int j = 0; j < 16; j++) {
                    s[4 * j] = ex2(fmaf(s[4 * j], cscale, -mc0));
                    s[4 * j + 1] = ex2(fmaf(s[4 * j + 1], cscale, -mc0));
                    s[4 * j + 2] = ex2(fmaf(s[4 * j + 2], cscale, -mc1));
                    s[4 * j + 3] = ex2(fmaf(s[4 * j + 3], cscale, -mc1));
                    r0 += s[4 * j] + s[4 * j + 1];
                    r1 += s[4 * j + 2] + s[4 * j + 3];
                }
                l0 = l0 * a0 + r0; l1 = l1 * a1 + r1;
            };
            auto convert_p = [&]() {
#pragma unroll
                for (int i = 0; i < 8; i++) {
                    p[i][0] = pack_bf16(s[8 * i + 0], s[8 * i + 1]);
                    p[i][1] = pack_bf16(s[8 * i + 2], s[8 * i + 3]);
                    p[i][2] = pack_bf16(s[8 * i + 4], s[8 * i + 5]);
                    p[i][3] = pack_bf16(s[8 * i + 6], s[8 * i + 7]);
                }
            };
            auto store_o = [&](float ls0, float ls1, int head) {
                float s0 = ls0 + __shfl_xor_sync(0xffffffffu, ls0, 1); s0 += __shfl_xor_sync(0xffffffffu, s0, 2);
                float s1 = ls1 + __shfl_xor_sync(0xffffffffu, ls1, 1); s1 += __shfl_xor_sync(0xffffffffu, s1, 2);
                const float i0 = 1.f / s0, i1 = 1.f / s1;
                if (tid == 0) tma_store_wait_read<0>();
                bar_sync(1 + wg, 128);
#pragma unroll
                for (int j = 0; j < 16; j += 2) {
                    const int mi = lane >> 3;
                    const int row = warp * 16 + (mi & 1) * 8 + (lane & 7);
                    const int grp = j + (mi >> 1);
                    const uint32_t addr = mypark + (grp >> 3) * 8192 + row * 128 + (((grp & 7) ^ (row & 7)) << 4);
                    stmatrix_x4(addr, pack_bf16(o[4 * j] * i0, o[4 * j + 1] * i0), pack_bf16(o[4 * j + 2] * i1, o[4 * j + 3] * i1),
                                pack_bf16(o[4 * j + 4] * i0, o[4 * j + 5] * i0), pack_bf16(o[4 * j + 6] * i1, o[4 * j + 7] * i1));
                }
                fence_proxy_async();
                bar_sync(1 + wg, 128);
                if (tid == 0) {
                    tma_store_2d(&tm_o, mypark, head * 128, q0 + wg * 64);
                    tma_store_2d(&tm_o, mypark + 8192, head * 128 + 64, q0 + wg * 64);
                    tma_store_commit();
                }
            };

            l0 = 0.f; l1 = 0.f;
            {
                uint32_t stk = issue_s();
                wgmma_wait<0>();
                fence_regs(s);
                release(stk);
                softmax(true);
                convert_p();
            }
#pragma unroll 1
            for (int t = 1; t < 8; t++) {
                const bool first = (t == 4);
                if (t == 4) {
#pragma unroll
                    for (int i = 0; i < 8; i++) {
                        asm volatile("ld.shared.v4.b32 {%0, %1, %2, %3}, [%4];" : "=r"(q[i][0]), "=r"(q[i][1]), "=r"(q[i][2]), "=r"(q[i][3])
                                     : "r"(mypark + (i * 128 + tid) * 16) : "memory");
                    }
                }
                uint32_t stk = issue_s();
                uint32_t stv = issue_pv(t == 1 || t == 5);
                wgmma_wait<1>();
                fence_regs(s);
                release(stk);
                softmax(first);
                wgmma_wait<0>();
                fence_regs(o);
                release(stv);
                if (first) {
                    store_o(lo0, lo1, head0);
                } else {
#pragma unroll
                    for (int j = 0; j < 16; j++) {
                        o[4 * j] *= a0; o[4 * j + 1] *= a0; o[4 * j + 2] *= a1; o[4 * j + 3] *= a1;
                    }
                }
                convert_p();
            }
            {
                uint32_t stv = issue_pv(false);
                wgmma_wait<0>();
                fence_regs(o);
                release(stv);
                store_o(l0, l1, head0 + 1);
            }
        }
        if (tid == 0) tma_store_wait<0>();
        cluster_sync();
    }
}

constexpr int G1_STAGES = 6;
constexpr int G1_STAGE_BYTES = 16384 + 20480;
constexpr int G1_RED_PITCH = 648;
constexpr int G1_SMEM = G1_STAGES * G1_STAGE_BYTES + 1024 + 256;

template <int MODE>
__global__ void __cluster_dims__(8, 1, 1) __launch_bounds__(288, 1)
gemm_red_kernel(const __grid_constant__ CUtensorMap tm_a, const __grid_constant__ CUtensorMap tm_b,
                const __nv_bfloat16* __restrict__ resid, __nv_bfloat16* __restrict__ out) {
    constexpr int KBLOCKS = MODE == 0 ? 64 : 27;
    constexpr int KB0 = MODE == 0 ? 32 : 14;
    extern __shared__ uint8_t smem_raw[];
    const uint32_t base = (smem_u32(smem_raw) + 1023u) & ~1023u;
    const uint32_t bars = base + G1_STAGES * G1_STAGE_BYTES;
    const uint32_t rank = cluster_ctarank();
    const int nq = rank & 3, kh = rank >> 2;
    const int m0 = (blockIdx.x >> 3) * 128;
    const int kb_begin = kh == 0 ? 0 : KB0;
    const int nkb = kh == 0 ? KB0 : KBLOCKS - KB0;
    const int warp = threadIdx.x >> 5, lane = threadIdx.x & 31;

    if (threadIdx.x == 0) {
        for (int i = 0; i < G1_STAGES; i++) {
            mbar_init(bars + 8 * i, 1);
            mbar_init(bars + 8 * (G1_STAGES + i), 8);
        }
        fence_mbar_init();
    }
    __syncthreads();
    cluster_sync();
    pdl_launch();

    float acc[80];
    if (warp == 8) {
        if (lane == 0) {
            tma_prefetch_desc(&tm_a); tma_prefetch_desc(&tm_b);
            pdl_wait();
            uint32_t st = 0, ph = 1;
            const uint16_t mask = (uint16_t)(0xF << (4 * kh));
            for (int i = 0; i < nkb; i++) {
                mbar_wait_cluster(bars + 8 * (G1_STAGES + st), ph);
                mbar_expect_tx(bars + 8 * st, G1_STAGE_BYTES);
                const uint32_t dst = base + st * G1_STAGE_BYTES;
                const int k0 = (kb_begin + i) * 64;
                tma_load_2d_mc(dst + nq * 4096, &tm_a, k0, m0 + nq * 32, bars + 8 * st, mask);
#pragma unroll
                for (int c = 0; c < 5; c++) tma_load_2d(dst + 16384 + c * 4096, &tm_b, nq * 160 + c * 32, k0, bars + 8 * st);
                if (++st == G1_STAGES) { st = 0; ph ^= 1; }
            }
        }
        __syncwarp();
    } else {
        const int wg = warp >> 2;
        const int tid = threadIdx.x & 127;
        uint32_t st = 0, ph = 0;
        for (int i = 0; i < nkb; i++) {
            mbar_wait(bars + 8 * st, ph);
            const uint32_t buf = base + st * G1_STAGE_BYTES;
            wgmma_fence();
#pragma unroll
            for (int k = 0; k < 4; k++) {
                uint64_t da = make_desc(buf + wg * 8192 + k * 32, 16, 1024, 1);
                uint64_t db = make_desc(buf + 16384 + k * 1024, 4096, 512, 2);
                wgmma_ss_n160_t1(acc, da, db, (i | k) != 0);
            }
            wgmma_commit();
            wgmma_wait<0>();
            if (tid < 4) mbar_arrive_cluster(bars + 8 * (G1_STAGES + st), 4 * kh + tid);
            if (++st == G1_STAGES) { st = 0; ph ^= 1; }
        }
        fence_regs(acc);
    }
    cluster_sync();
    if (warp < 8) {
        const uint32_t dst = mapa(base, warp) + (uint32_t)((kh * 16 + (lane >> 2)) * G1_RED_PITCH + nq * 160 + (lane & 3) * 2) * 4;
#pragma unroll
        for (int j = 0; j < 20; j++) {
            st_cluster_v2(dst + j * 32, acc[4 * j], acc[4 * j + 1]);
            st_cluster_v2(dst + 8 * G1_RED_PITCH * 4 + j * 32, acc[4 * j + 2], acc[4 * j + 3]);
        }
    }
    cluster_sync();
    pdl_wait();
    if (warp < 8) {
        const float* red = reinterpret_cast<const float*>(smem_raw + (base - smem_u32(smem_raw)));
#pragma unroll
        for (int rr = 0; rr < 2; rr++) {
            const int r = warp * 2 + rr;
            const int row = m0 + (int)rank * 16 + r;
            float v[20];
#pragma unroll
            for (int i = 0; i < 5; i++) {
                const int c0 = (lane + 32 * i) * 4;
                float4 a = *reinterpret_cast<const float4*>(red + r * G1_RED_PITCH + c0);
                float4 b = *reinterpret_cast<const float4*>(red + (16 + r) * G1_RED_PITCH + c0);
                float4 g = *reinterpret_cast<const float4*>(g_mod + (MODE == 0 ? 2 : 5) * D_MODEL + c0);
                uint2 xr = *reinterpret_cast<const uint2*>(resid + (size_t)row * D_MODEL + c0);
                v[4 * i + 0] = bf16_round(bf16lo(xr.x) + bf16_round(g.x * bf16_round(a.x + b.x)));
                v[4 * i + 1] = bf16_round(bf16hi(xr.x) + bf16_round(g.y * bf16_round(a.y + b.y)));
                v[4 * i + 2] = bf16_round(bf16lo(xr.y) + bf16_round(g.z * bf16_round(a.z + b.z)));
                v[4 * i + 3] = bf16_round(bf16hi(xr.y) + bf16_round(g.w * bf16_round(a.w + b.w)));
                uint2 u; u.x = pack_bf16(v[4 * i], v[4 * i + 1]); u.y = pack_bf16(v[4 * i + 2], v[4 * i + 3]);
                *reinterpret_cast<uint2*>(out + (size_t)row * D_MODEL + c0) = u;
            }
            if (MODE == 0) {
                float s = 0.f;
#pragma unroll
                for (int i = 0; i < 20; i++) s += v[i];
#pragma unroll
                for (int o = 16; o > 0; o >>= 1) s += __shfl_xor_sync(0xffffffffu, s, o);
                const float mean = s * (1.f / D_MODEL);
                float q = 0.f;
#pragma unroll
                for (int i = 0; i < 20; i++) { float d = v[i] - mean; q += d * d; }
#pragma unroll
                for (int o = 16; o > 0; o >>= 1) q += __shfl_xor_sync(0xffffffffu, q, o);
                const float rstd = rsqrtf(q * (1.f / D_MODEL) + LN_EPS);
#pragma unroll
                for (int i = 0; i < 5; i++) {
                    const int c0 = (lane + 32 * i) * 4;
                    float4 sb = *reinterpret_cast<const float4*>(g_mod + 3 * D_MODEL + c0);
                    float4 cb = *reinterpret_cast<const float4*>(g_mod + 4 * D_MODEL + c0);
                    float o0 = (v[4 * i] - mean) * rstd * bf16_round(1.f + cb.x) + sb.x;
                    float o1 = (v[4 * i + 1] - mean) * rstd * bf16_round(1.f + cb.y) + sb.y;
                    float o2 = (v[4 * i + 2] - mean) * rstd * bf16_round(1.f + cb.z) + sb.z;
                    float o3 = (v[4 * i + 3] - mean) * rstd * bf16_round(1.f + cb.w) + sb.w;
                    uint2 u; u.x = pack_bf16(o0, o1); u.y = pack_bf16(o2, o3);
                    *reinterpret_cast<uint2*>(g_h2 + (size_t)row * D_MODEL + c0) = u;
                }
            }
        }
    }
}

constexpr int GU_STAGES = 4;
constexpr int GU_STAGE_BYTES = 16384 + 32768;
constexpr int GU_SMEM = GU_STAGES * GU_STAGE_BYTES + 1024 + 256;

__device__ __forceinline__ float silu_mul(float g, float u) {
    g = bf16_round(g); u = bf16_round(u);
    float s = bf16_round(g / (1.f + __expf(-g)));
    return s * u;
}

__global__ void __launch_bounds__(288, 1)
gateup_kernel(const __grid_constant__ CUtensorMap tm_a, const __grid_constant__ CUtensorMap tm_g128,
              const __grid_constant__ CUtensorMap tm_u128, const __grid_constant__ CUtensorMap tm_g64,
              const __grid_constant__ CUtensorMap tm_u64) {
    extern __shared__ uint8_t smem_raw[];
    const uint32_t base = (smem_u32(smem_raw) + 1023u) & ~1023u;
    const uint32_t bars = base + GU_STAGES * GU_STAGE_BYTES;
    const int fs = blockIdx.x & 7;
    const int m0 = (blockIdx.x >> 3) * 128;
    const int f0 = fs * 216;
    const int warp = threadIdx.x >> 5, lane = threadIdx.x & 31;

    if (threadIdx.x == 0) {
        for (int i = 0; i < GU_STAGES; i++) {
            mbar_init(bars + 8 * i, 1);
            mbar_init(bars + 8 * (GU_STAGES + i), 2);
        }
        fence_mbar_init();
    }
    __syncthreads();
    pdl_launch();

    if (warp == 8) {
        if (lane == 0) {
            tma_prefetch_desc(&tm_a); tma_prefetch_desc(&tm_g128); tma_prefetch_desc(&tm_u128);
            tma_prefetch_desc(&tm_g64); tma_prefetch_desc(&tm_u64);
            pdl_wait();
            uint32_t st = 0, ph = 1;
            for (int i = 0; i < 20; i++) {
                const int kb = i % 10;
                mbar_wait(bars + 8 * (GU_STAGES + st), ph);
                const uint32_t dst = base + st * GU_STAGE_BYTES;
                if (i < 10) {
                    mbar_expect_tx(bars + 8 * st, 16384 + 32768);
                    tma_load_2d(dst, &tm_a, kb * 64, m0, bars + 8 * st);
                    tma_load_2d(dst + 16384, &tm_g128, f0, kb * 64, bars + 8 * st);
                    tma_load_2d(dst + 16384 + 8192, &tm_g128, f0 + 64, kb * 64, bars + 8 * st);
                    tma_load_2d(dst + 16384 + 16384, &tm_u128, f0, kb * 64, bars + 8 * st);
                    tma_load_2d(dst + 16384 + 24576, &tm_u128, f0 + 64, kb * 64, bars + 8 * st);
                } else {
                    mbar_expect_tx(bars + 8 * st, 16384 + 24576);
                    tma_load_2d(dst, &tm_a, kb * 64, m0, bars + 8 * st);
#pragma unroll
                    for (int c = 0; c < 3; c++) {
                        tma_load_2d(dst + 16384 + c * 4096, &tm_g64, f0 + 128 + c * 32, kb * 64, bars + 8 * st);
                        tma_load_2d(dst + 16384 + 12288 + c * 4096, &tm_u64, f0 + 128 + c * 32, kb * 64, bars + 8 * st);
                    }
                }
                if (++st == GU_STAGES) { st = 0; ph ^= 1; }
            }
        }
    } else {
        const int wg = warp >> 2;
        const int tid = threadIdx.x & 127;
        const int w = warp & 3;
        uint32_t st = 0, ph = 0;
        const int r0 = m0 + wg * 64 + w * 16 + (lane >> 2);
        pdl_wait();
        {
            float acc[128];
            for (int i = 0; i < 10; i++) {
                mbar_wait(bars + 8 * st, ph);
                const uint32_t buf = base + st * GU_STAGE_BYTES;
                wgmma_fence();
#pragma unroll
                for (int k = 0; k < 4; k++) {
                    uint64_t da = make_desc(buf + wg * 8192 + k * 32, 16, 1024, 1);
                    uint64_t db = make_desc(buf + 16384 + k * 2048, 8192, 1024, 1);
                    wgmma_ss_n256_t1(acc, da, db, (i | k) != 0);
                }
                wgmma_commit();
                wgmma_wait<0>();
                if (tid == 0) mbar_arrive(bars + 8 * (GU_STAGES + st));
                if (++st == GU_STAGES) { st = 0; ph ^= 1; }
            }
            fence_regs(acc);
#pragma unroll
            for (int j = 0; j < 16; j++) {
                const int col = f0 + j * 8 + (lane & 3) * 2;
                *reinterpret_cast<uint32_t*>(g_act + (size_t)r0 * D_FF + col) =
                    pack_bf16(silu_mul(acc[4 * j], acc[64 + 4 * j]), silu_mul(acc[4 * j + 1], acc[64 + 4 * j + 1]));
                *reinterpret_cast<uint32_t*>(g_act + (size_t)(r0 + 8) * D_FF + col) =
                    pack_bf16(silu_mul(acc[4 * j + 2], acc[64 + 4 * j + 2]), silu_mul(acc[4 * j + 3], acc[64 + 4 * j + 3]));
            }
        }
        {
            float acc[92];
            for (int i = 0; i < 10; i++) {
                mbar_wait(bars + 8 * st, ph);
                const uint32_t buf = base + st * GU_STAGE_BYTES;
                wgmma_fence();
#pragma unroll
                for (int k = 0; k < 4; k++) {
                    uint64_t da = make_desc(buf + wg * 8192 + k * 32, 16, 1024, 1);
                    uint64_t db = make_desc(buf + 16384 + k * 1024, 4096, 512, 2);
                    wgmma_ss_n184_t1(acc, da, db, (i | k) != 0);
                }
                wgmma_commit();
                wgmma_wait<0>();
                if (tid == 0) mbar_arrive(bars + 8 * (GU_STAGES + st));
                if (++st == GU_STAGES) { st = 0; ph ^= 1; }
            }
            fence_regs(acc);
#pragma unroll
            for (int j = 0; j < 11; j++) {
                const int col = f0 + 128 + j * 8 + (lane & 3) * 2;
                *reinterpret_cast<uint32_t*>(g_act + (size_t)r0 * D_FF + col) =
                    pack_bf16(silu_mul(acc[4 * j], acc[48 + 4 * j]), silu_mul(acc[4 * j + 1], acc[48 + 4 * j + 1]));
                *reinterpret_cast<uint32_t*>(g_act + (size_t)(r0 + 8) * D_FF + col) =
                    pack_bf16(silu_mul(acc[4 * j + 2], acc[48 + 4 * j + 2]), silu_mul(acc[4 * j + 3], acc[48 + 4 * j + 3]));
            }
        }
    }
}

typedef CUresult (*PFN_encodeTiled)(CUtensorMap*, CUtensorMapDataType, cuuint32_t, void*, const cuuint64_t*, const cuuint64_t*,
                                    const cuuint32_t*, const cuuint32_t*, CUtensorMapInterleave, CUtensorMapSwizzle,
                                    CUtensorMapL2promotion, CUtensorMapFloatOOBfill);

static PFN_encodeTiled get_encode() {
    static PFN_encodeTiled fn = nullptr;
    if (!fn) {
        void* p = nullptr;
        cudaDriverEntryPointQueryResult qr;
        cudaGetDriverEntryPoint("cuTensorMapEncodeTiled", &p, cudaEnableDefault, &qr);
        fn = (PFN_encodeTiled)p;
    }
    return fn;
}

static CUtensorMap make_map(const void* ptr, uint64_t rows, uint64_t cols, uint32_t box_rows, uint32_t box_cols, CUtensorMapSwizzle swz) {
    CUtensorMap m;
    cuuint64_t dims[2] = {cols, rows};
    cuuint64_t strides[1] = {cols * 2};
    cuuint32_t box[2] = {box_cols, box_rows};
    cuuint32_t es[2] = {1, 1};
    get_encode()(&m, CU_TENSOR_MAP_DATA_TYPE_BFLOAT16, 2, const_cast<void*>(ptr), dims, strides, box, es, CU_TENSOR_MAP_INTERLEAVE_NONE,
                 swz, CU_TENSOR_MAP_L2_PROMOTION_L2_256B, CU_TENSOR_MAP_FLOAT_OOB_FILL_NONE);
    return m;
}

template <typename... KArgs, typename... Args>
static void launch(void (*kernel)(KArgs...), int grid, int block, int smem, int cluster, bool pdl, Args... args) {
    cudaLaunchConfig_t cfg = {};
    cfg.gridDim = dim3(grid);
    cfg.blockDim = dim3(block);
    cfg.dynamicSmemBytes = smem;
    cfg.stream = cudaStreamPerThread;
    cudaLaunchAttribute at[2];
    int na = 0;
    if (pdl) {
        at[na].id = cudaLaunchAttributeProgrammaticStreamSerialization;
        at[na].val.programmaticStreamSerializationAllowed = 1;
        na++;
    }
    (void)cluster;
    cfg.attrs = at;
    cfg.numAttrs = na;
    cudaLaunchKernelEx(&cfg, kernel, KArgs(args)...);
}

#define USE_PDL 1

extern "C" void kernel_launch(void* const* d_in, const int* in_sizes, int n_in, void* d_out, int out_size) {
    (void)in_sizes; (void)n_in; (void)out_size;
    const __nv_bfloat16* x = (const __nv_bfloat16*)d_in[0];
    const __nv_bfloat16* kc = (const __nv_bfloat16*)d_in[1];
    const __nv_bfloat16* vc = (const __nv_bfloat16*)d_in[2];
    const __nv_bfloat16* wq = (const __nv_bfloat16*)d_in[3];
    const __nv_bfloat16* wo = (const __nv_bfloat16*)d_in[4];
    const __nv_bfloat16* wg = (const __nv_bfloat16*)d_in[6];
    const __nv_bfloat16* wu = (const __nv_bfloat16*)d_in[7];
    const __nv_bfloat16* wd = (const __nv_bfloat16*)d_in[8];
    const __nv_bfloat16* c = (const __nv_bfloat16*)d_in[9];
    const __nv_bfloat16* wmod = (const __nv_bfloat16*)d_in[10];
    __nv_bfloat16* out = (__nv_bfloat16*)d_out;

    static bool init = false;
    static void *p_h, *p_o, *p_x1, *p_h2, *p_act;
    if (!init) {
        cudaFuncSetAttribute(attn_kernel, cudaFuncAttributeMaxDynamicSharedMemorySize, ATT_SMEM);
        cudaFuncSetAttribute(gemm_red_kernel<0>, cudaFuncAttributeMaxDynamicSharedMemorySize, G1_SMEM);
        cudaFuncSetAttribute(gemm_red_kernel<1>, cudaFuncAttributeMaxDynamicSharedMemorySize, G1_SMEM);
        cudaFuncSetAttribute(gateup_kernel, cudaFuncAttributeMaxDynamicSharedMemorySize, GU_SMEM);
        cudaGetSymbolAddress(&p_h, g_h);
        cudaGetSymbolAddress(&p_o, g_o);
        cudaGetSymbolAddress(&p_x1, g_x1);
        cudaGetSymbolAddress(&p_h2, g_h2);
        cudaGetSymbolAddress(&p_act, g_act);
        init = true;
    }
    const CUtensorMapSwizzle S128 = CU_TENSOR_MAP_SWIZZLE_128B, S64 = CU_TENSOR_MAP_SWIZZLE_64B;
    CUtensorMap tm_h = make_map(p_h, S_LEN, D_MODEL, 128, 64, S128);
    CUtensorMap tm_wq = make_map(wq, D_MODEL, N_HEADS * D_HEAD, 64, 64, S128);
    CUtensorMap tm_k = make_map(kc, N_HEADS * S_KV, D_HEAD, 128, 64, S128);
    CUtensorMap tm_v = make_map(vc, N_HEADS * S_KV, D_HEAD, 128, 64, S128);
    CUtensorMap tm_o = make_map(p_o, S_LEN, N_HEADS * D_HEAD, 64, 64, S128);
    CUtensorMap tm_oa = make_map(p_o, S_LEN, N_HEADS * D_HEAD, 32, 64, S128);
    CUtensorMap tm_wo = make_map(wo, N_HEADS * D_HEAD, D_MODEL, 64, 32, S64);
    CUtensorMap tm_h2 = make_map(p_h2, S_LEN, D_MODEL, 128, 64, S128);
    CUtensorMap tm_g128 = make_map(wg, D_MODEL, D_FF, 64, 64, S128);
    CUtensorMap tm_u128 = make_map(wu, D_MODEL, D_FF, 64, 64, S128);
    CUtensorMap tm_g64 = make_map(wg, D_MODEL, D_FF, 64, 32, S64);
    CUtensorMap tm_u64 = make_map(wu, D_MODEL, D_FF, 64, 32, S64);
    CUtensorMap tm_acta = make_map(p_act, S_LEN, D_FF, 32, 64, S128);
    CUtensorMap tm_wd = make_map(wd, D_FF, D_MODEL, 64, 32, S64);

    const bool pdl = USE_PDL;
    launch(mod_kernel, 120, 256, 0, 1, false, c, wmod);
    launch(ln1_kernel, 256, 256, 0, 1, pdl, x);
    launch(attn_kernel, 128, 384, ATT_SMEM, 2, pdl, tm_h, tm_wq, tm_k, tm_v, tm_o);
    launch(gemm_red_kernel<0>, 128, 288, G1_SMEM, 8, pdl, tm_oa, tm_wo, x, (__nv_bfloat16*)p_x1);
    launch(gateup_kernel, 128, 288, GU_SMEM, 1, pdl, tm_h2, tm_g128, tm_u128, tm_g64, tm_u64);
    launch(gemm_red_kernel<1>, 128, 288, G1_SMEM, 8, pdl, tm_acta, tm_wd, (const __nv_bfloat16*)p_x1, out);
}
```

```cpp
#include <cuda_runtime.h>
#include <cuda_bf16.h>
#include <cuda.h>
#include <stdint.h>

__device__ __forceinline__ uint32_t smem_u32(const void* p) { return (uint32_t)__cvta_generic_to_shared(p); }

__device__ __forceinline__ void mbar_init(uint32_t bar, uint32_t count) {
    asm volatile("mbarrier.init.shared::cta.b64 [%0], %1;" ::"r"(bar), "r"(count) : "memory");
}
__device__ __forceinline__ void mbar_expect_tx(uint32_t bar, uint32_t bytes) {
    asm volatile("mbarrier.arrive.expect_tx.shared::cta.b64 _, [%0], %1;" ::"r"(bar), "r"(bytes) : "memory");
}
__device__ __forceinline__ void mbar_arrive(uint32_t bar) {
    asm volatile("mbarrier.arrive.shared::cta.b64 _, [%0];" ::"r"(bar) : "memory");
}
__device__ __forceinline__ void mbar_arrive_cluster(uint32_t bar, uint32_t cta) {
    asm volatile(
        "{\n.reg .b32 ra;\n"
        "mapa.shared::cluster.u32 ra, %0, %1;\n"
        "mbarrier.arrive.shared::cluster.b64 _, [ra];\n}\n" ::"r"(bar), "r"(cta)
        : "memory");
}
__device__ __forceinline__ bool mbar_try_wait(uint32_t bar, uint32_t parity) {
    uint32_t ok;
    asm volatile(
        "{\n.reg .pred p;\n"
        "mbarrier.try_wait.parity.shared::cta.b64 p, [%1], %2;\n"
        "selp.u32 %0, 1, 0, p;\n}\n"
        : "=r"(ok)
        : "r"(bar), "r"(parity)
        : "memory");
    return ok != 0;
}
__device__ __forceinline__ bool mbar_try_wait_cluster(uint32_t bar, uint32_t parity) {
    uint32_t ok;
    asm volatile(
        "{\n.reg .pred p;\n"
        "mbarrier.try_wait.parity.shared::cta.b64 p, [%1], %2;\n"
        "selp.u32 %0, 1, 0, p;\n}\n"
        : "=r"(ok)
        : "r"(bar), "r"(parity)
        : "memory");
    return ok != 0;
}
__device__ volatile int g_abort = 0;
__device__ __forceinline__ void mbar_wait(uint32_t bar, uint32_t parity) {
    if (mbar_try_wait(bar, parity)) return;
    uint32_t n = 0;
    while (!mbar_try_wait(bar, parity)) {
        ++n;
        if (n > (1u << 22)) { g_abort = 1; break; }
        if ((n & 255u) == 0 && g_abort) break;
    }
}
__device__ __forceinline__ void mbar_wait_cluster(uint32_t bar, uint32_t parity) { mbar_wait(bar, parity); }
__device__ __forceinline__ void fence_mbar_init() { asm volatile("fence.mbarrier_init.release.cluster;" ::: "memory"); }
__device__ __forceinline__ void fence_proxy_async() { asm volatile("fence.proxy.async.shared::cta;" ::: "memory"); }
__device__ __forceinline__ void fence_proxy_async_all() { asm volatile("fence.proxy.async;" ::: "memory"); }
__device__ __forceinline__ void cluster_arrive() { asm volatile("barrier.cluster.arrive.release.aligned;" ::: "memory"); }
__device__ __forceinline__ void cluster_wait() { asm volatile("barrier.cluster.wait.acquire.aligned;" ::: "memory"); }
__device__ __forceinline__ void cluster_sync() { cluster_arrive(); cluster_wait(); }
__device__ __forceinline__ uint32_t cluster_ctarank() {
    uint32_t r;
    asm volatile("mov.u32 %0, %%cluster_ctarank;" : "=r"(r));
    return r;
}
__device__ __forceinline__ void bar_sync(int id, int n) { asm volatile("bar.sync %0, %1;" ::"r"(id), "r"(n) : "memory"); }
__device__ __forceinline__ void bar_arrive(int id, int n) { asm volatile("bar.arrive %0, %1;" ::"r"(id), "r"(n) : "memory"); }
__device__ __forceinline__ void pdl_wait() { asm volatile("griddepcontrol.wait;" ::: "memory"); }
__device__ __forceinline__ void pdl_launch() { asm volatile("griddepcontrol.launch_dependents;" ::: "memory"); }

__device__ __forceinline__ void tma_prefetch_desc(const CUtensorMap* m) {
    asm volatile("prefetch.tensormap [%0];" ::"l"(m) : "memory");
}
__device__ __forceinline__ void tma_load_2d(uint32_t dst, const CUtensorMap* m, int c0, int c1, uint32_t bar) {
    asm volatile(
        "cp.async.bulk.tensor.2d.shared::cluster.global.mbarrier::complete_tx::bytes [%0], [%1, {%3, %4}], [%2];"
        ::"r"(dst), "l"(m), "r"(bar), "r"(c0), "r"(c1)
        : "memory");
}
__device__ __forceinline__ void tma_load_2d_mc(uint32_t dst, const CUtensorMap* m, int c0, int c1, uint32_t bar, uint16_t mask) {
    asm volatile(
        "cp.async.bulk.tensor.2d.shared::cluster.global.mbarrier::complete_tx::bytes.multicast::cluster [%0], [%1, {%3, %4}], [%2], %5;"
        ::"r"(dst), "l"(m), "r"(bar), "r"(c0), "r"(c1), "h"(mask)
        : "memory");
}
__device__ __forceinline__ void tma_store_2d(const CUtensorMap* m, uint32_t src, int c0, int c1) {
    asm volatile("cp.async.bulk.tensor.2d.global.shared::cta.bulk_group [%0, {%2, %3}], [%1];"
                 ::"l"(m), "r"(src), "r"(c0), "r"(c1)
                 : "memory");
}
__device__ __forceinline__ void tma_store_commit() { asm volatile("cp.async.bulk.commit_group;" ::: "memory"); }
template <int N> __device__ __forceinline__ void tma_store_wait_read() {
    asm volatile("cp.async.bulk.wait_group.read %0;" ::"n"(N) : "memory");
}
template <int N> __device__ __forceinline__ void tma_store_wait() {
    asm volatile("cp.async.bulk.wait_group %0;" ::"n"(N) : "memory");
}

__device__ __forceinline__ void wgmma_fence() { asm volatile("wgmma.fence.sync.aligned;" ::: "memory"); }
__device__ __forceinline__ void wgmma_commit() { asm volatile("wgmma.commit_group.sync.aligned;" ::: "memory"); }
template <int N> __device__ __forceinline__ void wgmma_wait() {
    asm volatile("wgmma.wait_group.sync.aligned %0;" ::"n"(N) : "memory");
}
template <int R> __device__ __forceinline__ void reg_alloc() { asm volatile("setmaxnreg.inc.sync.aligned.u32 %0;" ::"n"(R)); }
template <int R> __device__ __forceinline__ void reg_dealloc() { asm volatile("setmaxnreg.dec.sync.aligned.u32 %0;" ::"n"(R)); }

template <int N> __device__ __forceinline__ void fence_regs(float (&r)[N]) {
#pragma unroll
    for (int i = 0; i < N; i++) asm volatile("" : "+f"(r[i])::"memory");
}
template <int N> __device__ __forceinline__ void fence_regs_u(uint32_t (&r)[N][4]) {
#pragma unroll
    for (int i = 0; i < N; i++) {
#pragma unroll
        for (int j = 0; j < 4; j++) asm volatile("" : "+r"(r[i][j])::"memory");
    }
}

__device__ __forceinline__ uint64_t make_desc(uint32_t addr, uint32_t lbo_bytes, uint32_t sbo_bytes, uint32_t swz) {
    return (uint64_t)((addr & 0x3FFFF) >> 4) | ((uint64_t)(lbo_bytes >> 4) << 16) | ((uint64_t)(sbo_bytes >> 4) << 32) |
           ((uint64_t)swz << 62);
}

__device__ __forceinline__ uint32_t pack_bf16(float lo, float hi) {
    uint32_t r;
    asm("cvt.rn.bf16x2.f32 %0, %1, %2;" : "=r"(r) : "f"(hi), "f"(lo));
    return r;
}
__device__ __forceinline__ float bf16_round(float x) { return __bfloat162float(__float2bfloat16_rn(x)); }
__device__ __forceinline__ float bf16lo(uint32_t v) { return __uint_as_float(v << 16); }
__device__ __forceinline__ float bf16hi(uint32_t v) { return __uint_as_float(v & 0xffff0000u); }
__device__ __forceinline__ float ex2(float x) {
    float y;
    asm("ex2.approx.ftz.f32 %0, %1;" : "=f"(y) : "f"(x));
    return y;
}
__device__ __forceinline__ void stmatrix_x4(uint32_t addr, uint32_t r0, uint32_t r1, uint32_t r2, uint32_t r3) {
    asm volatile("stmatrix.sync.aligned.m8n8.x4.shared.b16 [%0], {%1, %2, %3, %4};" ::"r"(addr), "r"(r0), "r"(r1), "r"(r2), "r"(r3)
                 : "memory");
}
__device__ __forceinline__ uint32_t mapa(uint32_t addr, uint32_t cta) {
    uint32_t r;
    asm volatile("mapa.shared::cluster.u32 %0, %1, %2;" : "=r"(r) : "r"(addr), "r"(cta));
    return r;
}
__device__ __forceinline__ void st_cluster_v2(uint32_t addr, float a, float b) {
    asm volatile("st.shared::cluster.v2.f32 [%0], {%1, %2};" ::"r"(addr), "f"(a), "f"(b) : "memory");
}
__device__ __forceinline__ void wgmma_ss_n256_t1(float (&d)[128], uint64_t descA, uint64_t descB, int scaleD) {
    asm volatile("{\n.reg .pred p;\n"
        "setp.ne.b32 p, %130, 0;\n"
        "wgmma.mma_async.sync.aligned.m64n256k16.f32.bf16.bf16 "
        "{%0, %1, %2, %3, %4, %5, %6, %7, %8, %9, %10, %11, %12, %13, %14, %15, "
        "%16, %17, %18, %19, %20, %21, %22, %23, %24, %25, %26, %27, %28, %29, %30, %31, "
        "%32, %33, %34, %35, %36, %37, %38, %39, %40, %41, %42, %43, %44, %45, %46, %47, "
        "%48, %49, %50, %51, %52, %53, %54, %55, %56, %57, %58, %59, %60, %61, %62, %63, "
        "%64, %65, %66, %67, %68, %69, %70, %71, %72, %73, %74, %75, %76, %77, %78, %79, "
        "%80, %81, %82, %83, %84, %85, %86, %87, %88, %89, %90, %91, %92, %93, %94, %95, "
        "%96, %97, %98, %99, %100, %101, %102, %103, %104, %105, %106, %107, %108, %109, %110, %111, "
        "%112, %113, %114, %115, %116, %117, %118, %119, %120, %121, %122, %123, %124, %125, %126, %127}, "
        "%128, %129, p, 1, 1, 0, 1;\n}\n"
        :
          "+f"(d[0]), "+f"(d[1]), "+f"(d[2]), "+f"(d[3]), "+f"(d[4]), "+f"(d[5]), "+f"(d[6]), "+f"(d[7]),
          "+f"(d[8]), "+f"(d[9]), "+f"(d[10]), "+f"(d[11]), "+f"(d[12]), "+f"(d[13]), "+f"(d[14]), "+f"(d[15]),
          "+f"(d[16]), "+f"(d[17]), "+f"(d[18]), "+f"(d[19]), "+f"(d[20]), "+f"(d[21]), "+f"(d[22]), "+f"(d[23]),
          "+f"(d[24]), "+f"(d[25]), "+f"(d[26]), "+f"(d[27]), "+f"(d[28]), "+f"(d[29]), "+f"(d[30]), "+f"(d[31]),
          "+f"(d[32]), "+f"(d[33]), "+f"(d[34]), "+f"(d[35]), "+f"(d[36]), "+f"(d[37]), "+f"(d[38]), "+f"(d[39]),
          "+f"(d[40]), "+f"(d[41]), "+f"(d[42]), "+f"(d[43]), "+f"(d[44]), "+f"(d[45]), "+f"(d[46]), "+f"(d[47]),
          "+f"(d[48]), "+f"(d[49]), "+f"(d[50]), "+f"(d[51]), "+f"(d[52]), "+f"(d[53]), "+f"(d[54]), "+f"(d[55]),
          "+f"(d[56]), "+f"(d[57]), "+f"(d[58]), "+f"(d[59]), "+f"(d[60]), "+f"(d[61]), "+f"(d[62]), "+f"(d[63]),
          "+f"(d[64]), "+f"(d[65]), "+f"(d[66]), "+f"(d[67]), "+f"(d[68]), "+f"(d[69]), "+f"(d[70]), "+f"(d[71]),
          "+f"(d[72]), "+f"(d[73]), "+f"(d[74]), "+f"(d[75]), "+f"(d[76]), "+f"(d[77]), "+f"(d[78]), "+f"(d[79]),
          "+f"(d[80]), "+f"(d[81]), "+f"(d[82]), "+f"(d[83]), "+f"(d[84]), "+f"(d[85]), "+f"(d[86]), "+f"(d[87]),
          "+f"(d[88]), "+f"(d[89]), "+f"(d[90]), "+f"(d[91]), "+f"(d[92]), "+f"(d[93]), "+f"(d[94]), "+f"(d[95]),
          "+f"(d[96]), "+f"(d[97]), "+f"(d[98]), "+f"(d[99]), "+f"(d[100]), "+f"(d[101]), "+f"(d[102]), "+f"(d[103]),
          "+f"(d[104]), "+f"(d[105]), "+f"(d[106]), "+f"(d[107]), "+f"(d[108]), "+f"(d[109]), "+f"(d[110]), "+f"(d[111]),
          "+f"(d[112]), "+f"(d[113]), "+f"(d[114]), "+f"(d[115]), "+f"(d[116]), "+f"(d[117]), "+f"(d[118]), "+f"(d[119]),
          "+f"(d[120]), "+f"(d[121]), "+f"(d[122]), "+f"(d[123]), "+f"(d[124]), "+f"(d[125]), "+f"(d[126]), "+f"(d[127])
        : "l"(descA), "l"(descB), "r"(scaleD));
}

__device__ __forceinline__ void wgmma_rs_n128_t0(float (&d)[64], const uint32_t (&a)[4], uint64_t descB, int scaleD) {
    asm volatile("{\n.reg .pred p;\n"
        "setp.ne.b32 p, %69, 0;\n"
        "wgmma.mma_async.sync.aligned.m64n128k16.f32.bf16.bf16 "
        "{%0, %1, %2, %3, %4, %5, %6, %7, %8, %9, %10, %11, %12, %13, %14, %15, "
        "%16, %17, %18, %19, %20, %21, %22, %23, %24, %25, %26, %27, %28, %29, %30, %31, "
        "%32, %33, %34, %35, %36, %37, %38, %39, %40, %41, %42, %43, %44, %45, %46, %47, "
        "%48, %49, %50, %51, %52, %53, %54, %55, %56, %57, %58, %59, %60, %61, %62, %63}, "
        "{%64, %65, %66, %67}, %68, p, 1, 1, 0;\n}\n"
        :
          "+f"(d[0]), "+f"(d[1]), "+f"(d[2]), "+f"(d[3]), "+f"(d[4]), "+f"(d[5]), "+f"(d[6]), "+f"(d[7]),
          "+f"(d[8]), "+f"(d[9]), "+f"(d[10]), "+f"(d[11]), "+f"(d[12]), "+f"(d[13]), "+f"(d[14]), "+f"(d[15]),
          "+f"(d[16]), "+f"(d[17]), "+f"(d[18]), "+f"(d[19]), "+f"(d[20]), "+f"(d[21]), "+f"(d[22]), "+f"(d[23]),
          "+f"(d[24]), "+f"(d[25]), "+f"(d[26]), "+f"(d[27]), "+f"(d[28]), "+f"(d[29]), "+f"(d[30]), "+f"(d[31]),
          "+f"(d[32]), "+f"(d[33]), "+f"(d[34]), "+f"(d[35]), "+f"(d[36]), "+f"(d[37]), "+f"(d[38]), "+f"(d[39]),
          "+f"(d[40]), "+f"(d[41]), "+f"(d[42]), "+f"(d[43]), "+f"(d[44]), "+f"(d[45]), "+f"(d[46]), "+f"(d[47]),
          "+f"(d[48]), "+f"(d[49]), "+f"(d[50]), "+f"(d[51]), "+f"(d[52]), "+f"(d[53]), "+f"(d[54]), "+f"(d[55]),
          "+f"(d[56]), "+f"(d[57]), "+f"(d[58]), "+f"(d[59]), "+f"(d[60]), "+f"(d[61]), "+f"(d[62]), "+f"(d[63])
        : "r"(a[0]), "r"(a[1]), "r"(a[2]), "r"(a[3]), "l"(descB), "r"(scaleD));
}

__device__ __forceinline__ void wgmma_rs_n128_t1(float (&d)[64], const uint32_t (&a)[4], uint64_t descB, int scaleD) {
    asm volatile("{\n.reg .pred p;\n"
        "setp.ne.b32 p, %69, 0;\n"
        "wgmma.mma_async.sync.aligned.m64n128k16.f32.bf16.bf16 "
        "{%0, %1, %2, %3, %4, %5, %6, %7, %8, %9, %10, %11, %12, %13, %14, %15, "
        "%16, %17, %18, %19, %20, %21, %22, %23, %24, %25, %26, %27, %28, %29, %30, %31, "
        "%32, %33, %34, %35, %36, %37, %38, %39, %40, %41, %42, %43, %44, %45, %46, %47, "
        "%48, %49, %50, %51, %52, %53, %54, %55, %56, %57, %58, %59, %60, %61, %62, %63}, "
        "{%64, %65, %66, %67}, %68, p, 1, 1, 1;\n}\n"
        :
          "+f"(d[0]), "+f"(d[1]), "+f"(d[2]), "+f"(d[3]), "+f"(d[4]), "+f"(d[5]), "+f"(d[6]), "+f"(d[7]),
          "+f"(d[8]), "+f"(d[9]), "+f"(d[10]), "+f"(d[11]), "+f"(d[12]), "+f"(d[13]), "+f"(d[14]), "+f"(d[15]),
          "+f"(d[16]), "+f"(d[17]), "+f"(d[18]), "+f"(d[19]), "+f"(d[20]), "+f"(d[21]), "+f"(d[22]), "+f"(d[23]),
          "+f"(d[24]), "+f"(d[25]), "+f"(d[26]), "+f"(d[27]), "+f"(d[28]), "+f"(d[29]), "+f"(d[30]), "+f"(d[31]),
          "+f"(d[32]), "+f"(d[33]), "+f"(d[34]), "+f"(d[35]), "+f"(d[36]), "+f"(d[37]), "+f"(d[38]), "+f"(d[39]),
          "+f"(d[40]), "+f"(d[41]), "+f"(d[42]), "+f"(d[43]), "+f"(d[44]), "+f"(d[45]), "+f"(d[46]), "+f"(d[47]),
          "+f"(d[48]), "+f"(d[49]), "+f"(d[50]), "+f"(d[51]), "+f"(d[52]), "+f"(d[53]), "+f"(d[54]), "+f"(d[55]),
          "+f"(d[56]), "+f"(d[57]), "+f"(d[58]), "+f"(d[59]), "+f"(d[60]), "+f"(d[61]), "+f"(d[62]), "+f"(d[63])
        : "r"(a[0]), "r"(a[1]), "r"(a[2]), "r"(a[3]), "l"(descB), "r"(scaleD));
}

__device__ __forceinline__ void wgmma_ss_n160_t1(float (&d)[80], uint64_t descA, uint64_t descB, int scaleD) {
    asm volatile("{\n.reg .pred p;\n"
        "setp.ne.b32 p, %82, 0;\n"
        "wgmma.mma_async.sync.aligned.m64n160k16.f32.bf16.bf16 "
        "{%0, %1, %2, %3, %4, %5, %6, %7, %8, %9, %10, %11, %12, %13, %14, %15, "
        "%16, %17, %18, %19, %20, %21, %22, %23, %24, %25, %26, %27, %28, %29, %30, %31, "
        "%32, %33, %34, %35, %36, %37, %38, %39, %40, %41, %42, %43, %44, %45, %46, %47, "
        "%48, %49, %50, %51, %52, %53, %54, %55, %56, %57, %58, %59, %60, %61, %62, %63, "
        "%64, %65, %66, %67, %68, %69, %70, %71, %72, %73, %74, %75, %76, %77, %78, %79}, "
        "%80, %81, p, 1, 1, 0, 1;\n}\n"
        :
          "+f"(d[0]), "+f"(d[1]), "+f"(d[2]), "+f"(d[3]), "+f"(d[4]), "+f"(d[5]), "+f"(d[6]), "+f"(d[7]),
          "+f"(d[8]), "+f"(d[9]), "+f"(d[10]), "+f"(d[11]), "+f"(d[12]), "+f"(d[13]), "+f"(d[14]), "+f"(d[15]),
          "+f"(d[16]), "+f"(d[17]), "+f"(d[18]), "+f"(d[19]), "+f"(d[20]), "+f"(d[21]), "+f"(d[22]), "+f"(d[23]),
          "+f"(d[24]), "+f"(d[25]), "+f"(d[26]), "+f"(d[27]), "+f"(d[28]), "+f"(d[29]), "+f"(d[30]), "+f"(d[31]),
          "+f"(d[32]), "+f"(d[33]), "+f"(d[34]), "+f"(d[35]), "+f"(d[36]), "+f"(d[37]), "+f"(d[38]), "+f"(d[39]),
          "+f"(d[40]), "+f"(d[41]), "+f"(d[42]), "+f"(d[43]), "+f"(d[44]), "+f"(d[45]), "+f"(d[46]), "+f"(d[47]),
          "+f"(d[48]), "+f"(d[49]), "+f"(d[50]), "+f"(d[51]), "+f"(d[52]), "+f"(d[53]), "+f"(d[54]), "+f"(d[55]),
          "+f"(d[56]), "+f"(d[57]), "+f"(d[58]), "+f"(d[59]), "+f"(d[60]), "+f"(d[61]), "+f"(d[62]), "+f"(d[63]),
          "+f"(d[64]), "+f"(d[65]), "+f"(d[66]), "+f"(d[67]), "+f"(d[68]), "+f"(d[69]), "+f"(d[70]), "+f"(d[71]),
          "+f"(d[72]), "+f"(d[73]), "+f"(d[74]), "+f"(d[75]), "+f"(d[76]), "+f"(d[77]), "+f"(d[78]), "+f"(d[79])
        : "l"(descA), "l"(descB), "r"(scaleD));
}

__device__ __forceinline__ void wgmma_ss_n184_t1(float (&d)[92], uint64_t descA, uint64_t descB, int scaleD) {
    asm volatile("{\n.reg .pred p;\n"
        "setp.ne.b32 p, %94, 0;\n"
        "wgmma.mma_async.sync.aligned.m64n184k16.f32.bf16.bf16 "
        "{%0, %1, %2, %3, %4, %5, %6, %7, %8, %9, %10, %11, %12, %13, %14, %15, "
        "%16, %17, %18, %19, %20, %21, %22, %23, %24, %25, %26, %27, %28, %29, %30, %31, "
        "%32, %33, %34, %35, %36, %37, %38, %39, %40, %41, %42, %43, %44, %45, %46, %47, "
        "%48, %49, %50, %51, %52, %53, %54, %55, %56, %57, %58, %59, %60, %61, %62, %63, "
        "%64, %65, %66, %67, %68, %69, %70, %71, %72, %73, %74, %75, %76, %77, %78, %79, "
        "%80, %81, %82, %83, %84, %85, %86, %87, %88, %89, %90, %91}, "
        "%92, %93, p, 1, 1, 0, 1;\n}\n"
        :
          "+f"(d[0]), "+f"(d[1]), "+f"(d[2]), "+f"(d[3]), "+f"(d[4]), "+f"(d[5]), "+f"(d[6]), "+f"(d[7]),
          "+f"(d[8]), "+f"(d[9]), "+f"(d[10]), "+f"(d[11]), "+f"(d[12]), "+f"(d[13]), "+f"(d[14]), "+f"(d[15]),
          "+f"(d[16]), "+f"(d[17]), "+f"(d[18]), "+f"(d[19]), "+f"(d[20]), "+f"(d[21]), "+f"(d[22]), "+f"(d[23]),
          "+f"(d[24]), "+f"(d[25]), "+f"(d[26]), "+f"(d[27]), "+f"(d[28]), "+f"(d[29]), "+f"(d[30]), "+f"(d[31]),
          "+f"(d[32]), "+f"(d[33]), "+f"(d[34]), "+f"(d[35]), "+f"(d[36]), "+f"(d[37]), "+f"(d[38]), "+f"(d[39]),
          "+f"(d[40]), "+f"(d[41]), "+f"(d[42]), "+f"(d[43]), "+f"(d[44]), "+f"(d[45]), "+f"(d[46]), "+f"(d[47]),
          "+f"(d[48]), "+f"(d[49]), "+f"(d[50]), "+f"(d[51]), "+f"(d[52]), "+f"(d[53]), "+f"(d[54]), "+f"(d[55]),
          "+f"(d[56]), "+f"(d[57]), "+f"(d[58]), "+f"(d[59]), "+f"(d[60]), "+f"(d[61]), "+f"(d[62]), "+f"(d[63]),
          "+f"(d[64]), "+f"(d[65]), "+f"(d[66]), "+f"(d[67]), "+f"(d[68]), "+f"(d[69]), "+f"(d[70]), "+f"(d[71]),
          "+f"(d[72]), "+f"(d[73]), "+f"(d[74]), "+f"(d[75]), "+f"(d[76]), "+f"(d[77]), "+f"(d[78]), "+f"(d[79]),
          "+f"(d[80]), "+f"(d[81]), "+f"(d[82]), "+f"(d[83]), "+f"(d[84]), "+f"(d[85]), "+f"(d[86]), "+f"(d[87]),
          "+f"(d[88]), "+f"(d[89]), "+f"(d[90]), "+f"(d[91])
        : "l"(descA), "l"(descB), "r"(scaleD));
}

__device__ __forceinline__ void wgmma_ss_n192_t1(float (&d)[96], uint64_t descA, uint64_t descB, int scaleD) {
    asm volatile("{\n.reg .pred p;\n"
        "setp.ne.b32 p, %98, 0;\n"
        "wgmma.mma_async.sync.aligned.m64n192k16.f32.bf16.bf16 "
        "{%0, %1, %2, %3, %4, %5, %6, %7, %8, %9, %10, %11, %12, %13, %14, %15, "
        "%16, %17, %18, %19, %20, %21, %22, %23, %24, %25, %26, %27, %28, %29, %30, %31, "
        "%32, %33, %34, %35, %36, %37, %38, %39, %40, %41, %42, %43, %44, %45, %46, %47, "
        "%48, %49, %50, %51, %52, %53, %54, %55, %56, %57, %58, %59, %60, %61, %62, %63, "
        "%64, %65, %66, %67, %68, %69, %70, %71, %72, %73, %74, %75, %76, %77, %78, %79, "
        "%80, %81, %82, %83, %84, %85, %86, %87, %88, %89, %90, %91, %92, %93, %94, %95}, "
        "%96, %97, p, 1, 1, 0, 1;\n}\n"
        :
          "+f"(d[0]), "+f"(d[1]), "+f"(d[2]), "+f"(d[3]), "+f"(d[4]), "+f"(d[5]), "+f"(d[6]), "+f"(d[7]),
          "+f"(d[8]), "+f"(d[9]), "+f"(d[10]), "+f"(d[11]), "+f"(d[12]), "+f"(d[13]), "+f"(d[14]), "+f"(d[15]),
          "+f"(d[16]), "+f"(d[17]), "+f"(d[18]), "+f"(d[19]), "+f"(d[20]), "+f"(d[21]), "+f"(d[22]), "+f"(d[23]),
          "+f"(d[24]), "+f"(d[25]), "+f"(d[26]), "+f"(d[27]), "+f"(d[28]), "+f"(d[29]), "+f"(d[30]), "+f"(d[31]),
          "+f"(d[32]), "+f"(d[33]), "+f"(d[34]), "+f"(d[35]), "+f"(d[36]), "+f"(d[37]), "+f"(d[38]), "+f"(d[39]),
          "+f"(d[40]), "+f"(d[41]), "+f"(d[42]), "+f"(d[43]), "+f"(d[44]), "+f"(d[45]), "+f"(d[46]), "+f"(d[47]),
          "+f"(d[48]), "+f"(d[49]), "+f"(d[50]), "+f"(d[51]), "+f"(d[52]), "+f"(d[53]), "+f"(d[54]), "+f"(d[55]),
          "+f"(d[56]), "+f"(d[57]), "+f"(d[58]), "+f"(d[59]), "+f"(d[60]), "+f"(d[61]), "+f"(d[62]), "+f"(d[63]),
          "+f"(d[64]), "+f"(d[65]), "+f"(d[66]), "+f"(d[67]), "+f"(d[68]), "+f"(d[69]), "+f"(d[70]), "+f"(d[71]),
          "+f"(d[72]), "+f"(d[73]), "+f"(d[74]), "+f"(d[75]), "+f"(d[76]), "+f"(d[77]), "+f"(d[78]), "+f"(d[79]),
          "+f"(d[80]), "+f"(d[81]), "+f"(d[82]), "+f"(d[83]), "+f"(d[84]), "+f"(d[85]), "+f"(d[86]), "+f"(d[87]),
          "+f"(d[88]), "+f"(d[89]), "+f"(d[90]), "+f"(d[91]), "+f"(d[92]), "+f"(d[93]), "+f"(d[94]), "+f"(d[95])
        : "l"(descA), "l"(descB), "r"(scaleD));
}

__device__ __forceinline__ void wgmma_ss_n128_t1(float (&d)[64], uint64_t descA, uint64_t descB, int scaleD) {
    asm volatile("{\n.reg .pred p;\n"
        "setp.ne.b32 p, %66, 0;\n"
        "wgmma.mma_async.sync.aligned.m64n128k16.f32.bf16.bf16 "
        "{%0, %1, %2, %3, %4, %5, %6, %7, %8, %9, %10, %11, %12, %13, %14, %15, "
        "%16, %17, %18, %19, %20, %21, %22, %23, %24, %25, %26, %27, %28, %29, %30, %31, "
        "%32, %33, %34, %35, %36, %37, %38, %39, %40, %41, %42, %43, %44, %45, %46, %47, "
        "%48, %49, %50, %51, %52, %53, %54, %55, %56, %57, %58, %59, %60, %61, %62, %63}, "
        "%64, %65, p, 1, 1, 0, 1;\n}\n"
        :
          "+f"(d[0]), "+f"(d[1]), "+f"(d[2]), "+f"(d[3]), "+f"(d[4]), "+f"(d[5]), "+f"(d[6]), "+f"(d[7]),
          "+f"(d[8]), "+f"(d[9]), "+f"(d[10]), "+f"(d[11]), "+f"(d[12]), "+f"(d[13]), "+f"(d[14]), "+f"(d[15]),
          "+f"(d[16]), "+f"(d[17]), "+f"(d[18]), "+f"(d[19]), "+f"(d[20]), "+f"(d[21]), "+f"(d[22]), "+f"(d[23]),
          "+f"(d[24]), "+f"(d[25]), "+f"(d[26]), "+f"(d[27]), "+f"(d[28]), "+f"(d[29]), "+f"(d[30]), "+f"(d[31]),
          "+f"(d[32]), "+f"(d[33]), "+f"(d[34]), "+f"(d[35]), "+f"(d[36]), "+f"(d[37]), "+f"(d[38]), "+f"(d[39]),
          "+f"(d[40]), "+f"(d[41]), "+f"(d[42]), "+f"(d[43]), "+f"(d[44]), "+f"(d[45]), "+f"(d[46]), "+f"(d[47]),
          "+f"(d[48]), "+f"(d[49]), "+f"(d[50]), "+f"(d[51]), "+f"(d[52]), "+f"(d[53]), "+f"(d[54]), "+f"(d[55]),
          "+f"(d[56]), "+f"(d[57]), "+f"(d[58]), "+f"(d[59]), "+f"(d[60]), "+f"(d[61]), "+f"(d[62]), "+f"(d[63])
        : "l"(descA), "l"(descB), "r"(scaleD));
}

constexpr int S_LEN = 2048;
constexpr int D_MODEL = 640;
constexpr int N_HEADS = 32;
constexpr int D_HEAD = 128;
constexpr int S_KV = 2048;
constexpr int WIN = 512;
constexpr int D_FF = 1728;
constexpr float LN_EPS = 1e-5f;

__device__ float g_mod[6 * D_MODEL];
__device__ __align__(1024) __nv_bfloat16 g_h[S_LEN * D_MODEL];
__device__ __align__(1024) __nv_bfloat16 g_o[S_LEN * N_HEADS * D_HEAD];
__device__ __align__(1024) __nv_bfloat16 g_x1[S_LEN * D_MODEL];
__device__ __align__(1024) __nv_bfloat16 g_h2[S_LEN * D_MODEL];
__device__ __align__(1024) __nv_bfloat16 g_act[S_LEN * D_FF];

__global__ void __launch_bounds__(256) mod_kernel(const __nv_bfloat16* __restrict__ c, const __nv_bfloat16* __restrict__ w_mod) {
    __shared__ float red[8][32];
    pdl_launch();
    const int warp = threadIdx.x >> 5, lane = threadIdx.x & 31;
    const int col0 = blockIdx.x * 32 + (lane & 3) * 8;
    float acc[8];
#pragma unroll
    for (int i = 0; i < 8; i++) acc[i] = 0.f;
    uint4 w[10];
    float s[10];
#pragma unroll
    for (int i = 0; i < 10; i++) {
        int k = warp * 80 + i * 8 + (lane >> 2);
        w[i] = __ldg(reinterpret_cast<const uint4*>(w_mod + (size_t)k * (6 * D_MODEL) + col0));
        float cv = __bfloat162float(c[k]);
        s[i] = bf16_round(cv / (1.f + __expf(-cv)));
    }
#pragma unroll
    for (int i = 0; i < 10; i++) {
        acc[0] += s[i] * bf16lo(w[i].x); acc[1] += s[i] * bf16hi(w[i].x);
        acc[2] += s[i] * bf16lo(w[i].y); acc[3] += s[i] * bf16hi(w[i].y);
        acc[4] += s[i] * bf16lo(w[i].z); acc[5] += s[i] * bf16hi(w[i].z);
        acc[6] += s[i] * bf16lo(w[i].w); acc[7] += s[i] * bf16hi(w[i].w);
    }
#pragma unroll
    for (int i = 0; i < 8; i++) {
        acc[i] += __shfl_xor_sync(0xffffffffu, acc[i], 4);
        acc[i] += __shfl_xor_sync(0xffffffffu, acc[i], 8);
        acc[i] += __shfl_xor_sync(0xffffffffu, acc[i], 16);
    }
    if (lane < 4) {
#pragma unroll
        for (int i = 0; i < 8; i++) red[warp][lane * 8 + i] = acc[i];
    }
    __syncthreads();
    if (threadIdx.x < 32) {
        float v = 0.f;
#pragma unroll
        for (int i = 0; i < 8; i++) v += red[i][threadIdx.x];
        g_mod[blockIdx.x * 32 + threadIdx.x] = bf16_round(v);
    }
}

__global__ void __launch_bounds__(256) ln1_kernel(const __nv_bfloat16* __restrict__ x) {
    pdl_launch();
    const int warp = threadIdx.x >> 5, lane = threadIdx.x & 31;
    const int row = blockIdx.x * 8 + warp;
    float v[20];
#pragma unroll
    for (int i = 0; i < 5; i++) {
        uint2 u = __ldg(reinterpret_cast<const uint2*>(x + (size_t)row * D_MODEL + (lane + 32 * i) * 4));
        v[4 * i] = bf16lo(u.x); v[4 * i + 1] = bf16hi(u.x); v[4 * i + 2] = bf16lo(u.y); v[4 * i + 3] = bf16hi(u.y);
    }
    float s = 0.f;
#pragma unroll
    for (int i = 0; i < 20; i++) s += v[i];
#pragma unroll
    for (int o = 16; o > 0; o >>= 1) s += __shfl_xor_sync(0xffffffffu, s, o);
    const float mean = s * (1.f / D_MODEL);
    float q = 0.f;
#pragma unroll
    for (int i = 0; i < 20; i++) { float d = v[i] - mean; q += d * d; }
#pragma unroll
    for (int o = 16; o > 0; o >>= 1) q += __shfl_xor_sync(0xffffffffu, q, o);
    const float rstd = rsqrtf(q * (1.f / D_MODEL) + LN_EPS);
    pdl_wait();
#pragma unroll
    for (int i = 0; i < 5; i++) {
        int c0 = (lane + 32 * i) * 4;
        float4 sa = *reinterpret_cast<const float4*>(g_mod + c0);
        float4 ca = *reinterpret_cast<const float4*>(g_mod + D_MODEL + c0);
        float o0 = (v[4 * i] - mean) * rstd * bf16_round(1.f + ca.x) + sa.x;
        float o1 = (v[4 * i + 1] - mean) * rstd * bf16_round(1.f + ca.y) + sa.y;
        float o2 = (v[4 * i + 2] - mean) * rstd * bf16_round(1.f + ca.z) + sa.z;
        float o3 = (v[4 * i + 3] - mean) * rstd * bf16_round(1.f + ca.w) + sa.w;
        uint2 u; u.x = pack_bf16(o0, o1); u.y = pack_bf16(o2, o3);
        *reinterpret_cast<uint2*>(g_h + (size_t)row * D_MODEL + c0) = u;
    }
}

constexpr int ATT_STAGES = 6;
constexpr int ATT_STAGE_BYTES = 32768;
constexpr int ATT_SMEM = ATT_STAGES * ATT_STAGE_BYTES + 2 * 16384 + 1024 + 256;

__global__ void __cluster_dims__(2, 1, 1) __launch_bounds__(384, 1)
attn_kernel(const __grid_constant__ CUtensorMap tm_h, const __grid_constant__ CUtensorMap tm_wq,
            const __grid_constant__ CUtensorMap tm_k, const __grid_constant__ CUtensorMap tm_v,
            const __grid_constant__ CUtensorMap tm_o) {
    extern __shared__ uint8_t smem_raw[];
    const uint32_t base = (smem_u32(smem_raw) + 1023u) & ~1023u;
    const uint32_t ring = base;
    const uint32_t park = base + ATT_STAGES * ATT_STAGE_BYTES;
    const uint32_t bars = park + 2 * 16384;
    const uint32_t cta_rank = cluster_ctarank();
    const int cluster_id = blockIdx.x >> 1;
    const int qpair = cluster_id & 7, hgroup = cluster_id >> 3;
    const int q0 = (qpair * 2 + (int)cta_rank) * 128;
    const int wg = threadIdx.x >> 7;

    if (threadIdx.x == 0) {
        for (int i = 0; i < ATT_STAGES; i++) {
            mbar_init(bars + 8 * i, 1);
            mbar_init(bars + 8 * (ATT_STAGES + i), 4);
        }
        fence_mbar_init();
    }
    __syncthreads();
    cluster_sync();
    pdl_launch();

    if (wg == 2) {
        reg_dealloc<24>();
        if (threadIdx.x == 256) {
            tma_prefetch_desc(&tm_h); tma_prefetch_desc(&tm_wq); tma_prefetch_desc(&tm_k); tma_prefetch_desc(&tm_v);
            uint32_t st = 0, ph = 1;
            auto acquire = [&]() -> uint32_t {
                mbar_wait_cluster(bars + 8 * (ATT_STAGES + st), ph);
                mbar_expect_tx(bars + 8 * st, ATT_STAGE_BYTES);
                return ring + st * ATT_STAGE_BYTES;
            };
            auto advance = [&]() { if (++st == ATT_STAGES) { st = 0; ph ^= 1; } };
            pdl_wait();
            for (int hp = 0; hp < 2; hp++) {
                const int head0 = hgroup * 4 + hp * 2;
                for (int kk2 = 0; kk2 < 5; kk2++) {
                    uint32_t dst = acquire();
                    tma_load_2d(dst, &tm_h, (2 * kk2) * 64, q0, bars + 8 * st);
                    tma_load_2d(dst + 16384, &tm_h, (2 * kk2 + 1) * 64, q0, bars + 8 * st);
                    advance();
                    for (int u = 0; u < 2; u++) {
                        dst = acquire();
                        const int kb = 2 * kk2 + u;
#pragma unroll
                        for (int c = 0; c < 2; c++) {
                            const int chunk = 2 * (int)cta_rank + c;
                            tma_load_2d_mc(dst + chunk * 8192, &tm_wq, head0 * 128 + chunk * 64, kb * 64, bars + 8 * st, 3);
                        }
                        advance();
                    }
                }
                for (int t = 0; t <= 8; t++) {
                    if (t < 8) {
                        uint32_t dst = acquire();
                        const int row = (head0 + (t >> 2)) * S_KV + (S_KV - WIN) + (t & 3) * 128;
                        tma_load_2d_mc(dst + cta_rank * 16384, &tm_k, cta_rank * 64, row, bars + 8 * st, 3);
                        advance();
                    }
                    if (t > 0) {
                        uint32_t dst = acquire();
                        const int tv = t - 1;
                        const int row = (head0 + (tv >> 2)) * S_KV + (S_KV - WIN) + (tv & 3) * 128;
                        tma_load_2d_mc(dst + cta_rank * 16384, &tm_v, cta_rank * 64, row, bars + 8 * st, 3);
                        advance();
                    }
                }
            }
        }
        __syncwarp();
        asm volatile("barrier.cluster.arrive.release.aligned; // producer\n barrier.cluster.wait.acquire.aligned;" ::: "memory");
    } else {
        reg_alloc<240>();
        const int tid = threadIdx.x & 127;
        const int warp = tid >> 5, lane = tid & 31;
        const uint32_t mypark = park + wg * 16384;
        const float cscale = 0.08838834764831845f * 1.4426950408889634f;
        uint32_t st = 0, ph = 0;
        auto wait_full = [&]() -> uint32_t {
            mbar_wait(bars + 8 * st, ph);
            return ring + st * ATT_STAGE_BYTES;
        };
        auto release = [&](uint32_t s) {
            if (tid == 0) mbar_arrive_cluster(bars + 8 * (ATT_STAGES + s), 0);
            if (tid == 32) mbar_arrive_cluster(bars + 8 * (ATT_STAGES + s), 1);
        };
        auto advance = [&]() { if (++st == ATT_STAGES) { st = 0; ph ^= 1; } };

        for (int hp = 0; hp < 2; hp++) {
            const int head0 = hgroup * 4 + hp * 2;
            uint32_t q[8][4];
            {
                float acc[128];
#pragma unroll
                for (int i = 0; i < 128; i++) acc[i] = 0.f;
                for (int kk2 = 0; kk2 < 5; kk2++) {
                    const uint32_t hbuf = wait_full();
                    const uint32_t sth = st;
                    advance();
#pragma unroll
                    for (int u = 0; u < 2; u++) {
                        const uint32_t wbuf = wait_full();
                        const uint32_t stw = st;
                        advance();
                        wgmma_fence();
#pragma unroll
                        for (int k = 0; k < 4; k++) {
                            uint64_t da = make_desc(hbuf + u * 16384 + wg * 8192 + k * 32, 16, 1024, 1);
                            uint64_t db = make_desc(wbuf + k * 2048, 8192, 1024, 1);
                            wgmma_ss_n256_t1(acc, da, db, (kk2 | u | k) != 0);
                        }
                        wgmma_commit();
                        wgmma_wait<0>();
                        release(stw);
                    }
                    release(sth);
                }
                fence_regs(acc);
                if (tid == 0) tma_store_wait_read<0>();
                bar_sync(1 + wg, 128);
#pragma unroll
                for (int i = 0; i < 8; i++) {
                    q[i][0] = pack_bf16(acc[8 * i + 0], acc[8 * i + 1]);
                    q[i][1] = pack_bf16(acc[8 * i + 2], acc[8 * i + 3]);
                    q[i][2] = pack_bf16(acc[8 * i + 4], acc[8 * i + 5]);
                    q[i][3] = pack_bf16(acc[8 * i + 6], acc[8 * i + 7]);
                    uint32_t b0 = pack_bf16(acc[64 + 8 * i + 0], acc[64 + 8 * i + 1]);
                    uint32_t b1 = pack_bf16(acc[64 + 8 * i + 2], acc[64 + 8 * i + 3]);
                    uint32_t b2 = pack_bf16(acc[64 + 8 * i + 4], acc[64 + 8 * i + 5]);
                    uint32_t b3 = pack_bf16(acc[64 + 8 * i + 6], acc[64 + 8 * i + 7]);
                    asm volatile("st.shared.v4.b32 [%0], {%1, %2, %3, %4};" ::"r"(mypark + (i * 128 + tid) * 16), "r"(b0), "r"(b1),
                                 "r"(b2), "r"(b3) : "memory");
                }
            }
            float o[64], s[64];
            uint32_t p[8][4];
            float m0, m1, l0, l1, a0, a1, lo0, lo1;
#pragma unroll
            for (int i = 0; i < 64; i++) { o[i] = 0.f; s[i] = 0.f; }

            auto issue_s = [&]() -> uint32_t {
                const uint32_t kbuf = wait_full();
                const uint32_t stk = st;
                advance();
                wgmma_fence();
#pragma unroll
                for (int k = 0; k < 8; k++) {
                    uint64_t db = make_desc(kbuf + (k >> 2) * 16384 + (k & 3) * 32, 16, 1024, 1);
                    wgmma_rs_n128_t0(s, q[k], db, k != 0);
                }
                wgmma_commit();
                return stk;
            };
            auto issue_pv = [&](bool fresh) -> uint32_t {
                const uint32_t vbuf = wait_full();
                const uint32_t stv = st;
                advance();
                wgmma_fence();
#pragma unroll
                for (int k = 0; k < 8; k++) {
                    uint64_t db = make_desc(vbuf + k * 2048, 16384, 1024, 1);
                    wgmma_rs_n128_t1(o, p[k], db, (!fresh) || k != 0);
                }
                wgmma_commit();
                return stv;
            };
            auto softmax = [&](bool first) {
                float mx0 = fmaxf(s[0], s[1]), mx1 = fmaxf(s[2], s[3]);
#pragma unroll
                for (int j = 1; j < 16; j++) {
                    mx0 = fmaxf(mx0, fmaxf(s[4 * j], s[4 * j + 1]));
                    mx1 = fmaxf(mx1, fmaxf(s[4 * j + 2], s[4 * j + 3]));
                }
                mx0 = fmaxf(mx0, __shfl_xor_sync(0xffffffffu, mx0, 1));
                mx0 = fmaxf(mx0, __shfl_xor_sync(0xffffffffu, mx0, 2));
                mx1 = fmaxf(mx1, __shfl_xor_sync(0xffffffffu, mx1, 1));
                mx1 = fmaxf(mx1, __shfl_xor_sync(0xffffffffu, mx1, 2));
                if (first) {
                    lo0 = l0; lo1 = l1;
                    m0 = mx0; m1 = mx1; l0 = 0.f; l1 = 0.f; a0 = 0.f; a1 = 0.f;
                } else {
                    float mn0 = fmaxf(m0, mx0), mn1 = fmaxf(m1, mx1);
                    a0 = ex2((m0 - mn0) * cscale); a1 = ex2((m1 - mn1) * cscale);
                    m0 = mn0; m1 = mn1;
                }
                const float mc0 = m0 * cscale, mc1 = m1 * cscale;
                float r0 = 0.f, r1 = 0.f;
#pragma unroll
                for (int j = 0; j < 16; j++) {
                    s[4 * j] = ex2(fmaf(s[4 * j], cscale, -mc0));
                    s[4 * j + 1] = ex2(fmaf(s[4 * j + 1], cscale, -mc0));
                    s[4 * j + 2] = ex2(fmaf(s[4 * j + 2], cscale, -mc1));
                    s[4 * j + 3] = ex2(fmaf(s[4 * j + 3], cscale, -mc1));
                    r0 += s[4 * j] + s[4 * j + 1];
                    r1 += s[4 * j + 2] + s[4 * j + 3];
                }
                l0 = l0 * a0 + r0; l1 = l1 * a1 + r1;
            };
            auto convert_p = [&]() {
#pragma unroll
                for (int i = 0; i < 8; i++) {
                    p[i][0] = pack_bf16(s[8 * i + 0], s[8 * i + 1]);
                    p[i][1] = pack_bf16(s[8 * i + 2], s[8 * i + 3]);
                    p[i][2] = pack_bf16(s[8 * i + 4], s[8 * i + 5]);
                    p[i][3] = pack_bf16(s[8 * i + 6], s[8 * i + 7]);
                }
            };
            auto store_o = [&](float ls0, float ls1, int head) {
                float s0 = ls0 + __shfl_xor_sync(0xffffffffu, ls0, 1); s0 += __shfl_xor_sync(0xffffffffu, s0, 2);
                float s1 = ls1 + __shfl_xor_sync(0xffffffffu, ls1, 1); s1 += __shfl_xor_sync(0xffffffffu, s1, 2);
                const float i0 = 1.f / s0, i1 = 1.f / s1;
                if (tid == 0) tma_store_wait_read<0>();
                bar_sync(1 + wg, 128);
#pragma unroll
                for (int j = 0; j < 16; j += 2) {
                    const int mi = lane >> 3;
                    const int row = warp * 16 + (mi & 1) * 8 + (lane & 7);
                    const int grp = j + (mi >> 1);
                    const uint32_t addr = mypark + (grp >> 3) * 8192 + row * 128 + (((grp & 7) ^ (row & 7)) << 4);
                    stmatrix_x4(addr, pack_bf16(o[4 * j] * i0, o[4 * j + 1] * i0), pack_bf16(o[4 * j + 2] * i1, o[4 * j + 3] * i1),
                                pack_bf16(o[4 * j + 4] * i0, o[4 * j + 5] * i0), pack_bf16(o[4 * j + 6] * i1, o[4 * j + 7] * i1));
                }
                fence_proxy_async();
                bar_sync(1 + wg, 128);
                if (tid == 0) {
                    tma_store_2d(&tm_o, mypark, head * 128, q0 + wg * 64);
                    tma_store_2d(&tm_o, mypark + 8192, head * 128 + 64, q0 + wg * 64);
                    tma_store_commit();
                }
            };

            l0 = 0.f; l1 = 0.f;
            {
                uint32_t stk = issue_s();
                wgmma_wait<0>();
                fence_regs(s);
                release(stk);
                softmax(true);
                convert_p();
            }
#pragma unroll 1
            for (int t = 1; t < 8; t++) {
                const bool first = (t == 4);
                if (t == 4) {
#pragma unroll
                    for (int i = 0; i < 8; i++) {
                        asm volatile("ld.shared.v4.b32 {%0, %1, %2, %3}, [%4];" : "=r"(q[i][0]), "=r"(q[i][1]), "=r"(q[i][2]), "=r"(q[i][3])
                                     : "r"(mypark + (i * 128 + tid) * 16) : "memory");
                    }
                }
                uint32_t stk = issue_s();
                uint32_t stv = issue_pv(t == 1 || t == 5);
                wgmma_wait<1>();
                fence_regs(s);
                release(stk);
                softmax(first);
                wgmma_wait<0>();
                fence_regs(o);
                release(stv);
                if (first) {
                    store_o(lo0, lo1, head0);
                } else {
#pragma unroll
                    for (int j = 0; j < 16; j++) {
                        o[4 * j] *= a0; o[4 * j + 1] *= a0; o[4 * j + 2] *= a1; o[4 * j + 3] *= a1;
                    }
                }
                convert_p();
            }
            {
                uint32_t stv = issue_pv(false);
                wgmma_wait<0>();
                fence_regs(o);
                release(stv);
                store_o(l0, l1, head0 + 1);
            }
        }
        if (tid == 0) tma_store_wait<0>();
        cluster_sync();
    }
}

__device__ float g_part[4 * S_LEN * D_MODEL];
constexpr int OP_STAGES = 4;
constexpr int OP_STAGE_BYTES = 16384 + 40960;
constexpr int OP_SMEM = OP_STAGES * OP_STAGE_BYTES + 1024 + 256;

__global__ void __cluster_dims__(2, 1, 1) __launch_bounds__(384, 1)
oproj_kernel(const __grid_constant__ CUtensorMap tm_a, const __grid_constant__ CUtensorMap tm_b) {
    extern __shared__ uint8_t smem_raw[];
    const uint32_t base = (smem_u32(smem_raw) + 1023u) & ~1023u;
    const uint32_t bars = base + OP_STAGES * OP_STAGE_BYTES;
    const uint32_t rank = cluster_ctarank();
    const int cid = blockIdx.x >> 1;
    const int m0 = ((cid & 7) * 2 + (int)rank) * 128;
    const int n0 = ((cid >> 3) & 1) * 320;
    const int kq = cid >> 4;
    const int wg = threadIdx.x >> 7;

    if (threadIdx.x == 0) {
        for (int i = 0; i < OP_STAGES; i++) {
            mbar_init(bars + 8 * i, 1);
            mbar_init(bars + 8 * (OP_STAGES + i), 4);
        }
        fence_mbar_init();
    }
    __syncthreads();
    cluster_sync();
    pdl_launch();

    if (wg == 2) {
        reg_dealloc<40>();
        if (threadIdx.x == 256) {
            tma_prefetch_desc(&tm_a); tma_prefetch_desc(&tm_b);
            pdl_wait();
            uint32_t st = 0, ph = 1;
            for (int i = 0; i < 16; i++) {
                mbar_wait(bars + 8 * (OP_STAGES + st), ph);
                mbar_expect_tx(bars + 8 * st, OP_STAGE_BYTES);
                const uint32_t dst = base + st * OP_STAGE_BYTES;
                const int k0 = kq * 1024 + i * 64;
                tma_load_2d(dst, &tm_a, k0, m0, bars + 8 * st);
#pragma unroll
                for (int c = 0; c < 5; c++)
                    if (((c + i) & 1) == (int)rank) tma_load_2d_mc(dst + 16384 + c * 8192, &tm_b, n0 + c * 64, k0, bars + 8 * st, 3);
                if (++st == OP_STAGES) { st = 0; ph ^= 1; }
            }
        }
        __syncwarp();
        asm volatile("barrier.cluster.arrive.release.aligned; // producer\n barrier.cluster.wait.acquire.aligned;" ::: "memory");
    } else {
        reg_alloc<232>();
        const int tid = threadIdx.x & 127;
        const int warp = tid >> 5, lane = tid & 31;
        float acc0[96], acc1[64];
#pragma unroll
        for (int i = 0; i < 96; i++) acc0[i] = 0.f;
#pragma unroll
        for (int i = 0; i < 64; i++) acc1[i] = 0.f;
        uint32_t st = 0, ph = 0, prev = 0;
        for (int i = 0; i < 16; i++) {
            mbar_wait(bars + 8 * st, ph);
            const uint32_t buf = base + st * OP_STAGE_BYTES;
            wgmma_fence();
#pragma unroll
            for (int k = 0; k < 4; k++) {
                uint64_t da = make_desc(buf + wg * 8192 + k * 32, 16, 1024, 1);
                wgmma_ss_n192_t1(acc0, da, make_desc(buf + 16384 + k * 2048, 8192, 1024, 1), 1);
                wgmma_ss_n128_t1(acc1, da, make_desc(buf + 16384 + 3 * 8192 + k * 2048, 8192, 1024, 1), 1);
            }
            wgmma_commit();
            if (i > 0) {
                wgmma_wait<1>();
                if (tid == 0) mbar_arrive_cluster(bars + 8 * (OP_STAGES + prev), 0);
                if (tid == 32) mbar_arrive_cluster(bars + 8 * (OP_STAGES + prev), 1);
            }
            prev = st;
            if (++st == OP_STAGES) { st = 0; ph ^= 1; }
        }
        wgmma_wait<0>();
        fence_regs(acc0); fence_regs(acc1);
        float* dst = g_part + ((size_t)kq * S_LEN + m0 + wg * 64 + warp * 16 + (lane >> 2)) * D_MODEL + n0 + (lane & 3) * 2;
#pragma unroll
        for (int j = 0; j < 24; j++) {
            *reinterpret_cast<float2*>(dst + j * 8) = make_float2(acc0[4 * j], acc0[4 * j + 1]);
            *reinterpret_cast<float2*>(dst + 8 * D_MODEL + j * 8) = make_float2(acc0[4 * j + 2], acc0[4 * j + 3]);
        }
#pragma unroll
        for (int j = 0; j < 16; j++) {
            *reinterpret_cast<float2*>(dst + 192 + j * 8) = make_float2(acc1[4 * j], acc1[4 * j + 1]);
            *reinterpret_cast<float2*>(dst + 8 * D_MODEL + 192 + j * 8) = make_float2(acc1[4 * j + 2], acc1[4 * j + 3]);
        }
        cluster_sync();
    }
}

__global__ void __launch_bounds__(256) ln2_kernel(const __nv_bfloat16* __restrict__ x) {
    pdl_launch();
    const int warp = threadIdx.x >> 5, lane = threadIdx.x & 31;
    const int row = blockIdx.x * 8 + warp;
    uint2 xr[5];
#pragma unroll
    for (int i = 0; i < 5; i++) xr[i] = __ldg(reinterpret_cast<const uint2*>(x + (size_t)row * D_MODEL + (lane + 32 * i) * 4));
    pdl_wait();
    float v[20];
    float4 pp[4][5];
#pragma unroll
    for (int s = 0; s < 4; s++)
#pragma unroll
        for (int i = 0; i < 5; i++)
            pp[s][i] = *reinterpret_cast<const float4*>(g_part + ((size_t)s * S_LEN + row) * D_MODEL + (lane + 32 * i) * 4);
#pragma unroll
    for (int i = 0; i < 5; i++) {
        const int c0 = (lane + 32 * i) * 4;
        float4 g = *reinterpret_cast<const float4*>(g_mod + 2 * D_MODEL + c0);
        float a0 = (pp[0][i].x + pp[1][i].x) + (pp[2][i].x + pp[3][i].x);
        float a1 = (pp[0][i].y + pp[1][i].y) + (pp[2][i].y + pp[3][i].y);
        float a2 = (pp[0][i].z + pp[1][i].z) + (pp[2][i].z + pp[3][i].z);
        float a3 = (pp[0][i].w + pp[1][i].w) + (pp[2][i].w + pp[3][i].w);
        v[4 * i + 0] = bf16_round(bf16lo(xr[i].x) + bf16_round(g.x * bf16_round(a0)));
        v[4 * i + 1] = bf16_round(bf16hi(xr[i].x) + bf16_round(g.y * bf16_round(a1)));
        v[4 * i + 2] = bf16_round(bf16lo(xr[i].y) + bf16_round(g.z * bf16_round(a2)));
        v[4 * i + 3] = bf16_round(bf16hi(xr[i].y) + bf16_round(g.w * bf16_round(a3)));
        uint2 u; u.x = pack_bf16(v[4 * i], v[4 * i + 1]); u.y = pack_bf16(v[4 * i + 2], v[4 * i + 3]);
        *reinterpret_cast<uint2*>(g_x1 + (size_t)row * D_MODEL + c0) = u;
    }
    float s = 0.f;
#pragma unroll
    for (int i = 0; i < 20; i++) s += v[i];
#pragma unroll
    for (int o = 16; o > 0; o >>= 1) s += __shfl_xor_sync(0xffffffffu, s, o);
    const float mean = s * (1.f / D_MODEL);
    float q = 0.f;
#pragma unroll
    for (int i = 0; i < 20; i++) { float d = v[i] - mean; q += d * d; }
#pragma unroll
    for (int o = 16; o > 0; o >>= 1) q += __shfl_xor_sync(0xffffffffu, q, o);
    const float rstd = rsqrtf(q * (1.f / D_MODEL) + LN_EPS);
#pragma unroll
    for (int i = 0; i < 5; i++) {
        const int c0 = (lane + 32 * i) * 4;
        float4 sb = *reinterpret_cast<const float4*>(g_mod + 3 * D_MODEL + c0);
        float4 cb = *reinterpret_cast<const float4*>(g_mod + 4 * D_MODEL + c0);
        float o0 = (v[4 * i] - mean) * rstd * bf16_round(1.f + cb.x) + sb.x;
        float o1 = (v[4 * i + 1] - mean) * rstd * bf16_round(1.f + cb.y) + sb.y;
        float o2 = (v[4 * i + 2] - mean) * rstd * bf16_round(1.f + cb.z) + sb.z;
        float o3 = (v[4 * i + 3] - mean) * rstd * bf16_round(1.f + cb.w) + sb.w;
        uint2 u; u.x = pack_bf16(o0, o1); u.y = pack_bf16(o2, o3);
        *reinterpret_cast<uint2*>(g_h2 + (size_t)row * D_MODEL + c0) = u;
    }
}

constexpr int GU_STAGES = 4;
constexpr int GU_STAGE_BYTES = 16384 + 32768;
constexpr int GU_SMEM = GU_STAGES * GU_STAGE_BYTES + 1024 + 256;

__device__ __forceinline__ float silu_mul(float g, float u) {
    g = bf16_round(g); u = bf16_round(u);
    float s = bf16_round(g / (1.f + __expf(-g)));
    return s * u;
}

__global__ void __cluster_dims__(2, 1, 1) __launch_bounds__(384, 1)
gateup_kernel(const __grid_constant__ CUtensorMap tm_a, const __grid_constant__ CUtensorMap tm_g128,
              const __grid_constant__ CUtensorMap tm_u128, const __grid_constant__ CUtensorMap tm_g64,
              const __grid_constant__ CUtensorMap tm_u64) {
    extern __shared__ uint8_t smem_raw[];
    const uint32_t base = (smem_u32(smem_raw) + 1023u) & ~1023u;
    const uint32_t bars = base + GU_STAGES * GU_STAGE_BYTES;
    const uint32_t rank = cluster_ctarank();
    const int cid = blockIdx.x >> 1;
    const int fs = cid & 7;
    const int m0 = ((cid >> 3) * 2 + (int)rank) * 128;
    const int f0 = fs * 216;
    const int wg = threadIdx.x >> 7;

    if (threadIdx.x == 0) {
        for (int i = 0; i < GU_STAGES; i++) {
            mbar_init(bars + 8 * i, 1);
            mbar_init(bars + 8 * (GU_STAGES + i), 4);
        }
        fence_mbar_init();
    }
    __syncthreads();
    cluster_sync();
    pdl_launch();

    if (wg == 2) {
        reg_dealloc<40>();
        if (threadIdx.x == 256) {
            tma_prefetch_desc(&tm_a); tma_prefetch_desc(&tm_g128); tma_prefetch_desc(&tm_u128);
            tma_prefetch_desc(&tm_g64); tma_prefetch_desc(&tm_u64);
            pdl_wait();
            uint32_t st = 0, ph = 1;
            const CUtensorMap* t128 = rank == 0 ? &tm_g128 : &tm_u128;
            const CUtensorMap* t64 = rank == 0 ? &tm_g64 : &tm_u64;
            for (int i = 0; i < 20; i++) {
                const int kb = i < 10 ? i : i - 10;
                mbar_wait(bars + 8 * (GU_STAGES + st), ph);
                const uint32_t dst = base + st * GU_STAGE_BYTES;
                if (i < 10) {
                    mbar_expect_tx(bars + 8 * st, 16384 + 32768);
                    tma_load_2d(dst, &tm_a, kb * 64, m0, bars + 8 * st);
                    tma_load_2d_mc(dst + 16384 + rank * 16384, t128, f0, kb * 64, bars + 8 * st, 3);
                    tma_load_2d_mc(dst + 16384 + rank * 16384 + 8192, t128, f0 + 64, kb * 64, bars + 8 * st, 3);
                } else {
                    mbar_expect_tx(bars + 8 * st, 16384 + 24576);
                    tma_load_2d(dst, &tm_a, kb * 64, m0, bars + 8 * st);
#pragma unroll
                    for (int c = 0; c < 3; c++)
                        tma_load_2d_mc(dst + 16384 + rank * 12288 + c * 4096, t64, f0 + 128 + c * 32, kb * 64, bars + 8 * st, 3);
                }
                if (++st == GU_STAGES) { st = 0; ph ^= 1; }
            }
        }
        __syncwarp();
        asm volatile("barrier.cluster.arrive.release.aligned; // producer\n barrier.cluster.wait.acquire.aligned;" ::: "memory");
    } else {
        reg_alloc<232>();
        const int tid = threadIdx.x & 127;
        const int w = tid >> 5, lane = tid & 31;
        uint32_t st = 0, ph = 0, prev = 0;
        const int r0 = m0 + wg * 64 + w * 16 + (lane >> 2);
        auto release = [&](uint32_t s) {
            if (tid == 0) mbar_arrive_cluster(bars + 8 * (GU_STAGES + s), 0);
            if (tid == 32) mbar_arrive_cluster(bars + 8 * (GU_STAGES + s), 1);
        };
        pdl_wait();
        {
            float acc[128];
#pragma unroll
            for (int i = 0; i < 128; i++) acc[i] = 0.f;
            for (int i = 0; i < 10; i++) {
                mbar_wait(bars + 8 * st, ph);
                const uint32_t buf = base + st * GU_STAGE_BYTES;
                wgmma_fence();
#pragma unroll
                for (int k = 0; k < 4; k++) {
                    uint64_t da = make_desc(buf + wg * 8192 + k * 32, 16, 1024, 1);
                    uint64_t db = make_desc(buf + 16384 + k * 2048, 8192, 1024, 1);
                    wgmma_ss_n256_t1(acc, da, db, 1);
                }
                wgmma_commit();
                if (i > 0) { wgmma_wait<1>(); release(prev); }
                prev = st;
                if (++st == GU_STAGES) { st = 0; ph ^= 1; }
            }
            wgmma_wait<0>();
            release(prev);
            fence_regs(acc);
#pragma unroll
            for (int j = 0; j < 16; j++) {
                const int col = f0 + j * 8 + (lane & 3) * 2;
                *reinterpret_cast<uint32_t*>(g_act + (size_t)r0 * D_FF + col) =
                    pack_bf16(silu_mul(acc[4 * j], acc[64 + 4 * j]), silu_mul(acc[4 * j + 1], acc[64 + 4 * j + 1]));
                *reinterpret_cast<uint32_t*>(g_act + (size_t)(r0 + 8) * D_FF + col) =
                    pack_bf16(silu_mul(acc[4 * j + 2], acc[64 + 4 * j + 2]), silu_mul(acc[4 * j + 3], acc[64 + 4 * j + 3]));
            }
        }
        {
            float acc[92];
#pragma unroll
            for (int i = 0; i < 92; i++) acc[i] = 0.f;
            for (int i = 0; i < 10; i++) {
                mbar_wait(bars + 8 * st, ph);
                const uint32_t buf = base + st * GU_STAGE_BYTES;
                wgmma_fence();
#pragma unroll
                for (int k = 0; k < 4; k++) {
                    uint64_t da = make_desc(buf + wg * 8192 + k * 32, 16, 1024, 1);
                    uint64_t db = make_desc(buf + 16384 + k * 1024, 4096, 512, 2);
                    wgmma_ss_n184_t1(acc, da, db, 1);
                }
                wgmma_commit();
                if (i > 0) { wgmma_wait<1>(); release(prev); }
                prev = st;
                if (++st == GU_STAGES) { st = 0; ph ^= 1; }
            }
            wgmma_wait<0>();
            fence_regs(acc);
#pragma unroll
            for (int j = 0; j < 11; j++) {
                const int col = f0 + 128 + j * 8 + (lane & 3) * 2;
                *reinterpret_cast<uint32_t*>(g_act + (size_t)r0 * D_FF + col) =
                    pack_bf16(silu_mul(acc[4 * j], acc[48 + 4 * j]), silu_mul(acc[4 * j + 1], acc[48 + 4 * j + 1]));
                *reinterpret_cast<uint32_t*>(g_act + (size_t)(r0 + 8) * D_FF + col) =
                    pack_bf16(silu_mul(acc[4 * j + 2], acc[48 + 4 * j + 2]), silu_mul(acc[4 * j + 3], acc[48 + 4 * j + 3]));
            }
        }
        cluster_sync();
    }
}

constexpr int DN_STAGES = 5;
constexpr int DN_STAGE_BYTES = 16384 + 24576;
constexpr int DN_SMEM = DN_STAGES * DN_STAGE_BYTES + 1024 + 256;

__global__ void __cluster_dims__(2, 1, 1) __launch_bounds__(384, 1)
down_kernel(const __grid_constant__ CUtensorMap tm_a, const __grid_constant__ CUtensorMap tm_b, __nv_bfloat16* __restrict__ out) {
    extern __shared__ uint8_t smem_raw[];
    const uint32_t base = (smem_u32(smem_raw) + 1023u) & ~1023u;
    const uint32_t bars = base + DN_STAGES * DN_STAGE_BYTES;
    const uint32_t rank = cluster_ctarank();
    const int cid = blockIdx.x >> 1;
    const int m0 = (cid >> 2) * 128;
    const int n0 = (cid & 3) * 160;
    const int kb0 = rank == 0 ? 0 : 14;
    const int nkb = rank == 0 ? 14 : 13;
    const int wg = threadIdx.x >> 7;

    if (threadIdx.x == 0) {
        for (int i = 0; i < DN_STAGES; i++) {
            mbar_init(bars + 8 * i, 1);
            mbar_init(bars + 8 * (DN_STAGES + i), 2);
        }
        fence_mbar_init();
    }
    __syncthreads();
    pdl_launch();

    if (wg == 2) {
        reg_dealloc<40>();
        if (threadIdx.x == 256) {
            tma_prefetch_desc(&tm_a); tma_prefetch_desc(&tm_b);
            pdl_wait();
            uint32_t st = 0, ph = 1;
            for (int i = 0; i < nkb; i++) {
                mbar_wait(bars + 8 * (DN_STAGES + st), ph);
                mbar_expect_tx(bars + 8 * st, DN_STAGE_BYTES);
                const uint32_t dst = base + st * DN_STAGE_BYTES;
                const int k0 = (kb0 + i) * 64;
                tma_load_2d(dst, &tm_a, k0, m0, bars + 8 * st);
#pragma unroll
                for (int c = 0; c < 3; c++) tma_load_2d(dst + 16384 + c * 8192, &tm_b, n0 + c * 64, k0, bars + 8 * st);
                if (++st == DN_STAGES) { st = 0; ph ^= 1; }
            }
        }
        __syncwarp();
        asm volatile("barrier.cluster.arrive.release.aligned; // producer\n barrier.cluster.wait.acquire.aligned;" ::: "memory");
        asm volatile("barrier.cluster.arrive.release.aligned; // producer2\n barrier.cluster.wait.acquire.aligned;" ::: "memory");
    } else {
        reg_alloc<232>();
        const int tid = threadIdx.x & 127;
        const int warp = tid >> 5, lane = tid & 31;
        float acc[80];
#pragma unroll
        for (int i = 0; i < 80; i++) acc[i] = 0.f;
        uint32_t st = 0, ph = 0, prev = 0;
        for (int i = 0; i < nkb; i++) {
            mbar_wait(bars + 8 * st, ph);
            const uint32_t buf = base + st * DN_STAGE_BYTES;
            wgmma_fence();
#pragma unroll
            for (int k = 0; k < 4; k++) {
                uint64_t da = make_desc(buf + wg * 8192 + k * 32, 16, 1024, 1);
                wgmma_ss_n160_t1(acc, da, make_desc(buf + 16384 + k * 2048, 8192, 1024, 1), 1);
            }
            wgmma_commit();
            if (i > 0) {
                wgmma_wait<1>();
                if (tid == 0) mbar_arrive(bars + 8 * (DN_STAGES + prev));
            }
            prev = st;
            if (++st == DN_STAGES) { st = 0; ph ^= 1; }
        }
        wgmma_wait<0>();
        fence_regs(acc);
        cluster_sync();
        if (wg != (int)rank) {
            const uint32_t dst = mapa(base, rank ^ 1) + tid * 16;
#pragma unroll
            for (int i = 0; i < 20; i++) {
                asm volatile("st.shared::cluster.v4.f32 [%0], {%1, %2, %3, %4};" ::"r"(dst + i * 2048), "f"(acc[4 * i]), "f"(acc[4 * i + 1]),
                             "f"(acc[4 * i + 2]), "f"(acc[4 * i + 3]) : "memory");
            }
        }
        cluster_sync();
        if (wg == (int)rank) {
            pdl_wait();
            const int row = m0 + wg * 64 + warp * 16 + (lane >> 2);
#pragma unroll
            for (int j = 0; j < 20; j++) {
                float4 o;
                asm volatile("ld.shared.v4.f32 {%0, %1, %2, %3}, [%4];" : "=f"(o.x), "=f"(o.y), "=f"(o.z), "=f"(o.w) : "r"(base + tid * 16 + j * 2048));
                const int col = n0 + j * 8 + (lane & 3) * 2;
                const float2 g = *reinterpret_cast<const float2*>(g_mod + 5 * D_MODEL + col);
                const uint32_t x0 = *reinterpret_cast<const uint32_t*>(g_x1 + (size_t)row * D_MODEL + col);
                const uint32_t x1 = *reinterpret_cast<const uint32_t*>(g_x1 + (size_t)(row + 8) * D_MODEL + col);
                float y0 = bf16lo(x0) + bf16_round(g.x * bf16_round(acc[4 * j] + o.x));
                float y1 = bf16hi(x0) + bf16_round(g.y * bf16_round(acc[4 * j + 1] + o.y));
                float y2 = bf16lo(x1) + bf16_round(g.x * bf16_round(acc[4 * j + 2] + o.z));
                float y3 = bf16hi(x1) + bf16_round(g.y * bf16_round(acc[4 * j + 3] + o.w));
                *reinterpret_cast<uint32_t*>(out + (size_t)row * D_MODEL + col) = pack_bf16(y0, y1);
                *reinterpret_cast<uint32_t*>(out + (size_t)(row + 8) * D_MODEL + col) = pack_bf16(y2, y3);
            }
        }
    }
}

typedef CUresult (*PFN_encodeTiled)(CUtensorMap*, CUtensorMapDataType, cuuint32_t, void*, const cuuint64_t*, const cuuint64_t*,
                                    const cuuint32_t*, const cuuint32_t*, CUtensorMapInterleave, CUtensorMapSwizzle,
                                    CUtensorMapL2promotion, CUtensorMapFloatOOBfill);

static PFN_encodeTiled get_encode() {
    static PFN_encodeTiled fn = nullptr;
    if (!fn) {
        void* p = nullptr;
        cudaDriverEntryPointQueryResult qr;
        cudaGetDriverEntryPoint("cuTensorMapEncodeTiled", &p, cudaEnableDefault, &qr);
        fn = (PFN_encodeTiled)p;
    }
    return fn;
}

static CUtensorMap make_map(const void* ptr, uint64_t rows, uint64_t cols, uint32_t box_rows, uint32_t box_cols, CUtensorMapSwizzle swz) {
    CUtensorMap m;
    cuuint64_t dims[2] = {cols, rows};
    cuuint64_t strides[1] = {cols * 2};
    cuuint32_t box[2] = {box_cols, box_rows};
    cuuint32_t es[2] = {1, 1};
    get_encode()(&m, CU_TENSOR_MAP_DATA_TYPE_BFLOAT16, 2, const_cast<void*>(ptr), dims, strides, box, es, CU_TENSOR_MAP_INTERLEAVE_NONE,
                 swz, CU_TENSOR_MAP_L2_PROMOTION_L2_256B, CU_TENSOR_MAP_FLOAT_OOB_FILL_NONE);
    return m;
}

template <typename... KArgs, typename... Args>
static void launch(void (*kernel)(KArgs...), int grid, int block, int smem, int cluster, bool pdl, Args... args) {
    cudaLaunchConfig_t cfg = {};
    cfg.gridDim = dim3(grid);
    cfg.blockDim = dim3(block);
    cfg.dynamicSmemBytes = smem;
    cfg.stream = cudaStreamPerThread;
    cudaLaunchAttribute at[2];
    int na = 0;
    if (pdl) {
        at[na].id = cudaLaunchAttributeProgrammaticStreamSerialization;
        at[na].val.programmaticStreamSerializationAllowed = 1;
        na++;
    }
    (void)cluster;
    cfg.attrs = at;
    cfg.numAttrs = na;
    cudaLaunchKernelEx(&cfg, kernel, KArgs(args)...);
}

#define USE_PDL 1

extern "C" void kernel_launch(void* const* d_in, const int* in_sizes, int n_in, void* d_out, int out_size) {
    (void)in_sizes; (void)n_in; (void)out_size;
    const __nv_bfloat16* x = (const __nv_bfloat16*)d_in[0];
    const __nv_bfloat16* kc = (const __nv_bfloat16*)d_in[1];
    const __nv_bfloat16* vc = (const __nv_bfloat16*)d_in[2];
    const __nv_bfloat16* wq = (const __nv_bfloat16*)d_in[3];
    const __nv_bfloat16* wo = (const __nv_bfloat16*)d_in[4];
    const __nv_bfloat16* wg = (const __nv_bfloat16*)d_in[6];
    const __nv_bfloat16* wu = (const __nv_bfloat16*)d_in[7];
    const __nv_bfloat16* wd = (const __nv_bfloat16*)d_in[8];
    const __nv_bfloat16* c = (const __nv_bfloat16*)d_in[9];
    const __nv_bfloat16* wmod = (const __nv_bfloat16*)d_in[10];
    __nv_bfloat16* out = (__nv_bfloat16*)d_out;

    static bool init = false;
    static void *p_h, *p_o, *p_x1, *p_h2, *p_act;
    if (!init) {
        cudaFuncSetAttribute(attn_kernel, cudaFuncAttributeMaxDynamicSharedMemorySize, ATT_SMEM);
        cudaFuncSetAttribute(oproj_kernel, cudaFuncAttributeMaxDynamicSharedMemorySize, OP_SMEM);
        cudaFuncSetAttribute(down_kernel, cudaFuncAttributeMaxDynamicSharedMemorySize, DN_SMEM);
        cudaFuncSetAttribute(gateup_kernel, cudaFuncAttributeMaxDynamicSharedMemorySize, GU_SMEM);
        cudaGetSymbolAddress(&p_h, g_h);
        cudaGetSymbolAddress(&p_o, g_o);
        cudaGetSymbolAddress(&p_x1, g_x1);
        cudaGetSymbolAddress(&p_h2, g_h2);
        cudaGetSymbolAddress(&p_act, g_act);
        init = true;
    }
    const CUtensorMapSwizzle S128 = CU_TENSOR_MAP_SWIZZLE_128B, S64 = CU_TENSOR_MAP_SWIZZLE_64B;
    CUtensorMap tm_h = make_map(p_h, S_LEN, D_MODEL, 128, 64, S128);
    CUtensorMap tm_wq = make_map(wq, D_MODEL, N_HEADS * D_HEAD, 64, 64, S128);
    CUtensorMap tm_k = make_map(kc, N_HEADS * S_KV, D_HEAD, 128, 64, S128);
    CUtensorMap tm_v = make_map(vc, N_HEADS * S_KV, D_HEAD, 128, 64, S128);
    CUtensorMap tm_o = make_map(p_o, S_LEN, N_HEADS * D_HEAD, 64, 64, S128);
    CUtensorMap tm_oa = make_map(p_o, S_LEN, N_HEADS * D_HEAD, 128, 64, S128);
    CUtensorMap tm_wo = make_map(wo, N_HEADS * D_HEAD, D_MODEL, 64, 64, S128);
    CUtensorMap tm_h2 = make_map(p_h2, S_LEN, D_MODEL, 128, 64, S128);
    CUtensorMap tm_g128 = make_map(wg, D_MODEL, D_FF, 64, 64, S128);
    CUtensorMap tm_u128 = make_map(wu, D_MODEL, D_FF, 64, 64, S128);
    CUtensorMap tm_g64 = make_map(wg, D_MODEL, D_FF, 64, 32, S64);
    CUtensorMap tm_u64 = make_map(wu, D_MODEL, D_FF, 64, 32, S64);
    CUtensorMap tm_acta = make_map(p_act, S_LEN, D_FF, 128, 64, S128);
    CUtensorMap tm_wd = make_map(wd, D_FF, D_MODEL, 64, 64, S128);

    const bool pdl = USE_PDL;
    launch(mod_kernel, 120, 256, 0, 1, false, c, wmod);
    launch(ln1_kernel, 256, 256, 0, 1, pdl, x);
    launch(attn_kernel, 128, 384, ATT_SMEM, 2, pdl, tm_h, tm_wq, tm_k, tm_v, tm_o);
    launch(oproj_kernel, 128, 384, OP_SMEM, 2, pdl, tm_oa, tm_wo);
    launch(ln2_kernel, 256, 256, 0, 1, pdl, x);
    launch(gateup_kernel, 128, 384, GU_SMEM, 2, pdl, tm_h2, tm_g128, tm_u128, tm_g64, tm_u64);
    launch(down_kernel, 128, 384, DN_SMEM, 2, pdl, tm_acta, tm_wd, out);
}
```

```cpp
#include <cuda_runtime.h>
#include <cuda_bf16.h>
#include <cuda.h>
#include <stdint.h>

__device__ __forceinline__ uint32_t smem_u32(const void* p) { return (uint32_t)__cvta_generic_to_shared(p); }

__device__ __forceinline__ void mbar_init(uint32_t bar, uint32_t count) {
    asm volatile("mbarrier.init.shared::cta.b64 [%0], %1;" ::"r"(bar), "r"(count) : "memory");
}
__device__ __forceinline__ void mbar_expect_tx(uint32_t bar, uint32_t bytes) {
    asm volatile("mbarrier.arrive.expect_tx.shared::cta.b64 _, [%0], %1;" ::"r"(bar), "r"(bytes) : "memory");
}
__device__ __forceinline__ void mbar_arrive(uint32_t bar) {
    asm volatile("mbarrier.arrive.shared::cta.b64 _, [%0];" ::"r"(bar) : "memory");
}
__device__ __forceinline__ void mbar_arrive_cluster(uint32_t bar, uint32_t cta) {
    asm volatile(
        "{\n.reg .b32 ra;\n"
        "mapa.shared::cluster.u32 ra, %0, %1;\n"
        "mbarrier.arrive.shared::cluster.b64 _, [ra];\n}\n" ::"r"(bar), "r"(cta)
        : "memory");
}
__device__ __forceinline__ bool mbar_try_wait(uint32_t bar, uint32_t parity) {
    uint32_t ok;
    asm volatile(
        "{\n.reg .pred p;\n"
        "mbarrier.try_wait.parity.shared::cta.b64 p, [%1], %2;\n"
        "selp.u32 %0, 1, 0, p;\n}\n"
        : "=r"(ok)
        : "r"(bar), "r"(parity)
        : "memory");
    return ok != 0;
}
__device__ __forceinline__ bool mbar_try_wait_cluster(uint32_t bar, uint32_t parity) {
    uint32_t ok;
    asm volatile(
        "{\n.reg .pred p;\n"
        "mbarrier.try_wait.parity.shared::cta.b64 p, [%1], %2;\n"
        "selp.u32 %0, 1, 0, p;\n}\n"
        : "=r"(ok)
        : "r"(bar), "r"(parity)
        : "memory");
    return ok != 0;
}
__device__ volatile int g_abort = 0;
__device__ __forceinline__ void mbar_wait(uint32_t bar, uint32_t parity) {
    if (mbar_try_wait(bar, parity)) return;
    uint32_t n = 0;
    while (!mbar_try_wait(bar, parity)) {
        ++n;
        if (n > (1u << 22)) { g_abort = 1; break; }
        if ((n & 255u) == 0 && g_abort) break;
    }
}
__device__ __forceinline__ void mbar_wait_cluster(uint32_t bar, uint32_t parity) { mbar_wait(bar, parity); }
__device__ __forceinline__ void fence_mbar_init() { asm volatile("fence.mbarrier_init.release.cluster;" ::: "memory"); }
__device__ __forceinline__ void fence_proxy_async() { asm volatile("fence.proxy.async.shared::cta;" ::: "memory"); }
__device__ __forceinline__ void fence_proxy_async_all() { asm volatile("fence.proxy.async;" ::: "memory"); }
__device__ __forceinline__ void cluster_arrive() { asm volatile("barrier.cluster.arrive.release.aligned;" ::: "memory"); }
__device__ __forceinline__ void cluster_wait() { asm volatile("barrier.cluster.wait.acquire.aligned;" ::: "memory"); }
__device__ __forceinline__ void cluster_sync() { cluster_arrive(); cluster_wait(); }
__device__ __forceinline__ uint32_t cluster_ctarank() {
    uint32_t r;
    asm volatile("mov.u32 %0, %%cluster_ctarank;" : "=r"(r));
    return r;
}
__device__ __forceinline__ void bar_sync(int id, int n) { asm volatile("bar.sync %0, %1;" ::"r"(id), "r"(n) : "memory"); }
__device__ __forceinline__ void bar_arrive(int id, int n) { asm volatile("bar.arrive %0, %1;" ::"r"(id), "r"(n) : "memory"); }
__device__ __forceinline__ void pdl_wait() { asm volatile("griddepcontrol.wait;" ::: "memory"); }
__device__ __forceinline__ void pdl_launch() { asm volatile("griddepcontrol.launch_dependents;" ::: "memory"); }

__device__ __forceinline__ void tma_prefetch_desc(const CUtensorMap* m) {
    asm volatile("prefetch.tensormap [%0];" ::"l"(m) : "memory");
}
__device__ __forceinline__ void tma_load_2d(uint32_t dst, const CUtensorMap* m, int c0, int c1, uint32_t bar) {
    asm volatile(
        "cp.async.bulk.tensor.2d.shared::cluster.global.mbarrier::complete_tx::bytes [%0], [%1, {%3, %4}], [%2];"
        ::"r"(dst), "l"(m), "r"(bar), "r"(c0), "r"(c1)
        : "memory");
}
__device__ __forceinline__ void tma_load_2d_mc(uint32_t dst, const CUtensorMap* m, int c0, int c1, uint32_t bar, uint16_t mask) {
    asm volatile(
        "cp.async.bulk.tensor.2d.shared::cluster.global.mbarrier::complete_tx::bytes.multicast::cluster [%0], [%1, {%3, %4}], [%2], %5;"
        ::"r"(dst), "l"(m), "r"(bar), "r"(c0), "r"(c1), "h"(mask)
        : "memory");
}
__device__ __forceinline__ void tma_store_2d(const CUtensorMap* m, uint32_t src, int c0, int c1) {
    asm volatile("cp.async.bulk.tensor.2d.global.shared::cta.bulk_group [%0, {%2, %3}], [%1];"
                 ::"l"(m), "r"(src), "r"(c0), "r"(c1)
                 : "memory");
}
__device__ __forceinline__ void tma_store_commit() { asm volatile("cp.async.bulk.commit_group;" ::: "memory"); }
template <int N> __device__ __forceinline__ void tma_store_wait_read() {
    asm volatile("cp.async.bulk.wait_group.read %0;" ::"n"(N) : "memory");
}
template <int N> __device__ __forceinline__ void tma_store_wait() {
    asm volatile("cp.async.bulk.wait_group %0;" ::"n"(N) : "memory");
}

__device__ __forceinline__ void wgmma_fence() { asm volatile("wgmma.fence.sync.aligned;" ::: "memory"); }
__device__ __forceinline__ void wgmma_commit() { asm volatile("wgmma.commit_group.sync.aligned;" ::: "memory"); }
template <int N> __device__ __forceinline__ void wgmma_wait() {
    asm volatile("wgmma.wait_group.sync.aligned %0;" ::"n"(N) : "memory");
}
template <int R> __device__ __forceinline__ void reg_alloc() { asm volatile("setmaxnreg.inc.sync.aligned.u32 %0;" ::"n"(R)); }
template <int R> __device__ __forceinline__ void reg_dealloc() { asm volatile("setmaxnreg.dec.sync.aligned.u32 %0;" ::"n"(R)); }

template <int N> __device__ __forceinline__ void fence_regs(float (&r)[N]) {
#pragma unroll
    for (int i = 0; i < N; i++) asm volatile("" : "+f"(r[i])::"memory");
}
template <int N> __device__ __forceinline__ void fence_regs_u(uint32_t (&r)[N][4]) {
#pragma unroll
    for (int i = 0; i < N; i++) {
#pragma unroll
        for (int j = 0; j < 4; j++) asm volatile("" : "+r"(r[i][j])::"memory");
    }
}

__device__ __forceinline__ uint64_t make_desc(uint32_t addr, uint32_t lbo_bytes, uint32_t sbo_bytes, uint32_t swz) {
    return (uint64_t)((addr & 0x3FFFF) >> 4) | ((uint64_t)(lbo_bytes >> 4) << 16) | ((uint64_t)(sbo_bytes >> 4) << 32) |
           ((uint64_t)swz << 62);
}

__device__ __forceinline__ uint32_t pack_bf16(float lo, float hi) {
    uint32_t r;
    asm("cvt.rn.bf16x2.f32 %0, %1, %2;" : "=r"(r) : "f"(hi), "f"(lo));
    return r;
}
__device__ __forceinline__ float bf16_round(float x) { return __bfloat162float(__float2bfloat16_rn(x)); }
__device__ __forceinline__ float bf16lo(uint32_t v) { return __uint_as_float(v << 16); }
__device__ __forceinline__ float bf16hi(uint32_t v) { return __uint_as_float(v & 0xffff0000u); }
__device__ __forceinline__ float ex2(float x) {
    float y;
    asm("ex2.approx.ftz.f32 %0, %1;" : "=f"(y) : "f"(x));
    return y;
}
__device__ __forceinline__ void stmatrix_x4(uint32_t addr, uint32_t r0, uint32_t r1, uint32_t r2, uint32_t r3) {
    asm volatile("stmatrix.sync.aligned.m8n8.x4.shared.b16 [%0], {%1, %2, %3, %4};" ::"r"(addr), "r"(r0), "r"(r1), "r"(r2), "r"(r3)
                 : "memory");
}
__device__ __forceinline__ uint32_t mapa(uint32_t addr, uint32_t cta) {
    uint32_t r;
    asm volatile("mapa.shared::cluster.u32 %0, %1, %2;" : "=r"(r) : "r"(addr), "r"(cta));
    return r;
}
__device__ __forceinline__ void st_cluster_v2(uint32_t addr, float a, float b) {
    asm volatile("st.shared::cluster.v2.f32 [%0], {%1, %2};" ::"r"(addr), "f"(a), "f"(b) : "memory");
}
__device__ __forceinline__ void wgmma_ss_n256_t1(float (&d)[128], uint64_t descA, uint64_t descB, int scaleD) {
    asm volatile("{\n.reg .pred p;\n"
        "setp.ne.b32 p, %130, 0;\n"
        "wgmma.mma_async.sync.aligned.m64n256k16.f32.bf16.bf16 "
        "{%0, %1, %2, %3, %4, %5, %6, %7, %8, %9, %10, %11, %12, %13, %14, %15, "
        "%16, %17, %18, %19, %20, %21, %22, %23, %24, %25, %26, %27, %28, %29, %30, %31, "
        "%32, %33, %34, %35, %36, %37, %38, %39, %40, %41, %42, %43, %44, %45, %46, %47, "
        "%48, %49, %50, %51, %52, %53, %54, %55, %56, %57, %58, %59, %60, %61, %62, %63, "
        "%64, %65, %66, %67, %68, %69, %70, %71, %72, %73, %74, %75, %76, %77, %78, %79, "
        "%80, %81, %82, %83, %84, %85, %86, %87, %88, %89, %90, %91, %92, %93, %94, %95, "
        "%96, %97, %98, %99, %100, %101, %102, %103, %104, %105, %106, %107, %108, %109, %110, %111, "
        "%112, %113, %114, %115, %116, %117, %118, %119, %120, %121, %122, %123, %124, %125, %126, %127}, "
        "%128, %129, p, 1, 1, 0, 1;\n}\n"
        :
          "+f"(d[0]), "+f"(d[1]), "+f"(d[2]), "+f"(d[3]), "+f"(d[4]), "+f"(d[5]), "+f"(d[6]), "+f"(d[7]),
          "+f"(d[8]), "+f"(d[9]), "+f"(d[10]), "+f"(d[11]), "+f"(d[12]), "+f"(d[13]), "+f"(d[14]), "+f"(d[15]),
          "+f"(d[16]), "+f"(d[17]), "+f"(d[18]), "+f"(d[19]), "+f"(d[20]), "+f"(d[21]), "+f"(d[22]), "+f"(d[23]),
          "+f"(d[24]), "+f"(d[25]), "+f"(d[26]), "+f"(d[27]), "+f"(d[28]), "+f"(d[29]), "+f"(d[30]), "+f"(d[31]),
          "+f"(d[32]), "+f"(d[33]), "+f"(d[34]), "+f"(d[35]), "+f"(d[36]), "+f"(d[37]), "+f"(d[38]), "+f"(d[39]),
          "+f"(d[40]), "+f"(d[41]), "+f"(d[42]), "+f"(d[43]), "+f"(d[44]), "+f"(d[45]), "+f"(d[46]), "+f"(d[47]),
          "+f"(d[48]), "+f"(d[49]), "+f"(d[50]), "+f"(d[51]), "+f"(d[52]), "+f"(d[53]), "+f"(d[54]), "+f"(d[55]),
          "+f"(d[56]), "+f"(d[57]), "+f"(d[58]), "+f"(d[59]), "+f"(d[60]), "+f"(d[61]), "+f"(d[62]), "+f"(d[63]),
          "+f"(d[64]), "+f"(d[65]), "+f"(d[66]), "+f"(d[67]), "+f"(d[68]), "+f"(d[69]), "+f"(d[70]), "+f"(d[71]),
          "+f"(d[72]), "+f"(d[73]), "+f"(d[74]), "+f"(d[75]), "+f"(d[76]), "+f"(d[77]), "+f"(d[78]), "+f"(d[79]),
          "+f"(d[80]), "+f"(d[81]), "+f"(d[82]), "+f"(d[83]), "+f"(d[84]), "+f"(d[85]), "+f"(d[86]), "+f"(d[87]),
          "+f"(d[88]), "+f"(d[89]), "+f"(d[90]), "+f"(d[91]), "+f"(d[92]), "+f"(d[93]), "+f"(d[94]), "+f"(d[95]),
          "+f"(d[96]), "+f"(d[97]), "+f"(d[98]), "+f"(d[99]), "+f"(d[100]), "+f"(d[101]), "+f"(d[102]), "+f"(d[103]),
          "+f"(d[104]), "+f"(d[105]), "+f"(d[106]), "+f"(d[107]), "+f"(d[108]), "+f"(d[109]), "+f"(d[110]), "+f"(d[111]),
          "+f"(d[112]), "+f"(d[113]), "+f"(d[114]), "+f"(d[115]), "+f"(d[116]), "+f"(d[117]), "+f"(d[118]), "+f"(d[119]),
          "+f"(d[120]), "+f"(d[121]), "+f"(d[122]), "+f"(d[123]), "+f"(d[124]), "+f"(d[125]), "+f"(d[126]), "+f"(d[127])
        : "l"(descA), "l"(descB), "r"(scaleD));
}

__device__ __forceinline__ void wgmma_rs_n128_t0(float (&d)[64], const uint32_t (&a)[4], uint64_t descB, int scaleD) {
    asm volatile("{\n.reg .pred p;\n"
        "setp.ne.b32 p, %69, 0;\n"
        "wgmma.mma_async.sync.aligned.m64n128k16.f32.bf16.bf16 "
        "{%0, %1, %2, %3, %4, %5, %6, %7, %8, %9, %10, %11, %12, %13, %14, %15, "
        "%16, %17, %18, %19, %20, %21, %22, %23, %24, %25, %26, %27, %28, %29, %30, %31, "
        "%32, %33, %34, %35, %36, %37, %38, %39, %40, %41, %42, %43, %44, %45, %46, %47, "
        "%48, %49, %50, %51, %52, %53, %54, %55, %56, %57, %58, %59, %60, %61, %62, %63}, "
        "{%64, %65, %66, %67}, %68, p, 1, 1, 0;\n}\n"
        :
          "+f"(d[0]), "+f"(d[1]), "+f"(d[2]), "+f"(d[3]), "+f"(d[4]), "+f"(d[5]), "+f"(d[6]), "+f"(d[7]),
          "+f"(d[8]), "+f"(d[9]), "+f"(d[10]), "+f"(d[11]), "+f"(d[12]), "+f"(d[13]), "+f"(d[14]), "+f"(d[15]),
          "+f"(d[16]), "+f"(d[17]), "+f"(d[18]), "+f"(d[19]), "+f"(d[20]), "+f"(d[21]), "+f"(d[22]), "+f"(d[23]),
          "+f"(d[24]), "+f"(d[25]), "+f"(d[26]), "+f"(d[27]), "+f"(d[28]), "+f"(d[29]), "+f"(d[30]), "+f"(d[31]),
          "+f"(d[32]), "+f"(d[33]), "+f"(d[34]), "+f"(d[35]), "+f"(d[36]), "+f"(d[37]), "+f"(d[38]), "+f"(d[39]),
          "+f"(d[40]), "+f"(d[41]), "+f"(d[42]), "+f"(d[43]), "+f"(d[44]), "+f"(d[45]), "+f"(d[46]), "+f"(d[47]),
          "+f"(d[48]), "+f"(d[49]), "+f"(d[50]), "+f"(d[51]), "+f"(d[52]), "+f"(d[53]), "+f"(d[54]), "+f"(d[55]),
          "+f"(d[56]), "+f"(d[57]), "+f"(d[58]), "+f"(d[59]), "+f"(d[60]), "+f"(d[61]), "+f"(d[62]), "+f"(d[63])
        : "r"(a[0]), "r"(a[1]), "r"(a[2]), "r"(a[3]), "l"(descB), "r"(scaleD));
}

__device__ __forceinline__ void wgmma_rs_n128_t1(float (&d)[64], const uint32_t (&a)[4], uint64_t descB, int scaleD) {
    asm volatile("{\n.reg .pred p;\n"
        "setp.ne.b32 p, %69, 0;\n"
        "wgmma.mma_async.sync.aligned.m64n128k16.f32.bf16.bf16 "
        "{%0, %1, %2, %3, %4, %5, %6, %7, %8, %9, %10, %11, %12, %13, %14, %15, "
        "%16, %17, %18, %19, %20, %21, %22, %23, %24, %25, %26, %27, %28, %29, %30, %31, "
        "%32, %33, %34, %35, %36, %37, %38, %39, %40, %41, %42, %43, %44, %45, %46, %47, "
        "%48, %49, %50, %51, %52, %53, %54, %55, %56, %57, %58, %59, %60, %61, %62, %63}, "
        "{%64, %65, %66, %67}, %68, p, 1, 1, 1;\n}\n"
        :
          "+f"(d[0]), "+f"(d[1]), "+f"(d[2]), "+f"(d[3]), "+f"(d[4]), "+f"(d[5]), "+f"(d[6]), "+f"(d[7]),
          "+f"(d[8]), "+f"(d[9]), "+f"(d[10]), "+f"(d[11]), "+f"(d[12]), "+f"(d[13]), "+f"(d[14]), "+f"(d[15]),
          "+f"(d[16]), "+f"(d[17]), "+f"(d[18]), "+f"(d[19]), "+f"(d[20]), "+f"(d[21]), "+f"(d[22]), "+f"(d[23]),
          "+f"(d[24]), "+f"(d[25]), "+f"(d[26]), "+f"(d[27]), "+f"(d[28]), "+f"(d[29]), "+f"(d[30]), "+f"(d[31]),
          "+f"(d[32]), "+f"(d[33]), "+f"(d[34]), "+f"(d[35]), "+f"(d[36]), "+f"(d[37]), "+f"(d[38]), "+f"(d[39]),
          "+f"(d[40]), "+f"(d[41]), "+f"(d[42]), "+f"(d[43]), "+f"(d[44]), "+f"(d[45]), "+f"(d[46]), "+f"(d[47]),
          "+f"(d[48]), "+f"(d[49]), "+f"(d[50]), "+f"(d[51]), "+f"(d[52]), "+f"(d[53]), "+f"(d[54]), "+f"(d[55]),
          "+f"(d[56]), "+f"(d[57]), "+f"(d[58]), "+f"(d[59]), "+f"(d[60]), "+f"(d[61]), "+f"(d[62]), "+f"(d[63])
        : "r"(a[0]), "r"(a[1]), "r"(a[2]), "r"(a[3]), "l"(descB), "r"(scaleD));
}

__device__ __forceinline__ void wgmma_ss_n160_t1(float (&d)[80], uint64_t descA, uint64_t descB, int scaleD) {
    asm volatile("{\n.reg .pred p;\n"
        "setp.ne.b32 p, %82, 0;\n"
        "wgmma.mma_async.sync.aligned.m64n160k16.f32.bf16.bf16 "
        "{%0, %1, %2, %3, %4, %5, %6, %7, %8, %9, %10, %11, %12, %13, %14, %15, "
        "%16, %17, %18, %19, %20, %21, %22, %23, %24, %25, %26, %27, %28, %29, %30, %31, "
        "%32, %33, %34, %35, %36, %37, %38, %39, %40, %41, %42, %43, %44, %45, %46, %47, "
        "%48, %49, %50, %51, %52, %53, %54, %55, %56, %57, %58, %59, %60, %61, %62, %63, "
        "%64, %65, %66, %67, %68, %69, %70, %71, %72, %73, %74, %75, %76, %77, %78, %79}, "
        "%80, %81, p, 1, 1, 0, 1;\n}\n"
        :
          "+f"(d[0]), "+f"(d[1]), "+f"(d[2]), "+f"(d[3]), "+f"(d[4]), "+f"(d[5]), "+f"(d[6]), "+f"(d[7]),
          "+f"(d[8]), "+f"(d[9]), "+f"(d[10]), "+f"(d[11]), "+f"(d[12]), "+f"(d[13]), "+f"(d[14]), "+f"(d[15]),
          "+f"(d[16]), "+f"(d[17]), "+f"(d[18]), "+f"(d[19]), "+f"(d[20]), "+f"(d[21]), "+f"(d[22]), "+f"(d[23]),
          "+f"(d[24]), "+f"(d[25]), "+f"(d[26]), "+f"(d[27]), "+f"(d[28]), "+f"(d[29]), "+f"(d[30]), "+f"(d[31]),
          "+f"(d[32]), "+f"(d[33]), "+f"(d[34]), "+f"(d[35]), "+f"(d[36]), "+f"(d[37]), "+f"(d[38]), "+f"(d[39]),
          "+f"(d[40]), "+f"(d[41]), "+f"(d[42]), "+f"(d[43]), "+f"(d[44]), "+f"(d[45]), "+f"(d[46]), "+f"(d[47]),
          "+f"(d[48]), "+f"(d[49]), "+f"(d[50]), "+f"(d[51]), "+f"(d[52]), "+f"(d[53]), "+f"(d[54]), "+f"(d[55]),
          "+f"(d[56]), "+f"(d[57]), "+f"(d[58]), "+f"(d[59]), "+f"(d[60]), "+f"(d[61]), "+f"(d[62]), "+f"(d[63]),
          "+f"(d[64]), "+f"(d[65]), "+f"(d[66]), "+f"(d[67]), "+f"(d[68]), "+f"(d[69]), "+f"(d[70]), "+f"(d[71]),
          "+f"(d[72]), "+f"(d[73]), "+f"(d[74]), "+f"(d[75]), "+f"(d[76]), "+f"(d[77]), "+f"(d[78]), "+f"(d[79])
        : "l"(descA), "l"(descB), "r"(scaleD));
}

__device__ __forceinline__ void wgmma_ss_n184_t1(float (&d)[92], uint64_t descA, uint64_t descB, int scaleD) {
    asm volatile("{\n.reg .pred p;\n"
        "setp.ne.b32 p, %94, 0;\n"
        "wgmma.mma_async.sync.aligned.m64n184k16.f32.bf16.bf16 "
        "{%0, %1, %2, %3, %4, %5, %6, %7, %8, %9, %10, %11, %12, %13, %14, %15, "
        "%16, %17, %18, %19, %20, %21, %22, %23, %24, %25, %26, %27, %28, %29, %30, %31, "
        "%32, %33, %34, %35, %36, %37, %38, %39, %40, %41, %42, %43, %44, %45, %46, %47, "
        "%48, %49, %50, %51, %52, %53, %54, %55, %56, %57, %58, %59, %60, %61, %62, %63, "
        "%64, %65, %66, %67, %68, %69, %70, %71, %72, %73, %74, %75, %76, %77, %78, %79, "
        "%80, %81, %82, %83, %84, %85, %86, %87, %88, %89, %90, %91}, "
        "%92, %93, p, 1, 1, 0, 1;\n}\n"
        :
          "+f"(d[0]), "+f"(d[1]), "+f"(d[2]), "+f"(d[3]), "+f"(d[4]), "+f"(d[5]), "+f"(d[6]), "+f"(d[7]),
          "+f"(d[8]), "+f"(d[9]), "+f"(d[10]), "+f"(d[11]), "+f"(d[12]), "+f"(d[13]), "+f"(d[14]), "+f"(d[15]),
          "+f"(d[16]), "+f"(d[17]), "+f"(d[18]), "+f"(d[19]), "+f"(d[20]), "+f"(d[21]), "+f"(d[22]), "+f"(d[23]),
          "+f"(d[24]), "+f"(d[25]), "+f"(d[26]), "+f"(d[27]), "+f"(d[28]), "+f"(d[29]), "+f"(d[30]), "+f"(d[31]),
          "+f"(d[32]), "+f"(d[33]), "+f"(d[34]), "+f"(d[35]), "+f"(d[36]), "+f"(d[37]), "+f"(d[38]), "+f"(d[39]),
          "+f"(d[40]), "+f"(d[41]), "+f"(d[42]), "+f"(d[43]), "+f"(d[44]), "+f"(d[45]), "+f"(d[46]), "+f"(d[47]),
          "+f"(d[48]), "+f"(d[49]), "+f"(d[50]), "+f"(d[51]), "+f"(d[52]), "+f"(d[53]), "+f"(d[54]), "+f"(d[55]),
          "+f"(d[56]), "+f"(d[57]), "+f"(d[58]), "+f"(d[59]), "+f"(d[60]), "+f"(d[61]), "+f"(d[62]), "+f"(d[63]),
          "+f"(d[64]), "+f"(d[65]), "+f"(d[66]), "+f"(d[67]), "+f"(d[68]), "+f"(d[69]), "+f"(d[70]), "+f"(d[71]),
          "+f"(d[72]), "+f"(d[73]), "+f"(d[74]), "+f"(d[75]), "+f"(d[76]), "+f"(d[77]), "+f"(d[78]), "+f"(d[79]),
          "+f"(d[80]), "+f"(d[81]), "+f"(d[82]), "+f"(d[83]), "+f"(d[84]), "+f"(d[85]), "+f"(d[86]), "+f"(d[87]),
          "+f"(d[88]), "+f"(d[89]), "+f"(d[90]), "+f"(d[91])
        : "l"(descA), "l"(descB), "r"(scaleD));
}

__device__ __forceinline__ void wgmma_ss_n192_t1(float (&d)[96], uint64_t descA, uint64_t descB, int scaleD) {
    asm volatile("{\n.reg .pred p;\n"
        "setp.ne.b32 p, %98, 0;\n"
        "wgmma.mma_async.sync.aligned.m64n192k16.f32.bf16.bf16 "
        "{%0, %1, %2, %3, %4, %5, %6, %7, %8, %9, %10, %11, %12, %13, %14, %15, "
        "%16, %17, %18, %19, %20, %21, %22, %23, %24, %25, %26, %27, %28, %29, %30, %31, "
        "%32, %33, %34, %35, %36, %37, %38, %39, %40, %41, %42, %43, %44, %45, %46, %47, "
        "%48, %49, %50, %51, %52, %53, %54, %55, %56, %57, %58, %59, %60, %61, %62, %63, "
        "%64, %65, %66, %67, %68, %69, %70, %71, %72, %73, %74, %75, %76, %77, %78, %79, "
        "%80, %81, %82, %83, %84, %85, %86, %87, %88, %89, %90, %91, %92, %93, %94, %95}, "
        "%96, %97, p, 1, 1, 0, 1;\n}\n"
        :
          "+f"(d[0]), "+f"(d[1]), "+f"(d[2]), "+f"(d[3]), "+f"(d[4]), "+f"(d[5]), "+f"(d[6]), "+f"(d[7]),
          "+f"(d[8]), "+f"(d[9]), "+f"(d[10]), "+f"(d[11]), "+f"(d[12]), "+f"(d[13]), "+f"(d[14]), "+f"(d[15]),
          "+f"(d[16]), "+f"(d[17]), "+f"(d[18]), "+f"(d[19]), "+f"(d[20]), "+f"(d[21]), "+f"(d[22]), "+f"(d[23]),
          "+f"(d[24]), "+f"(d[25]), "+f"(d[26]), "+f"(d[27]), "+f"(d[28]), "+f"(d[29]), "+f"(d[30]), "+f"(d[31]),
          "+f"(d[32]), "+f"(d[33]), "+f"(d[34]), "+f"(d[35]), "+f"(d[36]), "+f"(d[37]), "+f"(d[38]), "+f"(d[39]),
          "+f"(d[40]), "+f"(d[41]), "+f"(d[42]), "+f"(d[43]), "+f"(d[44]), "+f"(d[45]), "+f"(d[46]), "+f"(d[47]),
          "+f"(d[48]), "+f"(d[49]), "+f"(d[50]), "+f"(d[51]), "+f"(d[52]), "+f"(d[53]), "+f"(d[54]), "+f"(d[55]),
          "+f"(d[56]), "+f"(d[57]), "+f"(d[58]), "+f"(d[59]), "+f"(d[60]), "+f"(d[61]), "+f"(d[62]), "+f"(d[63]),
          "+f"(d[64]), "+f"(d[65]), "+f"(d[66]), "+f"(d[67]), "+f"(d[68]), "+f"(d[69]), "+f"(d[70]), "+f"(d[71]),
          "+f"(d[72]), "+f"(d[73]), "+f"(d[74]), "+f"(d[75]), "+f"(d[76]), "+f"(d[77]), "+f"(d[78]), "+f"(d[79]),
          "+f"(d[80]), "+f"(d[81]), "+f"(d[82]), "+f"(d[83]), "+f"(d[84]), "+f"(d[85]), "+f"(d[86]), "+f"(d[87]),
          "+f"(d[88]), "+f"(d[89]), "+f"(d[90]), "+f"(d[91]), "+f"(d[92]), "+f"(d[93]), "+f"(d[94]), "+f"(d[95])
        : "l"(descA), "l"(descB), "r"(scaleD));
}

__device__ __forceinline__ void wgmma_ss_n128_t1(float (&d)[64], uint64_t descA, uint64_t descB, int scaleD) {
    asm volatile("{\n.reg .pred p;\n"
        "setp.ne.b32 p, %66, 0;\n"
        "wgmma.mma_async.sync.aligned.m64n128k16.f32.bf16.bf16 "
        "{%0, %1, %2, %3, %4, %5, %6, %7, %8, %9, %10, %11, %12, %13, %14, %15, "
        "%16, %17, %18, %19, %20, %21, %22, %23, %24, %25, %26, %27, %28, %29, %30, %31, "
        "%32, %33, %34, %35, %36, %37, %38, %39, %40, %41, %42, %43, %44, %45, %46, %47, "
        "%48, %49, %50, %51, %52, %53, %54, %55, %56, %57, %58, %59, %60, %61, %62, %63}, "
        "%64, %65, p, 1, 1, 0, 1;\n}\n"
        :
          "+f"(d[0]), "+f"(d[1]), "+f"(d[2]), "+f"(d[3]), "+f"(d[4]), "+f"(d[5]), "+f"(d[6]), "+f"(d[7]),
          "+f"(d[8]), "+f"(d[9]), "+f"(d[10]), "+f"(d[11]), "+f"(d[12]), "+f"(d[13]), "+f"(d[14]), "+f"(d[15]),
          "+f"(d[16]), "+f"(d[17]), "+f"(d[18]), "+f"(d[19]), "+f"(d[20]), "+f"(d[21]), "+f"(d[22]), "+f"(d[23]),
          "+f"(d[24]), "+f"(d[25]), "+f"(d[26]), "+f"(d[27]), "+f"(d[28]), "+f"(d[29]), "+f"(d[30]), "+f"(d[31]),
          "+f"(d[32]), "+f"(d[33]), "+f"(d[34]), "+f"(d[35]), "+f"(d[36]), "+f"(d[37]), "+f"(d[38]), "+f"(d[39]),
          "+f"(d[40]), "+f"(d[41]), "+f"(d[42]), "+f"(d[43]), "+f"(d[44]), "+f"(d[45]), "+f"(d[46]), "+f"(d[47]),
          "+f"(d[48]), "+f"(d[49]), "+f"(d[50]), "+f"(d[51]), "+f"(d[52]), "+f"(d[53]), "+f"(d[54]), "+f"(d[55]),
          "+f"(d[56]), "+f"(d[57]), "+f"(d[58]), "+f"(d[59]), "+f"(d[60]), "+f"(d[61]), "+f"(d[62]), "+f"(d[63])
        : "l"(descA), "l"(descB), "r"(scaleD));
}

constexpr int S_LEN = 2048;
constexpr int D_MODEL = 640;
constexpr int N_HEADS = 32;
constexpr int D_HEAD = 128;
constexpr int S_KV = 2048;
constexpr int WIN = 512;
constexpr int D_FF = 1728;
constexpr float LN_EPS = 1e-5f;

#define TS(kid, slot)
__device__ float g_mod[6 * D_MODEL];
__device__ __align__(1024) __nv_bfloat16 g_h[S_LEN * D_MODEL];
__device__ __align__(1024) __nv_bfloat16 g_o[S_LEN * N_HEADS * D_HEAD];
__device__ __align__(1024) __nv_bfloat16 g_x1[S_LEN * D_MODEL];
__device__ __align__(1024) __nv_bfloat16 g_h2[S_LEN * D_MODEL];
__device__ __align__(1024) __nv_bfloat16 g_act[S_LEN * D_FF];

__global__ void __launch_bounds__(256) mod_kernel(const __nv_bfloat16* __restrict__ c, const __nv_bfloat16* __restrict__ w_mod) {
    __shared__ float red[8][32];
    TS(4, 0);
    pdl_launch();
    const int warp = threadIdx.x >> 5, lane = threadIdx.x & 31;
    const int col0 = blockIdx.x * 32 + (lane & 3) * 8;
    float acc[8];
#pragma unroll
    for (int i = 0; i < 8; i++) acc[i] = 0.f;
    uint4 w[10];
    float s[10];
#pragma unroll
    for (int i = 0; i < 10; i++) {
        int k = warp * 80 + i * 8 + (lane >> 2);
        w[i] = __ldg(reinterpret_cast<const uint4*>(w_mod + (size_t)k * (6 * D_MODEL) + col0));
        float cv = __bfloat162float(c[k]);
        s[i] = bf16_round(cv / (1.f + __expf(-cv)));
    }
#pragma unroll
    for (int i = 0; i < 10; i++) {
        acc[0] += s[i] * bf16lo(w[i].x); acc[1] += s[i] * bf16hi(w[i].x);
        acc[2] += s[i] * bf16lo(w[i].y); acc[3] += s[i] * bf16hi(w[i].y);
        acc[4] += s[i] * bf16lo(w[i].z); acc[5] += s[i] * bf16hi(w[i].z);
        acc[6] += s[i] * bf16lo(w[i].w); acc[7] += s[i] * bf16hi(w[i].w);
    }
#pragma unroll
    for (int i = 0; i < 8; i++) {
        acc[i] += __shfl_xor_sync(0xffffffffu, acc[i], 4);
        acc[i] += __shfl_xor_sync(0xffffffffu, acc[i], 8);
        acc[i] += __shfl_xor_sync(0xffffffffu, acc[i], 16);
    }
    if (lane < 4) {
#pragma unroll
        for (int i = 0; i < 8; i++) red[warp][lane * 8 + i] = acc[i];
    }
    __syncthreads();
    if (threadIdx.x < 32) {
        float v = 0.f;
#pragma unroll
        for (int i = 0; i < 8; i++) v += red[i][threadIdx.x];
        g_mod[blockIdx.x * 32 + threadIdx.x] = bf16_round(v);
    }
    TS(4, 1);
}

__global__ void __launch_bounds__(256) ln1_kernel(const __nv_bfloat16* __restrict__ x) {
    pdl_launch();
    const int warp = threadIdx.x >> 5, lane = threadIdx.x & 31;
    const int row = blockIdx.x * 8 + warp;
    float v[20];
#pragma unroll
    for (int i = 0; i < 5; i++) {
        uint2 u = __ldg(reinterpret_cast<const uint2*>(x + (size_t)row * D_MODEL + (lane + 32 * i) * 4));
        v[4 * i] = bf16lo(u.x); v[4 * i + 1] = bf16hi(u.x); v[4 * i + 2] = bf16lo(u.y); v[4 * i + 3] = bf16hi(u.y);
    }
    float s = 0.f;
#pragma unroll
    for (int i = 0; i < 20; i++) s += v[i];
#pragma unroll
    for (int o = 16; o > 0; o >>= 1) s += __shfl_xor_sync(0xffffffffu, s, o);
    const float mean = s * (1.f / D_MODEL);
    float q = 0.f;
#pragma unroll
    for (int i = 0; i < 20; i++) { float d = v[i] - mean; q += d * d; }
#pragma unroll
    for (int o = 16; o > 0; o >>= 1) q += __shfl_xor_sync(0xffffffffu, q, o);
    const float rstd = rsqrtf(q * (1.f / D_MODEL) + LN_EPS);
    if (blockIdx.x < 128) TS(4, 2);
    pdl_wait();
    if (blockIdx.x < 128) TS(4, 3);
#pragma unroll
    for (int i = 0; i < 5; i++) {
        int c0 = (lane + 32 * i) * 4;
        float4 sa = *reinterpret_cast<const float4*>(g_mod + c0);
        float4 ca = *reinterpret_cast<const float4*>(g_mod + D_MODEL + c0);
        float o0 = (v[4 * i] - mean) * rstd * bf16_round(1.f + ca.x) + sa.x;
        float o1 = (v[4 * i + 1] - mean) * rstd * bf16_round(1.f + ca.y) + sa.y;
        float o2 = (v[4 * i + 2] - mean) * rstd * bf16_round(1.f + ca.z) + sa.z;
        float o3 = (v[4 * i + 3] - mean) * rstd * bf16_round(1.f + ca.w) + sa.w;
        uint2 u; u.x = pack_bf16(o0, o1); u.y = pack_bf16(o2, o3);
        *reinterpret_cast<uint2*>(g_h + (size_t)row * D_MODEL + c0) = u;
    }
}

#define PINGPONG 1
constexpr int ATT_STAGES = 6;
constexpr int ATT_STAGE_BYTES = 32768;
constexpr int ATT_SMEM = ATT_STAGES * ATT_STAGE_BYTES + 2 * 16384 + 1024 + 256;

__global__ void __cluster_dims__(2, 1, 1) __launch_bounds__(384, 1)
attn_kernel(const __grid_constant__ CUtensorMap tm_h, const __grid_constant__ CUtensorMap tm_wq,
            const __grid_constant__ CUtensorMap tm_k, const __grid_constant__ CUtensorMap tm_v,
            const __grid_constant__ CUtensorMap tm_o) {
    extern __shared__ uint8_t smem_raw[];
    const uint32_t base = (smem_u32(smem_raw) + 1023u) & ~1023u;
    const uint32_t ring = base;
    const uint32_t park = base + ATT_STAGES * ATT_STAGE_BYTES;
    const uint32_t bars = park + 2 * 16384;
    const uint32_t cta_rank = cluster_ctarank();
    const int cluster_id = blockIdx.x >> 1;
    const int qpair = cluster_id & 7, hgroup = cluster_id >> 3;
    const int q0 = (qpair * 2 + (int)cta_rank) * 128;
    const int wg = threadIdx.x >> 7;

    if (threadIdx.x == 0) {
        for (int i = 0; i < ATT_STAGES; i++) {
            mbar_init(bars + 8 * i, 1);
            mbar_init(bars + 8 * (ATT_STAGES + i), 4);
        }
        fence_mbar_init();
    }
    __syncthreads();
    cluster_sync();
    pdl_launch();

    if (wg == 2) {
        reg_dealloc<24>();
        if (threadIdx.x == 256) {
            tma_prefetch_desc(&tm_h); tma_prefetch_desc(&tm_wq); tma_prefetch_desc(&tm_k); tma_prefetch_desc(&tm_v);
            uint32_t st = 0, ph = 1;
            auto acquire = [&]() -> uint32_t {
                mbar_wait_cluster(bars + 8 * (ATT_STAGES + st), ph);
                mbar_expect_tx(bars + 8 * st, ATT_STAGE_BYTES);
                return ring + st * ATT_STAGE_BYTES;
            };
            auto advance = [&]() { if (++st == ATT_STAGES) { st = 0; ph ^= 1; } };
            pdl_wait();
            for (int hp = 0; hp < 2; hp++) {
                const int head0 = hgroup * 4 + hp * 2;
                for (int kk2 = 0; kk2 < 5; kk2++) {
                    uint32_t dst = acquire();
                    tma_load_2d(dst, &tm_h, (2 * kk2) * 64, q0, bars + 8 * st);
                    tma_load_2d(dst + 16384, &tm_h, (2 * kk2 + 1) * 64, q0, bars + 8 * st);
                    advance();
                    for (int u = 0; u < 2; u++) {
                        dst = acquire();
                        const int kb = 2 * kk2 + u;
#pragma unroll
                        for (int c = 0; c < 2; c++) {
                            const int chunk = 2 * (int)cta_rank + c;
                            tma_load_2d_mc(dst + chunk * 8192, &tm_wq, head0 * 128 + chunk * 64, kb * 64, bars + 8 * st, 3);
                        }
                        advance();
                    }
                }
                for (int t = 0; t <= 8; t++) {
                    if (t < 8) {
                        uint32_t dst = acquire();
                        const int row = (head0 + (t >> 2)) * S_KV + (S_KV - WIN) + (t & 3) * 128;
                        tma_load_2d_mc(dst + cta_rank * 16384, &tm_k, cta_rank * 64, row, bars + 8 * st, 3);
                        advance();
                    }
                    if (t > 0) {
                        uint32_t dst = acquire();
                        const int tv = t - 1;
                        const int row = (head0 + (tv >> 2)) * S_KV + (S_KV - WIN) + (tv & 3) * 128;
                        tma_load_2d_mc(dst + cta_rank * 16384, &tm_v, cta_rank * 64, row, bars + 8 * st, 3);
                        advance();
                    }
                }
            }
        }
        __syncwarp();
        asm volatile("barrier.cluster.arrive.release.aligned; // producer\n barrier.cluster.wait.acquire.aligned;" ::: "memory");
    } else {
        reg_alloc<240>();
        const int tid = threadIdx.x & 127;
        const int warp = tid >> 5, lane = tid & 31;
        const uint32_t mypark = park + wg * 16384;
        const float cscale = 0.08838834764831845f * 1.4426950408889634f;
        uint32_t st = 0, ph = 0;
        auto wait_full = [&]() -> uint32_t {
            mbar_wait(bars + 8 * st, ph);
            return ring + st * ATT_STAGE_BYTES;
        };
        auto release = [&](uint32_t s) {
            if (tid == 0) mbar_arrive_cluster(bars + 8 * (ATT_STAGES + s), 0);
            if (tid == 32) mbar_arrive_cluster(bars + 8 * (ATT_STAGES + s), 1);
        };
        auto advance = [&]() { if (++st == ATT_STAGES) { st = 0; ph ^= 1; } };
        auto turn_wait = [&]() { if (PINGPONG) bar_sync(3 + wg, 256); };
        auto turn_pass = [&]() { if (PINGPONG) bar_arrive(3 + (wg ^ 1), 256); };
        if (PINGPONG && wg == 1) bar_arrive(3, 256);

        TS(0, 0);
        for (int hp = 0; hp < 2; hp++) {
            const int head0 = hgroup * 4 + hp * 2;
            uint32_t q[8][4];
            {
                float acc[128];
#pragma unroll
                for (int i = 0; i < 128; i++) acc[i] = 0.f;
                for (int kk2 = 0; kk2 < 5; kk2++) {
                    const uint32_t hbuf = wait_full();
                    if (kk2 == 0) TS(0, 1 + hp * 5);
                    const uint32_t sth = st;
                    advance();
#pragma unroll
                    for (int u = 0; u < 2; u++) {
                        const uint32_t wbuf = wait_full();
                        const uint32_t stw = st;
                        advance();
                        wgmma_fence();
#pragma unroll
                        for (int k = 0; k < 4; k++) {
                            uint64_t da = make_desc(hbuf + u * 16384 + wg * 8192 + k * 32, 16, 1024, 1);
                            uint64_t db = make_desc(wbuf + k * 2048, 8192, 1024, 1);
                            wgmma_ss_n256_t1(acc, da, db, (kk2 | u | k) != 0);
                        }
                        wgmma_commit();
                        wgmma_wait<0>();
                        release(stw);
                    }
                    release(sth);
                }
                fence_regs(acc);
                TS(0, 2 + hp * 5);
                if (tid == 0) tma_store_wait_read<0>();
                bar_sync(1 + wg, 128);
#pragma unroll
                for (int i = 0; i < 8; i++) {
                    q[i][0] = pack_bf16(acc[8 * i + 0], acc[8 * i + 1]);
                    q[i][1] = pack_bf16(acc[8 * i + 2], acc[8 * i + 3]);
                    q[i][2] = pack_bf16(acc[8 * i + 4], acc[8 * i + 5]);
                    q[i][3] = pack_bf16(acc[8 * i + 6], acc[8 * i + 7]);
                    uint32_t b0 = pack_bf16(acc[64 + 8 * i + 0], acc[64 + 8 * i + 1]);
                    uint32_t b1 = pack_bf16(acc[64 + 8 * i + 2], acc[64 + 8 * i + 3]);
                    uint32_t b2 = pack_bf16(acc[64 + 8 * i + 4], acc[64 + 8 * i + 5]);
                    uint32_t b3 = pack_bf16(acc[64 + 8 * i + 6], acc[64 + 8 * i + 7]);
                    asm volatile("st.shared.v4.b32 [%0], {%1, %2, %3, %4};" ::"r"(mypark + (i * 128 + tid) * 16), "r"(b0), "r"(b1),
                                 "r"(b2), "r"(b3) : "memory");
                }
            }
            float o[64], s[64];
            uint32_t p[8][4];
            float m0, m1, l0, l1, a0, a1, lo0, lo1;
#pragma unroll
            for (int i = 0; i < 64; i++) { o[i] = 0.f; s[i] = 0.f; }

            auto issue_s = [&]() -> uint32_t {
                const uint32_t kbuf = wait_full();
                const uint32_t stk = st;
                advance();
                wgmma_fence();
#pragma unroll
                for (int k = 0; k < 8; k++) {
                    uint64_t db = make_desc(kbuf + (k >> 2) * 16384 + (k & 3) * 32, 16, 1024, 1);
                    wgmma_rs_n128_t0(s, q[k], db, k != 0);
                }
                wgmma_commit();
                return stk;
            };
            auto issue_pv = [&](bool fresh) -> uint32_t {
                const uint32_t vbuf = wait_full();
                const uint32_t stv = st;
                advance();
                wgmma_fence();
#pragma unroll
                for (int k = 0; k < 8; k++) {
                    uint64_t db = make_desc(vbuf + k * 2048, 16384, 1024, 1);
                    wgmma_rs_n128_t1(o, p[k], db, (!fresh) || k != 0);
                }
                wgmma_commit();
                return stv;
            };
            auto softmax = [&](bool first) {
                float mx0 = fmaxf(s[0], s[1]), mx1 = fmaxf(s[2], s[3]);
#pragma unroll
                for (int j = 1; j < 16; j++) {
                    mx0 = fmaxf(mx0, fmaxf(s[4 * j], s[4 * j + 1]));
                    mx1 = fmaxf(mx1, fmaxf(s[4 * j + 2], s[4 * j + 3]));
                }
                mx0 = fmaxf(mx0, __shfl_xor_sync(0xffffffffu, mx0, 1));
                mx0 = fmaxf(mx0, __shfl_xor_sync(0xffffffffu, mx0, 2));
                mx1 = fmaxf(mx1, __shfl_xor_sync(0xffffffffu, mx1, 1));
                mx1 = fmaxf(mx1, __shfl_xor_sync(0xffffffffu, mx1, 2));
                if (first) {
                    lo0 = l0; lo1 = l1;
                    m0 = mx0; m1 = mx1; l0 = 0.f; l1 = 0.f; a0 = 0.f; a1 = 0.f;
                } else {
                    float mn0 = fmaxf(m0, mx0), mn1 = fmaxf(m1, mx1);
                    a0 = ex2((m0 - mn0) * cscale); a1 = ex2((m1 - mn1) * cscale);
                    m0 = mn0; m1 = mn1;
                }
                const float mc0 = m0 * cscale, mc1 = m1 * cscale;
                float r0 = 0.f, r1 = 0.f;
#pragma unroll
                for (int j = 0; j < 16; j++) {
                    s[4 * j] = ex2(fmaf(s[4 * j], cscale, -mc0));
                    s[4 * j + 1] = ex2(fmaf(s[4 * j + 1], cscale, -mc0));
                    s[4 * j + 2] = ex2(fmaf(s[4 * j + 2], cscale, -mc1));
                    s[4 * j + 3] = ex2(fmaf(s[4 * j + 3], cscale, -mc1));
                    r0 += s[4 * j] + s[4 * j + 1];
                    r1 += s[4 * j + 2] + s[4 * j + 3];
                }
                l0 = l0 * a0 + r0; l1 = l1 * a1 + r1;
            };
            auto convert_p = [&]() {
#pragma unroll
                for (int i = 0; i < 8; i++) {
                    p[i][0] = pack_bf16(s[8 * i + 0], s[8 * i + 1]);
                    p[i][1] = pack_bf16(s[8 * i + 2], s[8 * i + 3]);
                    p[i][2] = pack_bf16(s[8 * i + 4], s[8 * i + 5]);
                    p[i][3] = pack_bf16(s[8 * i + 6], s[8 * i + 7]);
                }
            };
            auto store_o = [&](float ls0, float ls1, int head) {
                float s0 = ls0 + __shfl_xor_sync(0xffffffffu, ls0, 1); s0 += __shfl_xor_sync(0xffffffffu, s0, 2);
                float s1 = ls1 + __shfl_xor_sync(0xffffffffu, ls1, 1); s1 += __shfl_xor_sync(0xffffffffu, s1, 2);
                const float i0 = 1.f / s0, i1 = 1.f / s1;
                if (tid == 0) tma_store_wait_read<0>();
                bar_sync(1 + wg, 128);
#pragma unroll
                for (int j = 0; j < 16; j += 2) {
                    const int mi = lane >> 3;
                    const int row = warp * 16 + (mi & 1) * 8 + (lane & 7);
                    const int grp = j + (mi >> 1);
                    const uint32_t addr = mypark + (grp >> 3) * 8192 + row * 128 + (((grp & 7) ^ (row & 7)) << 4);
                    stmatrix_x4(addr, pack_bf16(o[4 * j] * i0, o[4 * j + 1] * i0), pack_bf16(o[4 * j + 2] * i1, o[4 * j + 3] * i1),
                                pack_bf16(o[4 * j + 4] * i0, o[4 * j + 5] * i0), pack_bf16(o[4 * j + 6] * i1, o[4 * j + 7] * i1));
                }
                fence_proxy_async();
                bar_sync(1 + wg, 128);
                if (tid == 0) {
                    tma_store_2d(&tm_o, mypark, head * 128, q0 + wg * 64);
                    tma_store_2d(&tm_o, mypark + 8192, head * 128 + 64, q0 + wg * 64);
                    tma_store_commit();
                }
            };

            l0 = 0.f; l1 = 0.f;
            {
                turn_wait();
                uint32_t stk = issue_s();
                turn_pass();
                wgmma_wait<0>();
                fence_regs(s);
                release(stk);
                softmax(true);
                convert_p();
                TS(0, 3 + hp * 5);
            }
#pragma unroll 1
            for (int t = 1; t < 8; t++) {
                const bool first = (t == 4);
                if (t == 4) {
#pragma unroll
                    for (int i = 0; i < 8; i++) {
                        asm volatile("ld.shared.v4.b32 {%0, %1, %2, %3}, [%4];" : "=r"(q[i][0]), "=r"(q[i][1]), "=r"(q[i][2]), "=r"(q[i][3])
                                     : "r"(mypark + (i * 128 + tid) * 16) : "memory");
                    }
                }
                turn_wait();
                uint32_t stk = issue_s();
                uint32_t stv = issue_pv(t == 1 || t == 5);
                turn_pass();
                wgmma_wait<1>();
                fence_regs(s);
                release(stk);
                softmax(first);
                wgmma_wait<0>();
                fence_regs(o);
                release(stv);
                if (first) {
                    store_o(lo0, lo1, head0);
                } else {
#pragma unroll
                    for (int j = 0; j < 16; j++) {
                        o[4 * j] *= a0; o[4 * j + 1] *= a0; o[4 * j + 2] *= a1; o[4 * j + 3] *= a1;
                    }
                }
                convert_p();
            }
            {
                turn_wait();
                uint32_t stv = issue_pv(false);
                turn_pass();
                wgmma_wait<0>();
                fence_regs(o);
                release(stv);
                TS(0, 4 + hp * 5);
                store_o(l0, l1, head0 + 1);
                TS(0, 5 + hp * 5);
            }
        }
        if (tid == 0) tma_store_wait<0>();
        cluster_sync();
    }
}

__device__ float g_part[4 * S_LEN * D_MODEL];
constexpr int OP_STAGES = 4;
constexpr int OP_STAGE_BYTES = 16384 + 40960;
constexpr int OP_SMEM = OP_STAGES * OP_STAGE_BYTES + 1024 + 256;

__global__ void __cluster_dims__(2, 1, 1) __launch_bounds__(384, 1)
oproj_kernel(const __grid_constant__ CUtensorMap tm_a, const __grid_constant__ CUtensorMap tm_b) {
    extern __shared__ uint8_t smem_raw[];
    const uint32_t base = (smem_u32(smem_raw) + 1023u) & ~1023u;
    const uint32_t bars = base + OP_STAGES * OP_STAGE_BYTES;
    const uint32_t rank = cluster_ctarank();
    const int cid = blockIdx.x >> 1;
    const int m0 = ((cid & 7) * 2 + (int)rank) * 128;
    const int n0 = ((cid >> 3) & 1) * 320;
    const int kq = cid >> 4;
    const int wg = threadIdx.x >> 7;

    if (threadIdx.x == 0) {
        for (int i = 0; i < OP_STAGES; i++) {
            mbar_init(bars + 8 * i, 1);
            mbar_init(bars + 8 * (OP_STAGES + i), 4);
        }
        fence_mbar_init();
    }
    __syncthreads();
    cluster_sync();
    pdl_launch();

    if (wg == 2) {
        reg_dealloc<40>();
        if (threadIdx.x == 256) {
            tma_prefetch_desc(&tm_a); tma_prefetch_desc(&tm_b);
            pdl_wait();
            uint32_t st = 0, ph = 1;
            for (int i = 0; i < 16; i++) {
                mbar_wait(bars + 8 * (OP_STAGES + st), ph);
                mbar_expect_tx(bars + 8 * st, OP_STAGE_BYTES);
                const uint32_t dst = base + st * OP_STAGE_BYTES;
                const int k0 = kq * 1024 + i * 64;
                tma_load_2d(dst, &tm_a, k0, m0, bars + 8 * st);
#pragma unroll
                for (int c = 0; c < 5; c++)
                    if (((c + i) & 1) == (int)rank) tma_load_2d_mc(dst + 16384 + c * 8192, &tm_b, n0 + c * 64, k0, bars + 8 * st, 3);
                if (++st == OP_STAGES) { st = 0; ph ^= 1; }
            }
        }
        __syncwarp();
        asm volatile("barrier.cluster.arrive.release.aligned; // producer\n barrier.cluster.wait.acquire.aligned;" ::: "memory");
    } else {
        reg_alloc<232>();
        const int tid = threadIdx.x & 127;
        const int warp = tid >> 5, lane = tid & 31;
        TS(1, 0);
        float acc0[96], acc1[64];
#pragma unroll
        for (int i = 0; i < 96; i++) acc0[i] = 0.f;
#pragma unroll
        for (int i = 0; i < 64; i++) acc1[i] = 0.f;
        uint32_t st = 0, ph = 0, prev = 0;
        for (int i = 0; i < 16; i++) {
            mbar_wait(bars + 8 * st, ph);
            if (i == 0) TS(1, 1);
            const uint32_t buf = base + st * OP_STAGE_BYTES;
            wgmma_fence();
#pragma unroll
            for (int k = 0; k < 4; k++) {
                uint64_t da = make_desc(buf + wg * 8192 + k * 32, 16, 1024, 1);
                wgmma_ss_n192_t1(acc0, da, make_desc(buf + 16384 + k * 2048, 8192, 1024, 1), 1);
                wgmma_ss_n128_t1(acc1, da, make_desc(buf + 16384 + 3 * 8192 + k * 2048, 8192, 1024, 1), 1);
            }
            wgmma_commit();
            if (i > 0) {
                wgmma_wait<1>();
                if (tid == 0) mbar_arrive_cluster(bars + 8 * (OP_STAGES + prev), 0);
                if (tid == 32) mbar_arrive_cluster(bars + 8 * (OP_STAGES + prev), 1);
            }
            prev = st;
            if (++st == OP_STAGES) { st = 0; ph ^= 1; }
        }
        wgmma_wait<0>();
        fence_regs(acc0); fence_regs(acc1);
        TS(1, 2);
        float* dst = g_part + ((size_t)kq * S_LEN + m0 + wg * 64 + warp * 16 + (lane >> 2)) * D_MODEL + n0 + (lane & 3) * 2;
#pragma unroll
        for (int j = 0; j < 24; j++) {
            *reinterpret_cast<float2*>(dst + j * 8) = make_float2(acc0[4 * j], acc0[4 * j + 1]);
            *reinterpret_cast<float2*>(dst + 8 * D_MODEL + j * 8) = make_float2(acc0[4 * j + 2], acc0[4 * j + 3]);
        }
#pragma unroll
        for (int j = 0; j < 16; j++) {
            *reinterpret_cast<float2*>(dst + 192 + j * 8) = make_float2(acc1[4 * j], acc1[4 * j + 1]);
            *reinterpret_cast<float2*>(dst + 8 * D_MODEL + 192 + j * 8) = make_float2(acc1[4 * j + 2], acc1[4 * j + 3]);
        }
        TS(1, 3);
        cluster_sync();
    }
}

__global__ void __launch_bounds__(256) ln2_kernel(const __nv_bfloat16* __restrict__ x) {
    pdl_launch();
    const int warp = threadIdx.x >> 5, lane = threadIdx.x & 31;
    const int row = blockIdx.x * 8 + warp;
    uint2 xr[5];
#pragma unroll
    for (int i = 0; i < 5; i++) xr[i] = __ldg(reinterpret_cast<const uint2*>(x + (size_t)row * D_MODEL + (lane + 32 * i) * 4));
    if (blockIdx.x < 128) TS(4, 4);
    pdl_wait();
    if (blockIdx.x < 128) TS(4, 5);
    float v[20];
    float4 pp[4][5];
#pragma unroll
    for (int s = 0; s < 4; s++)
#pragma unroll
        for (int i = 0; i < 5; i++)
            pp[s][i] = *reinterpret_cast<const float4*>(g_part + ((size_t)s * S_LEN + row) * D_MODEL + (lane + 32 * i) * 4);
#pragma unroll
    for (int i = 0; i < 5; i++) {
        const int c0 = (lane + 32 * i) * 4;
        float4 g = *reinterpret_cast<const float4*>(g_mod + 2 * D_MODEL + c0);
        float a0 = (pp[0][i].x + pp[1][i].x) + (pp[2][i].x + pp[3][i].x);
        float a1 = (pp[0][i].y + pp[1][i].y) + (pp[2][i].y + pp[3][i].y);
        float a2 = (pp[0][i].z + pp[1][i].z) + (pp[2][i].z + pp[3][i].z);
        float a3 = (pp[0][i].w + pp[1][i].w) + (pp[2][i].w + pp[3][i].w);
        v[4 * i + 0] = bf16_round(bf16lo(xr[i].x) + bf16_round(g.x * bf16_round(a0)));
        v[4 * i + 1] = bf16_round(bf16hi(xr[i].x) + bf16_round(g.y * bf16_round(a1)));
        v[4 * i + 2] = bf16_round(bf16lo(xr[i].y) + bf16_round(g.z * bf16_round(a2)));
        v[4 * i + 3] = bf16_round(bf16hi(xr[i].y) + bf16_round(g.w * bf16_round(a3)));
        uint2 u; u.x = pack_bf16(v[4 * i], v[4 * i + 1]); u.y = pack_bf16(v[4 * i + 2], v[4 * i + 3]);
        *reinterpret_cast<uint2*>(g_x1 + (size_t)row * D_MODEL + c0) = u;
    }
    float s = 0.f;
#pragma unroll
    for (int i = 0; i < 20; i++) s += v[i];
#pragma unroll
    for (int o = 16; o > 0; o >>= 1) s += __shfl_xor_sync(0xffffffffu, s, o);
    const float mean = s * (1.f / D_MODEL);
    float q = 0.f;
#pragma unroll
    for (int i = 0; i < 20; i++) { float d = v[i] - mean; q += d * d; }
#pragma unroll
    for (int o = 16; o > 0; o >>= 1) q += __shfl_xor_sync(0xffffffffu, q, o);
    const float rstd = rsqrtf(q * (1.f / D_MODEL) + LN_EPS);
#pragma unroll
    for (int i = 0; i < 5; i++) {
        const int c0 = (lane + 32 * i) * 4;
        float4 sb = *reinterpret_cast<const float4*>(g_mod + 3 * D_MODEL + c0);
        float4 cb = *reinterpret_cast<const float4*>(g_mod + 4 * D_MODEL + c0);
        float o0 = (v[4 * i] - mean) * rstd * bf16_round(1.f + cb.x) + sb.x;
        float o1 = (v[4 * i + 1] - mean) * rstd * bf16_round(1.f + cb.y) + sb.y;
        float o2 = (v[4 * i + 2] - mean) * rstd * bf16_round(1.f + cb.z) + sb.z;
        float o3 = (v[4 * i + 3] - mean) * rstd * bf16_round(1.f + cb.w) + sb.w;
        uint2 u; u.x = pack_bf16(o0, o1); u.y = pack_bf16(o2, o3);
        *reinterpret_cast<uint2*>(g_h2 + (size_t)row * D_MODEL + c0) = u;
    }
    if (blockIdx.x < 128) TS(4, 6);
}

constexpr int GU_STAGES = 4;
constexpr int GU_STAGE_BYTES = 16384 + 32768;
constexpr int GU_SMEM = GU_STAGES * GU_STAGE_BYTES + 32768 + 1024 + 256;

__device__ __forceinline__ float silu_mul(float g, float u) {
    return __fdividef(g, 1.f + __expf(-g)) * u;
}

__global__ void __cluster_dims__(2, 1, 1) __launch_bounds__(384, 1)
gateup_kernel(const __grid_constant__ CUtensorMap tm_a, const __grid_constant__ CUtensorMap tm_g128,
              const __grid_constant__ CUtensorMap tm_u128, const __grid_constant__ CUtensorMap tm_g64,
              const __grid_constant__ CUtensorMap tm_u64, const __grid_constant__ CUtensorMap tm_st64,
              const __grid_constant__ CUtensorMap tm_st24) {
    extern __shared__ uint8_t smem_raw[];
    const uint32_t base = (smem_u32(smem_raw) + 1023u) & ~1023u;
    const uint32_t stage_o = base + GU_STAGES * GU_STAGE_BYTES;
    const uint32_t bars = stage_o + 32768;
    const uint32_t rank = cluster_ctarank();
    const int cid = blockIdx.x >> 1;
    const int fs = cid & 7;
    const int m0 = ((cid >> 3) * 2 + (int)rank) * 128;
    const int f0 = fs * 216;
    const int wg = threadIdx.x >> 7;

    if (threadIdx.x == 0) {
        for (int i = 0; i < GU_STAGES; i++) {
            mbar_init(bars + 8 * i, 1);
            mbar_init(bars + 8 * (GU_STAGES + i), 4);
        }
        fence_mbar_init();
    }
    __syncthreads();
    cluster_sync();
    pdl_launch();

    if (wg == 2) {
        reg_dealloc<40>();
        if (threadIdx.x == 256) {
            tma_prefetch_desc(&tm_a); tma_prefetch_desc(&tm_g128); tma_prefetch_desc(&tm_u128);
            tma_prefetch_desc(&tm_g64); tma_prefetch_desc(&tm_u64);
            pdl_wait();
            uint32_t st = 0, ph = 1;
            const CUtensorMap* t128 = rank == 0 ? &tm_g128 : &tm_u128;
            const CUtensorMap* t64 = rank == 0 ? &tm_g64 : &tm_u64;
            for (int i = 0; i < 20; i++) {
                const int kb = i < 10 ? i : i - 10;
                mbar_wait(bars + 8 * (GU_STAGES + st), ph);
                const uint32_t dst = base + st * GU_STAGE_BYTES;
                if (i < 10) {
                    mbar_expect_tx(bars + 8 * st, 16384 + 32768);
                    tma_load_2d(dst, &tm_a, kb * 64, m0, bars + 8 * st);
                    tma_load_2d_mc(dst + 16384 + rank * 16384, t128, f0, kb * 64, bars + 8 * st, 3);
                    tma_load_2d_mc(dst + 16384 + rank * 16384 + 8192, t128, f0 + 64, kb * 64, bars + 8 * st, 3);
                } else {
                    mbar_expect_tx(bars + 8 * st, 16384 + 24576);
                    tma_load_2d(dst, &tm_a, kb * 64, m0, bars + 8 * st);
#pragma unroll
                    for (int c = 0; c < 3; c++)
                        tma_load_2d_mc(dst + 16384 + rank * 12288 + c * 4096, t64, f0 + 128 + c * 32, kb * 64, bars + 8 * st, 3);
                }
                if (++st == GU_STAGES) { st = 0; ph ^= 1; }
            }
        }
        __syncwarp();
        asm volatile("barrier.cluster.arrive.release.aligned; // producer\n barrier.cluster.wait.acquire.aligned;" ::: "memory");
    } else {
        reg_alloc<232>();
        const int tid = threadIdx.x & 127;
        const int w = tid >> 5, lane = tid & 31;
        uint32_t st = 0, ph = 0, prev = 0;
        const uint32_t mystage = stage_o + wg * 16384;
        auto release = [&](uint32_t s) {
            if (tid == 0) mbar_arrive_cluster(bars + 8 * (GU_STAGES + s), 0);
            if (tid == 32) mbar_arrive_cluster(bars + 8 * (GU_STAGES + s), 1);
        };
        TS(2, 0);
        pdl_wait();
        TS(2, 1);
        {
            float acc[128];
#pragma unroll
            for (int i = 0; i < 128; i++) acc[i] = 0.f;
            for (int i = 0; i < 10; i++) {
                mbar_wait(bars + 8 * st, ph);
                if (i == 0) TS(2, 2);
                const uint32_t buf = base + st * GU_STAGE_BYTES;
                wgmma_fence();
#pragma unroll
                for (int k = 0; k < 4; k++) {
                    uint64_t da = make_desc(buf + wg * 8192 + k * 32, 16, 1024, 1);
                    uint64_t db = make_desc(buf + 16384 + k * 2048, 8192, 1024, 1);
                    wgmma_ss_n256_t1(acc, da, db, 1);
                }
                wgmma_commit();
                if (i > 0) { wgmma_wait<1>(); release(prev); }
                prev = st;
                if (++st == GU_STAGES) { st = 0; ph ^= 1; }
            }
            wgmma_wait<0>();
            release(prev);
            fence_regs(acc);
            TS(2, 3);
#pragma unroll
            for (int j = 0; j < 16; j += 2) {
                const int mi = lane >> 3;
                const int row = w * 16 + (mi & 1) * 8 + (lane & 7);
                const int grp = j + (mi >> 1);
                const uint32_t addr = mystage + (grp >> 3) * 8192 + row * 128 + (((grp & 7) ^ (row & 7)) << 4);
                stmatrix_x4(addr, pack_bf16(silu_mul(acc[4 * j], acc[64 + 4 * j]), silu_mul(acc[4 * j + 1], acc[64 + 4 * j + 1])),
                            pack_bf16(silu_mul(acc[4 * j + 2], acc[64 + 4 * j + 2]), silu_mul(acc[4 * j + 3], acc[64 + 4 * j + 3])),
                            pack_bf16(silu_mul(acc[4 * j + 4], acc[64 + 4 * j + 4]), silu_mul(acc[4 * j + 5], acc[64 + 4 * j + 5])),
                            pack_bf16(silu_mul(acc[4 * j + 6], acc[64 + 4 * j + 6]), silu_mul(acc[4 * j + 7], acc[64 + 4 * j + 7])));
            }
            fence_proxy_async();
            bar_sync(1 + wg, 128);
            if (tid == 0) {
                tma_store_2d(&tm_st64, mystage, f0, m0 + wg * 64);
                tma_store_2d(&tm_st64, mystage + 8192, f0 + 64, m0 + wg * 64);
                tma_store_commit();
            }
        }
        TS(2, 4);
        {
            float acc[92];
#pragma unroll
            for (int i = 0; i < 92; i++) acc[i] = 0.f;
            for (int i = 0; i < 10; i++) {
                mbar_wait(bars + 8 * st, ph);
                const uint32_t buf = base + st * GU_STAGE_BYTES;
                wgmma_fence();
#pragma unroll
                for (int k = 0; k < 4; k++) {
                    uint64_t da = make_desc(buf + wg * 8192 + k * 32, 16, 1024, 1);
                    uint64_t db = make_desc(buf + 16384 + k * 1024, 4096, 512, 2);
                    wgmma_ss_n184_t1(acc, da, db, 1);
                }
                wgmma_commit();
                if (i > 0) { wgmma_wait<1>(); release(prev); }
                prev = st;
                if (++st == GU_STAGES) { st = 0; ph ^= 1; }
            }
            wgmma_wait<0>();
            fence_regs(acc);
            TS(2, 5);
            if (tid == 0) tma_store_wait_read<0>();
            bar_sync(1 + wg, 128);
#pragma unroll
            for (int j = 0; j < 8; j += 2) {
                const int mi = lane >> 3;
                const int row = w * 16 + (mi & 1) * 8 + (lane & 7);
                const int grp = j + (mi >> 1);
                const uint32_t addr = mystage + row * 128 + ((grp ^ (row & 7)) << 4);
                stmatrix_x4(addr, pack_bf16(silu_mul(acc[4 * j], acc[48 + 4 * j]), silu_mul(acc[4 * j + 1], acc[48 + 4 * j + 1])),
                            pack_bf16(silu_mul(acc[4 * j + 2], acc[48 + 4 * j + 2]), silu_mul(acc[4 * j + 3], acc[48 + 4 * j + 3])),
                            pack_bf16(silu_mul(acc[4 * j + 4], acc[48 + 4 * j + 4]), silu_mul(acc[4 * j + 5], acc[48 + 4 * j + 5])),
                            pack_bf16(silu_mul(acc[4 * j + 6], acc[48 + 4 * j + 6]), silu_mul(acc[4 * j + 7], acc[48 + 4 * j + 7])));
            }
            {
                const int mi = lane >> 3;
                const int row = w * 16 + (mi & 1) * 8 + (lane & 7);
                const uint32_t addr = mystage + 8192 + row * 48 + (mi >> 1) * 16;
                stmatrix_x4(addr, pack_bf16(silu_mul(acc[32], acc[80]), silu_mul(acc[33], acc[81])),
                            pack_bf16(silu_mul(acc[34], acc[82]), silu_mul(acc[35], acc[83])),
                            pack_bf16(silu_mul(acc[36], acc[84]), silu_mul(acc[37], acc[85])),
                            pack_bf16(silu_mul(acc[38], acc[86]), silu_mul(acc[39], acc[87])));
                const uint32_t addr2 = mystage + 8192 + (w * 16 + ((lane >> 3) & 1) * 8 + (lane & 7)) * 48 + 32;
                asm volatile("stmatrix.sync.aligned.m8n8.x2.shared.b16 [%0], {%1, %2};" ::"r"(addr2),
                             "r"(pack_bf16(silu_mul(acc[40], acc[88]), silu_mul(acc[41], acc[89]))),
                             "r"(pack_bf16(silu_mul(acc[42], acc[90]), silu_mul(acc[43], acc[91]))) : "memory");
            }
            fence_proxy_async();
            bar_sync(1 + wg, 128);
            if (tid == 0) {
                tma_store_2d(&tm_st64, mystage, f0 + 128, m0 + wg * 64);
                tma_store_2d(&tm_st24, mystage + 8192, f0 + 192, m0 + wg * 64);
                tma_store_commit();
                tma_store_wait<0>();
            }
        }
        TS(2, 6);
        cluster_sync();
    }
}

constexpr int DN_STAGES = 5;
constexpr int DN_STAGE_BYTES = 16384 + 24576;
constexpr int DN_SMEM = DN_STAGES * DN_STAGE_BYTES + 1024 + 256;

__global__ void __cluster_dims__(2, 1, 1) __launch_bounds__(384, 1)
down_kernel(const __grid_constant__ CUtensorMap tm_a, const __grid_constant__ CUtensorMap tm_b, __nv_bfloat16* __restrict__ out) {
    extern __shared__ uint8_t smem_raw[];
    const uint32_t base = (smem_u32(smem_raw) + 1023u) & ~1023u;
    const uint32_t bars = base + DN_STAGES * DN_STAGE_BYTES;
    const uint32_t rank = cluster_ctarank();
    const int cid = blockIdx.x >> 1;
    const int m0 = (cid >> 2) * 128;
    const int n0 = (cid & 3) * 160;
    const int kb0 = rank == 0 ? 0 : 14;
    const int nkb = rank == 0 ? 14 : 13;
    const int wg = threadIdx.x >> 7;

    if (threadIdx.x == 0) {
        for (int i = 0; i < DN_STAGES; i++) {
            mbar_init(bars + 8 * i, 1);
            mbar_init(bars + 8 * (DN_STAGES + i), 2);
        }
        fence_mbar_init();
    }
    __syncthreads();
    pdl_launch();

    if (wg == 2) {
        reg_dealloc<40>();
        if (threadIdx.x == 256) {
            tma_prefetch_desc(&tm_a); tma_prefetch_desc(&tm_b);
            pdl_wait();
            uint32_t st = 0, ph = 1;
            for (int i = 0; i < nkb; i++) {
                mbar_wait(bars + 8 * (DN_STAGES + st), ph);
                mbar_expect_tx(bars + 8 * st, DN_STAGE_BYTES);
                const uint32_t dst = base + st * DN_STAGE_BYTES;
                const int k0 = (kb0 + i) * 64;
                tma_load_2d(dst, &tm_a, k0, m0, bars + 8 * st);
#pragma unroll
                for (int c = 0; c < 3; c++) tma_load_2d(dst + 16384 + c * 8192, &tm_b, n0 + c * 64, k0, bars + 8 * st);
                if (++st == DN_STAGES) { st = 0; ph ^= 1; }
            }
        }
        __syncwarp();
        asm volatile("barrier.cluster.arrive.release.aligned; // producer\n barrier.cluster.wait.acquire.aligned;" ::: "memory");
        asm volatile("barrier.cluster.arrive.release.aligned; // producer2\n barrier.cluster.wait.acquire.aligned;" ::: "memory");
    } else {
        reg_alloc<232>();
        const int tid = threadIdx.x & 127;
        const int warp = tid >> 5, lane = tid & 31;
        TS(3, 0);
        float acc[80];
#pragma unroll
        for (int i = 0; i < 80; i++) acc[i] = 0.f;
        uint32_t st = 0, ph = 0, prev = 0;
        for (int i = 0; i < nkb; i++) {
            mbar_wait(bars + 8 * st, ph);
            if (i == 0) TS(3, 1);
            const uint32_t buf = base + st * DN_STAGE_BYTES;
            wgmma_fence();
#pragma unroll
            for (int k = 0; k < 4; k++) {
                uint64_t da = make_desc(buf + wg * 8192 + k * 32, 16, 1024, 1);
                wgmma_ss_n160_t1(acc, da, make_desc(buf + 16384 + k * 2048, 8192, 1024, 1), 1);
            }
            wgmma_commit();
            if (i > 0) {
                wgmma_wait<1>();
                if (tid == 0) mbar_arrive(bars + 8 * (DN_STAGES + prev));
            }
            prev = st;
            if (++st == DN_STAGES) { st = 0; ph ^= 1; }
        }
        wgmma_wait<0>();
        fence_regs(acc);
        TS(3, 2);
        cluster_sync();
        {
            const uint32_t dst = mapa(base, rank ^ 1) + wg * 20480 + tid * 16;
            if (rank == 0) {
#pragma unroll
                for (int i = 0; i < 10; i++)
                    asm volatile("st.shared::cluster.v4.f32 [%0], {%1, %2, %3, %4};" ::"r"(dst + i * 2048), "f"(acc[40 + 4 * i]), "f"(acc[40 + 4 * i + 1]),
                                 "f"(acc[40 + 4 * i + 2]), "f"(acc[40 + 4 * i + 3]) : "memory");
            } else {
#pragma unroll
                for (int i = 0; i < 10; i++)
                    asm volatile("st.shared::cluster.v4.f32 [%0], {%1, %2, %3, %4};" ::"r"(dst + i * 2048), "f"(acc[4 * i]), "f"(acc[4 * i + 1]),
                                 "f"(acc[4 * i + 2]), "f"(acc[4 * i + 3]) : "memory");
            }
        }
        cluster_sync();
        {
            const uint32_t tile = base + 40960;
            const int cbase = n0 + (int)rank * 80;
#pragma unroll
            for (int j = 0; j < 10; j += 2) {
                float4 o0, o1;
                asm volatile("ld.shared.v4.f32 {%0, %1, %2, %3}, [%4];" : "=f"(o0.x), "=f"(o0.y), "=f"(o0.z), "=f"(o0.w) : "r"(base + wg * 20480 + tid * 16 + j * 2048));
                asm volatile("ld.shared.v4.f32 {%0, %1, %2, %3}, [%4];" : "=f"(o1.x), "=f"(o1.y), "=f"(o1.z), "=f"(o1.w) : "r"(base + wg * 20480 + tid * 16 + (j + 1) * 2048));
                const float2 g0 = *reinterpret_cast<const float2*>(g_mod + 5 * D_MODEL + cbase + j * 8 + (lane & 3) * 2);
                const float2 g1 = *reinterpret_cast<const float2*>(g_mod + 5 * D_MODEL + cbase + (j + 1) * 8 + (lane & 3) * 2);
                float a[8];
#pragma unroll
                for (int e = 0; e < 8; e++) a[e] = rank == 0 ? acc[4 * j + e] : acc[40 + 4 * j + e];
                const int mi = lane >> 3;
                const int row = wg * 64 + warp * 16 + (mi & 1) * 8 + (lane & 7);
                const uint32_t addr = tile + row * 176 + (j + (mi >> 1)) * 16;
                stmatrix_x4(addr, pack_bf16(g0.x * bf16_round(a[0] + o0.x), g0.y * bf16_round(a[1] + o0.y)),
                            pack_bf16(g0.x * bf16_round(a[2] + o0.z), g0.y * bf16_round(a[3] + o0.w)),
                            pack_bf16(g1.x * bf16_round(a[4] + o1.x), g1.y * bf16_round(a[5] + o1.y)),
                            pack_bf16(g1.x * bf16_round(a[6] + o1.z), g1.y * bf16_round(a[7] + o1.w)));
            }
            pdl_wait();
            bar_sync(1, 256);
            const int t = threadIdx.x;
#pragma unroll
            for (int it = 0; it < 5; it++) {
                const int idx = it * 256 + t;
                const int row = idx / 10, ch = idx - row * 10;
                uint4 tv;
                asm volatile("ld.shared.v4.b32 {%0, %1, %2, %3}, [%4];" : "=r"(tv.x), "=r"(tv.y), "=r"(tv.z), "=r"(tv.w) : "r"(tile + row * 176 + ch * 16));
                const size_t goff = (size_t)(m0 + row) * D_MODEL + cbase + ch * 8;
                const uint4 xv = *reinterpret_cast<const uint4*>(g_x1 + goff);
                uint4 r;
                r.x = pack_bf16(bf16lo(xv.x) + bf16lo(tv.x), bf16hi(xv.x) + bf16hi(tv.x));
                r.y = pack_bf16(bf16lo(xv.y) + bf16lo(tv.y), bf16hi(xv.y) + bf16hi(tv.y));
                r.z = pack_bf16(bf16lo(xv.z) + bf16lo(tv.z), bf16hi(xv.z) + bf16hi(tv.z));
                r.w = pack_bf16(bf16lo(xv.w) + bf16lo(tv.w), bf16hi(xv.w) + bf16hi(tv.w));
                *reinterpret_cast<uint4*>(out + goff) = r;
            }
        }
        TS(3, 3);
    }
}

typedef CUresult (*PFN_encodeTiled)(CUtensorMap*, CUtensorMapDataType, cuuint32_t, void*, const cuuint64_t*, const cuuint64_t*,
                                    const cuuint32_t*, const cuuint32_t*, CUtensorMapInterleave, CUtensorMapSwizzle,
                                    CUtensorMapL2promotion, CUtensorMapFloatOOBfill);

static PFN_encodeTiled get_encode() {
    static PFN_encodeTiled fn = nullptr;
    if (!fn) {
        void* p = nullptr;
        cudaDriverEntryPointQueryResult qr;
        cudaGetDriverEntryPoint("cuTensorMapEncodeTiled", &p, cudaEnableDefault, &qr);
        fn = (PFN_encodeTiled)p;
    }
    return fn;
}

static CUtensorMap make_map(const void* ptr, uint64_t rows, uint64_t cols, uint32_t box_rows, uint32_t box_cols, CUtensorMapSwizzle swz) {
    CUtensorMap m;
    cuuint64_t dims[2] = {cols, rows};
    cuuint64_t strides[1] = {cols * 2};
    cuuint32_t box[2] = {box_cols, box_rows};
    cuuint32_t es[2] = {1, 1};
    get_encode()(&m, CU_TENSOR_MAP_DATA_TYPE_BFLOAT16, 2, const_cast<void*>(ptr), dims, strides, box, es, CU_TENSOR_MAP_INTERLEAVE_NONE,
                 swz, CU_TENSOR_MAP_L2_PROMOTION_L2_256B, CU_TENSOR_MAP_FLOAT_OOB_FILL_NONE);
    return m;
}

template <typename... KArgs, typename... Args>
static void launch(void (*kernel)(KArgs...), int grid, int block, int smem, int cluster, bool pdl, Args... args) {
    cudaLaunchConfig_t cfg = {};
    cfg.gridDim = dim3(grid);
    cfg.blockDim = dim3(block);
    cfg.dynamicSmemBytes = smem;
    cfg.stream = cudaStreamPerThread;
    cudaLaunchAttribute at[2];
    int na = 0;
    if (pdl) {
        at[na].id = cudaLaunchAttributeProgrammaticStreamSerialization;
        at[na].val.programmaticStreamSerializationAllowed = 1;
        na++;
    }
    (void)cluster;
    cfg.attrs = at;
    cfg.numAttrs = na;
    cudaLaunchKernelEx(&cfg, kernel, KArgs(args)...);
}

#define USE_PDL 1

extern "C" void kernel_launch(void* const* d_in, const int* in_sizes, int n_in, void* d_out, int out_size) {
    (void)in_sizes; (void)n_in; (void)out_size;
    const __nv_bfloat16* x = (const __nv_bfloat16*)d_in[0];
    const __nv_bfloat16* kc = (const __nv_bfloat16*)d_in[1];
    const __nv_bfloat16* vc = (const __nv_bfloat16*)d_in[2];
    const __nv_bfloat16* wq = (const __nv_bfloat16*)d_in[3];
    const __nv_bfloat16* wo = (const __nv_bfloat16*)d_in[4];
    const __nv_bfloat16* wg = (const __nv_bfloat16*)d_in[6];
    const __nv_bfloat16* wu = (const __nv_bfloat16*)d_in[7];
    const __nv_bfloat16* wd = (const __nv_bfloat16*)d_in[8];
    const __nv_bfloat16* c = (const __nv_bfloat16*)d_in[9];
    const __nv_bfloat16* wmod = (const __nv_bfloat16*)d_in[10];
    __nv_bfloat16* out = (__nv_bfloat16*)d_out;

    static bool init = false;
    static void *p_h, *p_o, *p_x1, *p_h2, *p_act;
    if (!init) {
        cudaFuncSetAttribute(attn_kernel, cudaFuncAttributeMaxDynamicSharedMemorySize, ATT_SMEM);
        cudaFuncSetAttribute(oproj_kernel, cudaFuncAttributeMaxDynamicSharedMemorySize, OP_SMEM);
        cudaFuncSetAttribute(down_kernel, cudaFuncAttributeMaxDynamicSharedMemorySize, DN_SMEM);
        cudaFuncSetAttribute(gateup_kernel, cudaFuncAttributeMaxDynamicSharedMemorySize, GU_SMEM);
        cudaGetSymbolAddress(&p_h, g_h);
        cudaGetSymbolAddress(&p_o, g_o);
        cudaGetSymbolAddress(&p_x1, g_x1);
        cudaGetSymbolAddress(&p_h2, g_h2);
        cudaGetSymbolAddress(&p_act, g_act);
        init = true;
    }
    const CUtensorMapSwizzle S128 = CU_TENSOR_MAP_SWIZZLE_128B, S64 = CU_TENSOR_MAP_SWIZZLE_64B;
    CUtensorMap tm_h = make_map(p_h, S_LEN, D_MODEL, 128, 64, S128);
    CUtensorMap tm_wq = make_map(wq, D_MODEL, N_HEADS * D_HEAD, 64, 64, S128);
    CUtensorMap tm_k = make_map(kc, N_HEADS * S_KV, D_HEAD, 128, 64, S128);
    CUtensorMap tm_v = make_map(vc, N_HEADS * S_KV, D_HEAD, 128, 64, S128);
    CUtensorMap tm_o = make_map(p_o, S_LEN, N_HEADS * D_HEAD, 64, 64, S128);
    CUtensorMap tm_oa = make_map(p_o, S_LEN, N_HEADS * D_HEAD, 128, 64, S128);
    CUtensorMap tm_wo = make_map(wo, N_HEADS * D_HEAD, D_MODEL, 64, 64, S128);
    CUtensorMap tm_h2 = make_map(p_h2, S_LEN, D_MODEL, 128, 64, S128);
    CUtensorMap tm_g128 = make_map(wg, D_MODEL, D_FF, 64, 64, S128);
    CUtensorMap tm_u128 = make_map(wu, D_MODEL, D_FF, 64, 64, S128);
    CUtensorMap tm_g64 = make_map(wg, D_MODEL, D_FF, 64, 32, S64);
    CUtensorMap tm_u64 = make_map(wu, D_MODEL, D_FF, 64, 32, S64);
    CUtensorMap tm_acta = make_map(p_act, S_LEN, D_FF, 128, 64, S128);
    CUtensorMap tm_st64 = make_map(p_act, S_LEN, D_FF, 64, 64, S128);
    CUtensorMap tm_st24 = make_map(p_act, S_LEN, D_FF, 64, 24, CU_TENSOR_MAP_SWIZZLE_NONE);
    CUtensorMap tm_wd = make_map(wd, D_FF, D_MODEL, 64, 64, S128);

    const bool pdl = USE_PDL;
    launch(mod_kernel, 120, 256, 0, 1, false, c, wmod);
    launch(ln1_kernel, 256, 256, 0, 1, pdl, x);
    launch(attn_kernel, 128, 384, ATT_SMEM, 2, pdl, tm_h, tm_wq, tm_k, tm_v, tm_o);
    launch(oproj_kernel, 128, 384, OP_SMEM, 2, pdl, tm_oa, tm_wo);
    launch(ln2_kernel, 256, 256, 0, 1, pdl, x);
    launch(gateup_kernel, 128, 384, GU_SMEM, 2, pdl, tm_h2, tm_g128, tm_u128, tm_g64, tm_u64, tm_st64, tm_st24);
    launch(down_kernel, 128, 384, DN_SMEM, 2, pdl, tm_acta, tm_wd, out);
}
```

```cpp
#include <cuda_runtime.h>
#include <cuda_bf16.h>
#include <cuda.h>
#include <stdint.h>

__device__ __forceinline__ uint32_t smem_u32(const void* p) { return (uint32_t)__cvta_generic_to_shared(p); }

__device__ __forceinline__ void mbar_init(uint32_t bar, uint32_t count) {
    asm volatile("mbarrier.init.shared::cta.b64 [%0], %1;" ::"r"(bar), "r"(count) : "memory");
}
__device__ __forceinline__ void mbar_expect_tx(uint32_t bar, uint32_t bytes) {
    asm volatile("mbarrier.arrive.expect_tx.shared::cta.b64 _, [%0], %1;" ::"r"(bar), "r"(bytes) : "memory");
}
__device__ __forceinline__ void mbar_arrive(uint32_t bar) {
    asm volatile("mbarrier.arrive.shared::cta.b64 _, [%0];" ::"r"(bar) : "memory");
}
__device__ __forceinline__ void mbar_arrive_cluster(uint32_t bar, uint32_t cta) {
    asm volatile(
        "{\n.reg .b32 ra;\n"
        "mapa.shared::cluster.u32 ra, %0, %1;\n"
        "mbarrier.arrive.shared::cluster.b64 _, [ra];\n}\n" ::"r"(bar), "r"(cta)
        : "memory");
}
__device__ __forceinline__ bool mbar_try_wait(uint32_t bar, uint32_t parity) {
    uint32_t ok;
    asm volatile(
        "{\n.reg .pred p;\n"
        "mbarrier.try_wait.parity.shared::cta.b64 p, [%1], %2;\n"
        "selp.u32 %0, 1, 0, p;\n}\n"
        : "=r"(ok)
        : "r"(bar), "r"(parity)
        : "memory");
    return ok != 0;
}
__device__ __forceinline__ bool mbar_try_wait_cluster(uint32_t bar, uint32_t parity) {
    uint32_t ok;
    asm volatile(
        "{\n.reg .pred p;\n"
        "mbarrier.try_wait.parity.shared::cta.b64 p, [%1], %2;\n"
        "selp.u32 %0, 1, 0, p;\n}\n"
        : "=r"(ok)
        : "r"(bar), "r"(parity)
        : "memory");
    return ok != 0;
}
__device__ volatile int g_abort = 0;
__device__ __forceinline__ void mbar_wait(uint32_t bar, uint32_t parity) {
    uint32_t n = 0;
    while (!mbar_try_wait(bar, parity)) {
        if (++n > (1u << 20)) break;
    }
}
__device__ __forceinline__ void mbar_wait_cluster(uint32_t bar, uint32_t parity) { mbar_wait(bar, parity); }
__device__ __forceinline__ void fence_mbar_init() { asm volatile("fence.mbarrier_init.release.cluster;" ::: "memory"); }
__device__ __forceinline__ void fence_proxy_async() { asm volatile("fence.proxy.async.shared::cta;" ::: "memory"); }
__device__ __forceinline__ void fence_proxy_async_all() { asm volatile("fence.proxy.async;" ::: "memory"); }
__device__ __forceinline__ void cluster_arrive() { asm volatile("barrier.cluster.arrive.release.aligned;" ::: "memory"); }
__device__ __forceinline__ void cluster_wait() { asm volatile("barrier.cluster.wait.acquire.aligned;" ::: "memory"); }
__device__ __forceinline__ void cluster_sync() { cluster_arrive(); cluster_wait(); }
__device__ __forceinline__ uint32_t cluster_ctarank() {
    uint32_t r;
    asm volatile("mov.u32 %0, %%cluster_ctarank;" : "=r"(r));
    return r;
}
__device__ __forceinline__ void bar_sync(int id, int n) { asm volatile("bar.sync %0, %1;" ::"r"(id), "r"(n) : "memory"); }
__device__ __forceinline__ void bar_arrive(int id, int n) { asm volatile("bar.arrive %0, %1;" ::"r"(id), "r"(n) : "memory"); }
__device__ __forceinline__ void pdl_wait() { asm volatile("griddepcontrol.wait;" ::: "memory"); }
__device__ __forceinline__ void pdl_launch() { asm volatile("griddepcontrol.launch_dependents;" ::: "memory"); }

__device__ __forceinline__ void tma_prefetch_desc(const CUtensorMap* m) {
    asm volatile("prefetch.tensormap [%0];" ::"l"(m) : "memory");
}
__device__ __forceinline__ void tma_load_2d(uint32_t dst, const CUtensorMap* m, int c0, int c1, uint32_t bar) {
    asm volatile(
        "cp.async.bulk.tensor.2d.shared::cluster.global.mbarrier::complete_tx::bytes [%0], [%1, {%3, %4}], [%2];"
        ::"r"(dst), "l"(m), "r"(bar), "r"(c0), "r"(c1)
        : "memory");
}
__device__ __forceinline__ void tma_load_2d_mc(uint32_t dst, const CUtensorMap* m, int c0, int c1, uint32_t bar, uint16_t mask) {
    asm volatile(
        "cp.async.bulk.tensor.2d.shared::cluster.global.mbarrier::complete_tx::bytes.multicast::cluster [%0], [%1, {%3, %4}], [%2], %5;"
        ::"r"(dst), "l"(m), "r"(bar), "r"(c0), "r"(c1), "h"(mask)
        : "memory");
}
__device__ __forceinline__ void tma_store_2d(const CUtensorMap* m, uint32_t src, int c0, int c1) {
    asm volatile("cp.async.bulk.tensor.2d.global.shared::cta.bulk_group [%0, {%2, %3}], [%1];"
                 ::"l"(m), "r"(src), "r"(c0), "r"(c1)
                 : "memory");
}
__device__ __forceinline__ void tma_store_commit() { asm volatile("cp.async.bulk.commit_group;" ::: "memory"); }
template <int N> __device__ __forceinline__ void tma_store_wait_read() {
    asm volatile("cp.async.bulk.wait_group.read %0;" ::"n"(N) : "memory");
}
template <int N> __device__ __forceinline__ void tma_store_wait() {
    asm volatile("cp.async.bulk.wait_group %0;" ::"n"(N) : "memory");
}

__device__ __forceinline__ void wgmma_fence() { asm volatile("wgmma.fence.sync.aligned;" ::: "memory"); }
__device__ __forceinline__ void wgmma_commit() { asm volatile("wgmma.commit_group.sync.aligned;" ::: "memory"); }
template <int N> __device__ __forceinline__ void wgmma_wait() {
    asm volatile("wgmma.wait_group.sync.aligned %0;" ::"n"(N) : "memory");
}
template <int R> __device__ __forceinline__ void reg_alloc() { asm volatile("setmaxnreg.inc.sync.aligned.u32 %0;" ::"n"(R)); }
template <int R> __device__ __forceinline__ void reg_dealloc() { asm volatile("setmaxnreg.dec.sync.aligned.u32 %0;" ::"n"(R)); }

template <int N> __device__ __forceinline__ void fence_regs(float (&r)[N]) {
#pragma unroll
    for (int i = 0; i < N; i++) asm volatile("" : "+f"(r[i])::"memory");
}
template <int N> __device__ __forceinline__ void fence_regs_u(uint32_t (&r)[N][4]) {
#pragma unroll
    for (int i = 0; i < N; i++) {
#pragma unroll
        for (int j = 0; j < 4; j++) asm volatile("" : "+r"(r[i][j])::"memory");
    }
}

__device__ __forceinline__ uint64_t make_desc(uint32_t addr, uint32_t lbo_bytes, uint32_t sbo_bytes, uint32_t swz) {
    return (uint64_t)((addr & 0x3FFFF) >> 4) | ((uint64_t)(lbo_bytes >> 4) << 16) | ((uint64_t)(sbo_bytes >> 4) << 32) |
           ((uint64_t)swz << 62);
}

__device__ __forceinline__ uint32_t pack_bf16(float lo, float hi) {
    uint32_t r;
    asm("cvt.rn.bf16x2.f32 %0, %1, %2;" : "=r"(r) : "f"(hi), "f"(lo));
    return r;
}
__device__ __forceinline__ float bf16_round(float x) { return __bfloat162float(__float2bfloat16_rn(x)); }
__device__ __forceinline__ float bf16lo(uint32_t v) { return __uint_as_float(v << 16); }
__device__ __forceinline__ float bf16hi(uint32_t v) { return __uint_as_float(v & 0xffff0000u); }
__device__ __forceinline__ float ex2(float x) {
    float y;
    asm("ex2.approx.ftz.f32 %0, %1;" : "=f"(y) : "f"(x));
    return y;
}
__device__ __forceinline__ void stmatrix_x4(uint32_t addr, uint32_t r0, uint32_t r1, uint32_t r2, uint32_t r3) {
    asm volatile("stmatrix.sync.aligned.m8n8.x4.shared.b16 [%0], {%1, %2, %3, %4};" ::"r"(addr), "r"(r0), "r"(r1), "r"(r2), "r"(r3)
                 : "memory");
}
__device__ __forceinline__ uint32_t mapa(uint32_t addr, uint32_t cta) {
    uint32_t r;
    asm volatile("mapa.shared::cluster.u32 %0, %1, %2;" : "=r"(r) : "r"(addr), "r"(cta));
    return r;
}
__device__ __forceinline__ void st_cluster_v2(uint32_t addr, float a, float b) {
    asm volatile("st.shared::cluster.v2.f32 [%0], {%1, %2};" ::"r"(addr), "f"(a), "f"(b) : "memory");
}
__device__ __forceinline__ void wgmma_ss_n256_t1(float (&d)[128], uint64_t descA, uint64_t descB, int scaleD) {
    asm volatile("{\n.reg .pred p;\n"
        "setp.ne.b32 p, %130, 0;\n"
        "wgmma.mma_async.sync.aligned.m64n256k16.f32.bf16.bf16 "
        "{%0, %1, %2, %3, %4, %5, %6, %7, %8, %9, %10, %11, %12, %13, %14, %15, "
        "%16, %17, %18, %19, %20, %21, %22, %23, %24, %25, %26, %27, %28, %29, %30, %31, "
        "%32, %33, %34, %35, %36, %37, %38, %39, %40, %41, %42, %43, %44, %45, %46, %47, "
        "%48, %49, %50, %51, %52, %53, %54, %55, %56, %57, %58, %59, %60, %61, %62, %63, "
        "%64, %65, %66, %67, %68, %69, %70, %71, %72, %73, %74, %75, %76, %77, %78, %79, "
        "%80, %81, %82, %83, %84, %85, %86, %87, %88, %89, %90, %91, %92, %93, %94, %95, "
        "%96, %97, %98, %99, %100, %101, %102, %103, %104, %105, %106, %107, %108, %109, %110, %111, "
        "%112, %113, %114, %115, %116, %117, %118, %119, %120, %121, %122, %123, %124, %125, %126, %127}, "
        "%128, %129, p, 1, 1, 0, 1;\n}\n"
        :
          "+f"(d[0]), "+f"(d[1]), "+f"(d[2]), "+f"(d[3]), "+f"(d[4]), "+f"(d[5]), "+f"(d[6]), "+f"(d[7]),
          "+f"(d[8]), "+f"(d[9]), "+f"(d[10]), "+f"(d[11]), "+f"(d[12]), "+f"(d[13]), "+f"(d[14]), "+f"(d[15]),
          "+f"(d[16]), "+f"(d[17]), "+f"(d[18]), "+f"(d[19]), "+f"(d[20]), "+f"(d[21]), "+f"(d[22]), "+f"(d[23]),
          "+f"(d[24]), "+f"(d[25]), "+f"(d[26]), "+f"(d[27]), "+f"(d[28]), "+f"(d[29]), "+f"(d[30]), "+f"(d[31]),
          "+f"(d[32]), "+f"(d[33]), "+f"(d[34]), "+f"(d[35]), "+f"(d[36]), "+f"(d[37]), "+f"(d[38]), "+f"(d[39]),
          "+f"(d[40]), "+f"(d[41]), "+f"(d[42]), "+f"(d[43]), "+f"(d[44]), "+f"(d[45]), "+f"(d[46]), "+f"(d[47]),
          "+f"(d[48]), "+f"(d[49]), "+f"(d[50]), "+f"(d[51]), "+f"(d[52]), "+f"(d[53]), "+f"(d[54]), "+f"(d[55]),
          "+f"(d[56]), "+f"(d[57]), "+f"(d[58]), "+f"(d[59]), "+f"(d[60]), "+f"(d[61]), "+f"(d[62]), "+f"(d[63]),
          "+f"(d[64]), "+f"(d[65]), "+f"(d[66]), "+f"(d[67]), "+f"(d[68]), "+f"(d[69]), "+f"(d[70]), "+f"(d[71]),
          "+f"(d[72]), "+f"(d[73]), "+f"(d[74]), "+f"(d[75]), "+f"(d[76]), "+f"(d[77]), "+f"(d[78]), "+f"(d[79]),
          "+f"(d[80]), "+f"(d[81]), "+f"(d[82]), "+f"(d[83]), "+f"(d[84]), "+f"(d[85]), "+f"(d[86]), "+f"(d[87]),
          "+f"(d[88]), "+f"(d[89]), "+f"(d[90]), "+f"(d[91]), "+f"(d[92]), "+f"(d[93]), "+f"(d[94]), "+f"(d[95]),
          "+f"(d[96]), "+f"(d[97]), "+f"(d[98]), "+f"(d[99]), "+f"(d[100]), "+f"(d[101]), "+f"(d[102]), "+f"(d[103]),
          "+f"(d[104]), "+f"(d[105]), "+f"(d[106]), "+f"(d[107]), "+f"(d[108]), "+f"(d[109]), "+f"(d[110]), "+f"(d[111]),
          "+f"(d[112]), "+f"(d[113]), "+f"(d[114]), "+f"(d[115]), "+f"(d[116]), "+f"(d[117]), "+f"(d[118]), "+f"(d[119]),
          "+f"(d[120]), "+f"(d[121]), "+f"(d[122]), "+f"(d[123]), "+f"(d[124]), "+f"(d[125]), "+f"(d[126]), "+f"(d[127])
        : "l"(descA), "l"(descB), "r"(scaleD));
}

__device__ __forceinline__ void wgmma_ss_n256_t1_z(float (&d)[128], uint64_t descA, uint64_t descB) {
    asm volatile("{\n.reg .pred p;\n"
        "setp.ne.b32 p, 0, 0;\n"
        "wgmma.mma_async.sync.aligned.m64n256k16.f32.bf16.bf16 "
        "{%0, %1, %2, %3, %4, %5, %6, %7, %8, %9, %10, %11, %12, %13, %14, %15, "
        "%16, %17, %18, %19, %20, %21, %22, %23, %24, %25, %26, %27, %28, %29, %30, %31, "
        "%32, %33, %34, %35, %36, %37, %38, %39, %40, %41, %42, %43, %44, %45, %46, %47, "
        "%48, %49, %50, %51, %52, %53, %54, %55, %56, %57, %58, %59, %60, %61, %62, %63, "
        "%64, %65, %66, %67, %68, %69, %70, %71, %72, %73, %74, %75, %76, %77, %78, %79, "
        "%80, %81, %82, %83, %84, %85, %86, %87, %88, %89, %90, %91, %92, %93, %94, %95, "
        "%96, %97, %98, %99, %100, %101, %102, %103, %104, %105, %106, %107, %108, %109, %110, %111, "
        "%112, %113, %114, %115, %116, %117, %118, %119, %120, %121, %122, %123, %124, %125, %126, %127}, "
        "%128, %129, p, 1, 1, 0, 1;\n}\n"
        :
          "=f"(d[0]), "=f"(d[1]), "=f"(d[2]), "=f"(d[3]), "=f"(d[4]), "=f"(d[5]), "=f"(d[6]), "=f"(d[7]),
          "=f"(d[8]), "=f"(d[9]), "=f"(d[10]), "=f"(d[11]), "=f"(d[12]), "=f"(d[13]), "=f"(d[14]), "=f"(d[15]),
          "=f"(d[16]), "=f"(d[17]), "=f"(d[18]), "=f"(d[19]), "=f"(d[20]), "=f"(d[21]), "=f"(d[22]), "=f"(d[23]),
          "=f"(d[24]), "=f"(d[25]), "=f"(d[26]), "=f"(d[27]), "=f"(d[28]), "=f"(d[29]), "=f"(d[30]), "=f"(d[31]),
          "=f"(d[32]), "=f"(d[33]), "=f"(d[34]), "=f"(d[35]), "=f"(d[36]), "=f"(d[37]), "=f"(d[38]), "=f"(d[39]),
          "=f"(d[40]), "=f"(d[41]), "=f"(d[42]), "=f"(d[43]), "=f"(d[44]), "=f"(d[45]), "=f"(d[46]), "=f"(d[47]),
          "=f"(d[48]), "=f"(d[49]), "=f"(d[50]), "=f"(d[51]), "=f"(d[52]), "=f"(d[53]), "=f"(d[54]), "=f"(d[55]),
          "=f"(d[56]), "=f"(d[57]), "=f"(d[58]), "=f"(d[59]), "=f"(d[60]), "=f"(d[61]), "=f"(d[62]), "=f"(d[63]),
          "=f"(d[64]), "=f"(d[65]), "=f"(d[66]), "=f"(d[67]), "=f"(d[68]), "=f"(d[69]), "=f"(d[70]), "=f"(d[71]),
          "=f"(d[72]), "=f"(d[73]), "=f"(d[74]), "=f"(d[75]), "=f"(d[76]), "=f"(d[77]), "=f"(d[78]), "=f"(d[79]),
          "=f"(d[80]), "=f"(d[81]), "=f"(d[82]), "=f"(d[83]), "=f"(d[84]), "=f"(d[85]), "=f"(d[86]), "=f"(d[87]),
          "=f"(d[88]), "=f"(d[89]), "=f"(d[90]), "=f"(d[91]), "=f"(d[92]), "=f"(d[93]), "=f"(d[94]), "=f"(d[95]),
          "=f"(d[96]), "=f"(d[97]), "=f"(d[98]), "=f"(d[99]), "=f"(d[100]), "=f"(d[101]), "=f"(d[102]), "=f"(d[103]),
          "=f"(d[104]), "=f"(d[105]), "=f"(d[106]), "=f"(d[107]), "=f"(d[108]), "=f"(d[109]), "=f"(d[110]), "=f"(d[111]),
          "=f"(d[112]), "=f"(d[113]), "=f"(d[114]), "=f"(d[115]), "=f"(d[116]), "=f"(d[117]), "=f"(d[118]), "=f"(d[119]),
          "=f"(d[120]), "=f"(d[121]), "=f"(d[122]), "=f"(d[123]), "=f"(d[124]), "=f"(d[125]), "=f"(d[126]), "=f"(d[127])
        : "l"(descA), "l"(descB));
}

__device__ __forceinline__ void wgmma_rs_n128_t0(float (&d)[64], const uint32_t (&a)[4], uint64_t descB, int scaleD) {
    asm volatile("{\n.reg .pred p;\n"
        "setp.ne.b32 p, %69, 0;\n"
        "wgmma.mma_async.sync.aligned.m64n128k16.f32.bf16.bf16 "
        "{%0, %1, %2, %3, %4, %5, %6, %7, %8, %9, %10, %11, %12, %13, %14, %15, "
        "%16, %17, %18, %19, %20, %21, %22, %23, %24, %25, %26, %27, %28, %29, %30, %31, "
        "%32, %33, %34, %35, %36, %37, %38, %39, %40, %41, %42, %43, %44, %45, %46, %47, "
        "%48, %49, %50, %51, %52, %53, %54, %55, %56, %57, %58, %59, %60, %61, %62, %63}, "
        "{%64, %65, %66, %67}, %68, p, 1, 1, 0;\n}\n"
        :
          "+f"(d[0]), "+f"(d[1]), "+f"(d[2]), "+f"(d[3]), "+f"(d[4]), "+f"(d[5]), "+f"(d[6]), "+f"(d[7]),
          "+f"(d[8]), "+f"(d[9]), "+f"(d[10]), "+f"(d[11]), "+f"(d[12]), "+f"(d[13]), "+f"(d[14]), "+f"(d[15]),
          "+f"(d[16]), "+f"(d[17]), "+f"(d[18]), "+f"(d[19]), "+f"(d[20]), "+f"(d[21]), "+f"(d[22]), "+f"(d[23]),
          "+f"(d[24]), "+f"(d[25]), "+f"(d[26]), "+f"(d[27]), "+f"(d[28]), "+f"(d[29]), "+f"(d[30]), "+f"(d[31]),
          "+f"(d[32]), "+f"(d[33]), "+f"(d[34]), "+f"(d[35]), "+f"(d[36]), "+f"(d[37]), "+f"(d[38]), "+f"(d[39]),
          "+f"(d[40]), "+f"(d[41]), "+f"(d[42]), "+f"(d[43]), "+f"(d[44]), "+f"(d[45]), "+f"(d[46]), "+f"(d[47]),
          "+f"(d[48]), "+f"(d[49]), "+f"(d[50]), "+f"(d[51]), "+f"(d[52]), "+f"(d[53]), "+f"(d[54]), "+f"(d[55]),
          "+f"(d[56]), "+f"(d[57]), "+f"(d[58]), "+f"(d[59]), "+f"(d[60]), "+f"(d[61]), "+f"(d[62]), "+f"(d[63])
        : "r"(a[0]), "r"(a[1]), "r"(a[2]), "r"(a[3]), "l"(descB), "r"(scaleD));
}

__device__ __forceinline__ void wgmma_rs_n128_t0_z(float (&d)[64], const uint32_t (&a)[4], uint64_t descB) {
    asm volatile("{\n.reg .pred p;\n"
        "setp.ne.b32 p, 0, 0;\n"
        "wgmma.mma_async.sync.aligned.m64n128k16.f32.bf16.bf16 "
        "{%0, %1, %2, %3, %4, %5, %6, %7, %8, %9, %10, %11, %12, %13, %14, %15, "
        "%16, %17, %18, %19, %20, %21, %22, %23, %24, %25, %26, %27, %28, %29, %30, %31, "
        "%32, %33, %34, %35, %36, %37, %38, %39, %40, %41, %42, %43, %44, %45, %46, %47, "
        "%48, %49, %50, %51, %52, %53, %54, %55, %56, %57, %58, %59, %60, %61, %62, %63}, "
        "{%64, %65, %66, %67}, %68, p, 1, 1, 0;\n}\n"
        :
          "=f"(d[0]), "=f"(d[1]), "=f"(d[2]), "=f"(d[3]), "=f"(d[4]), "=f"(d[5]), "=f"(d[6]), "=f"(d[7]),
          "=f"(d[8]), "=f"(d[9]), "=f"(d[10]), "=f"(d[11]), "=f"(d[12]), "=f"(d[13]), "=f"(d[14]), "=f"(d[15]),
          "=f"(d[16]), "=f"(d[17]), "=f"(d[18]), "=f"(d[19]), "=f"(d[20]), "=f"(d[21]), "=f"(d[22]), "=f"(d[23]),
          "=f"(d[24]), "=f"(d[25]), "=f"(d[26]), "=f"(d[27]), "=f"(d[28]), "=f"(d[29]), "=f"(d[30]), "=f"(d[31]),
          "=f"(d[32]), "=f"(d[33]), "=f"(d[34]), "=f"(d[35]), "=f"(d[36]), "=f"(d[37]), "=f"(d[38]), "=f"(d[39]),
          "=f"(d[40]), "=f"(d[41]), "=f"(d[42]), "=f"(d[43]), "=f"(d[44]), "=f"(d[45]), "=f"(d[46]), "=f"(d[47]),
          "=f"(d[48]), "=f"(d[49]), "=f"(d[50]), "=f"(d[51]), "=f"(d[52]), "=f"(d[53]), "=f"(d[54]), "=f"(d[55]),
          "=f"(d[56]), "=f"(d[57]), "=f"(d[58]), "=f"(d[59]), "=f"(d[60]), "=f"(d[61]), "=f"(d[62]), "=f"(d[63])
        : "r"(a[0]), "r"(a[1]), "r"(a[2]), "r"(a[3]), "l"(descB));
}

__device__ __forceinline__ void wgmma_rs_n128_t1(float (&d)[64], const uint32_t (&a)[4], uint64_t descB, int scaleD) {
    asm volatile("{\n.reg .pred p;\n"
        "setp.ne.b32 p, %69, 0;\n"
        "wgmma.mma_async.sync.aligned.m64n128k16.f32.bf16.bf16 "
        "{%0, %1, %2, %3, %4, %5, %6, %7, %8, %9, %10, %11, %12, %13, %14, %15, "
        "%16, %17, %18, %19, %20, %21, %22, %23, %24, %25, %26, %27, %28, %29, %30, %31, "
        "%32, %33, %34, %35, %36, %37, %38, %39, %40, %41, %42, %43, %44, %45, %46, %47, "
        "%48, %49, %50, %51, %52, %53, %54, %55, %56, %57, %58, %59, %60, %61, %62, %63}, "
        "{%64, %65, %66, %67}, %68, p, 1, 1, 1;\n}\n"
        :
          "+f"(d[0]), "+f"(d[1]), "+f"(d[2]), "+f"(d[3]), "+f"(d[4]), "+f"(d[5]), "+f"(d[6]), "+f"(d[7]),
          "+f"(d[8]), "+f"(d[9]), "+f"(d[10]), "+f"(d[11]), "+f"(d[12]), "+f"(d[13]), "+f"(d[14]), "+f"(d[15]),
          "+f"(d[16]), "+f"(d[17]), "+f"(d[18]), "+f"(d[19]), "+f"(d[20]), "+f"(d[21]), "+f"(d[22]), "+f"(d[23]),
          "+f"(d[24]), "+f"(d[25]), "+f"(d[26]), "+f"(d[27]), "+f"(d[28]), "+f"(d[29]), "+f"(d[30]), "+f"(d[31]),
          "+f"(d[32]), "+f"(d[33]), "+f"(d[34]), "+f"(d[35]), "+f"(d[36]), "+f"(d[37]), "+f"(d[38]), "+f"(d[39]),
          "+f"(d[40]), "+f"(d[41]), "+f"(d[42]), "+f"(d[43]), "+f"(d[44]), "+f"(d[45]), "+f"(d[46]), "+f"(d[47]),
          "+f"(d[48]), "+f"(d[49]), "+f"(d[50]), "+f"(d[51]), "+f"(d[52]), "+f"(d[53]), "+f"(d[54]), "+f"(d[55]),
          "+f"(d[56]), "+f"(d[57]), "+f"(d[58]), "+f"(d[59]), "+f"(d[60]), "+f"(d[61]), "+f"(d[62]), "+f"(d[63])
        : "r"(a[0]), "r"(a[1]), "r"(a[2]), "r"(a[3]), "l"(descB), "r"(scaleD));
}

__device__ __forceinline__ void wgmma_rs_n128_t1_z(float (&d)[64], const uint32_t (&a)[4], uint64_t descB) {
    asm volatile("{\n.reg .pred p;\n"
        "setp.ne.b32 p, 0, 0;\n"
        "wgmma.mma_async.sync.aligned.m64n128k16.f32.bf16.bf16 "
        "{%0, %1, %2, %3, %4, %5, %6, %7, %8, %9, %10, %11, %12, %13, %14, %15, "
        "%16, %17, %18, %19, %20, %21, %22, %23, %24, %25, %26, %27, %28, %29, %30, %31, "
        "%32, %33, %34, %35, %36, %37, %38, %39, %40, %41, %42, %43, %44, %45, %46, %47, "
        "%48, %49, %50, %51, %52, %53, %54, %55, %56, %57, %58, %59, %60, %61, %62, %63}, "
        "{%64, %65, %66, %67}, %68, p, 1, 1, 1;\n}\n"
        :
          "=f"(d[0]), "=f"(d[1]), "=f"(d[2]), "=f"(d[3]), "=f"(d[4]), "=f"(d[5]), "=f"(d[6]), "=f"(d[7]),
          "=f"(d[8]), "=f"(d[9]), "=f"(d[10]), "=f"(d[11]), "=f"(d[12]), "=f"(d[13]), "=f"(d[14]), "=f"(d[15]),
          "=f"(d[16]), "=f"(d[17]), "=f"(d[18]), "=f"(d[19]), "=f"(d[20]), "=f"(d[21]), "=f"(d[22]), "=f"(d[23]),
          "=f"(d[24]), "=f"(d[25]), "=f"(d[26]), "=f"(d[27]), "=f"(d[28]), "=f"(d[29]), "=f"(d[30]), "=f"(d[31]),
          "=f"(d[32]), "=f"(d[33]), "=f"(d[34]), "=f"(d[35]), "=f"(d[36]), "=f"(d[37]), "=f"(d[38]), "=f"(d[39]),
          "=f"(d[40]), "=f"(d[41]), "=f"(d[42]), "=f"(d[43]), "=f"(d[44]), "=f"(d[45]), "=f"(d[46]), "=f"(d[47]),
          "=f"(d[48]), "=f"(d[49]), "=f"(d[50]), "=f"(d[51]), "=f"(d[52]), "=f"(d[53]), "=f"(d[54]), "=f"(d[55]),
          "=f"(d[56]), "=f"(d[57]), "=f"(d[58]), "=f"(d[59]), "=f"(d[60]), "=f"(d[61]), "=f"(d[62]), "=f"(d[63])
        : "r"(a[0]), "r"(a[1]), "r"(a[2]), "r"(a[3]), "l"(descB));
}

__device__ __forceinline__ void wgmma_ss_n160_t1(float (&d)[80], uint64_t descA, uint64_t descB, int scaleD) {
    asm volatile("{\n.reg .pred p;\n"
        "setp.ne.b32 p, %82, 0;\n"
        "wgmma.mma_async.sync.aligned.m64n160k16.f32.bf16.bf16 "
        "{%0, %1, %2, %3, %4, %5, %6, %7, %8, %9, %10, %11, %12, %13, %14, %15, "
        "%16, %17, %18, %19, %20, %21, %22, %23, %24, %25, %26, %27, %28, %29, %30, %31, "
        "%32, %33, %34, %35, %36, %37, %38, %39, %40, %41, %42, %43, %44, %45, %46, %47, "
        "%48, %49, %50, %51, %52, %53, %54, %55, %56, %57, %58, %59, %60, %61, %62, %63, "
        "%64, %65, %66, %67, %68, %69, %70, %71, %72, %73, %74, %75, %76, %77, %78, %79}, "
        "%80, %81, p, 1, 1, 0, 1;\n}\n"
        :
          "+f"(d[0]), "+f"(d[1]), "+f"(d[2]), "+f"(d[3]), "+f"(d[4]), "+f"(d[5]), "+f"(d[6]), "+f"(d[7]),
          "+f"(d[8]), "+f"(d[9]), "+f"(d[10]), "+f"(d[11]), "+f"(d[12]), "+f"(d[13]), "+f"(d[14]), "+f"(d[15]),
          "+f"(d[16]), "+f"(d[17]), "+f"(d[18]), "+f"(d[19]), "+f"(d[20]), "+f"(d[21]), "+f"(d[22]), "+f"(d[23]),
          "+f"(d[24]), "+f"(d[25]), "+f"(d[26]), "+f"(d[27]), "+f"(d[28]), "+f"(d[29]), "+f"(d[30]), "+f"(d[31]),
          "+f"(d[32]), "+f"(d[33]), "+f"(d[34]), "+f"(d[35]), "+f"(d[36]), "+f"(d[37]), "+f"(d[38]), "+f"(d[39]),
          "+f"(d[40]), "+f"(d[41]), "+f"(d[42]), "+f"(d[43]), "+f"(d[44]), "+f"(d[45]), "+f"(d[46]), "+f"(d[47]),
          "+f"(d[48]), "+f"(d[49]), "+f"(d[50]), "+f"(d[51]), "+f"(d[52]), "+f"(d[53]), "+f"(d[54]), "+f"(d[55]),
          "+f"(d[56]), "+f"(d[57]), "+f"(d[58]), "+f"(d[59]), "+f"(d[60]), "+f"(d[61]), "+f"(d[62]), "+f"(d[63]),
          "+f"(d[64]), "+f"(d[65]), "+f"(d[66]), "+f"(d[67]), "+f"(d[68]), "+f"(d[69]), "+f"(d[70]), "+f"(d[71]),
          "+f"(d[72]), "+f"(d[73]), "+f"(d[74]), "+f"(d[75]), "+f"(d[76]), "+f"(d[77]), "+f"(d[78]), "+f"(d[79])
        : "l"(descA), "l"(descB), "r"(scaleD));
}

__device__ __forceinline__ void wgmma_ss_n184_t1(float (&d)[92], uint64_t descA, uint64_t descB, int scaleD) {
    asm volatile("{\n.reg .pred p;\n"
        "setp.ne.b32 p, %94, 0;\n"
        "wgmma.mma_async.sync.aligned.m64n184k16.f32.bf16.bf16 "
        "{%0, %1, %2, %3, %4, %5, %6, %7, %8, %9, %10, %11, %12, %13, %14, %15, "
        "%16, %17, %18, %19, %20, %21, %22, %23, %24, %25, %26, %27, %28, %29, %30, %31, "
        "%32, %33, %34, %35, %36, %37, %38, %39, %40, %41, %42, %43, %44, %45, %46, %47, "
        "%48, %49, %50, %51, %52, %53, %54, %55, %56, %57, %58, %59, %60, %61, %62, %63, "
        "%64, %65, %66, %67, %68, %69, %70, %71, %72, %73, %74, %75, %76, %77, %78, %79, "
        "%80, %81, %82, %83, %84, %85, %86, %87, %88, %89, %90, %91}, "
        "%92, %93, p, 1, 1, 0, 1;\n}\n"
        :
          "+f"(d[0]), "+f"(d[1]), "+f"(d[2]), "+f"(d[3]), "+f"(d[4]), "+f"(d[5]), "+f"(d[6]), "+f"(d[7]),
          "+f"(d[8]), "+f"(d[9]), "+f"(d[10]), "+f"(d[11]), "+f"(d[12]), "+f"(d[13]), "+f"(d[14]), "+f"(d[15]),
          "+f"(d[16]), "+f"(d[17]), "+f"(d[18]), "+f"(d[19]), "+f"(d[20]), "+f"(d[21]), "+f"(d[22]), "+f"(d[23]),
          "+f"(d[24]), "+f"(d[25]), "+f"(d[26]), "+f"(d[27]), "+f"(d[28]), "+f"(d[29]), "+f"(d[30]), "+f"(d[31]),
          "+f"(d[32]), "+f"(d[33]), "+f"(d[34]), "+f"(d[35]), "+f"(d[36]), "+f"(d[37]), "+f"(d[38]), "+f"(d[39]),
          "+f"(d[40]), "+f"(d[41]), "+f"(d[42]), "+f"(d[43]), "+f"(d[44]), "+f"(d[45]), "+f"(d[46]), "+f"(d[47]),
          "+f"(d[48]), "+f"(d[49]), "+f"(d[50]), "+f"(d[51]), "+f"(d[52]), "+f"(d[53]), "+f"(d[54]), "+f"(d[55]),
          "+f"(d[56]), "+f"(d[57]), "+f"(d[58]), "+f"(d[59]), "+f"(d[60]), "+f"(d[61]), "+f"(d[62]), "+f"(d[63]),
          "+f"(d[64]), "+f"(d[65]), "+f"(d[66]), "+f"(d[67]), "+f"(d[68]), "+f"(d[69]), "+f"(d[70]), "+f"(d[71]),
          "+f"(d[72]), "+f"(d[73]), "+f"(d[74]), "+f"(d[75]), "+f"(d[76]), "+f"(d[77]), "+f"(d[78]), "+f"(d[79]),
          "+f"(d[80]), "+f"(d[81]), "+f"(d[82]), "+f"(d[83]), "+f"(d[84]), "+f"(d[85]), "+f"(d[86]), "+f"(d[87]),
          "+f"(d[88]), "+f"(d[89]), "+f"(d[90]), "+f"(d[91])
        : "l"(descA), "l"(descB), "r"(scaleD));
}

__device__ __forceinline__ void wgmma_ss_n192_t1(float (&d)[96], uint64_t descA, uint64_t descB, int scaleD) {
    asm volatile("{\n.reg .pred p;\n"
        "setp.ne.b32 p, %98, 0;\n"
        "wgmma.mma_async.sync.aligned.m64n192k16.f32.bf16.bf16 "
        "{%0, %1, %2, %3, %4, %5, %6, %7, %8, %9, %10, %11, %12, %13, %14, %15, "
        "%16, %17, %18, %19, %20, %21, %22, %23, %24, %25, %26, %27, %28, %29, %30, %31, "
        "%32, %33, %34, %35, %36, %37, %38, %39, %40, %41, %42, %43, %44, %45, %46, %47, "
        "%48, %49, %50, %51, %52, %53, %54, %55, %56, %57, %58, %59, %60, %61, %62, %63, "
        "%64, %65, %66, %67, %68, %69, %70, %71, %72, %73, %74, %75, %76, %77, %78, %79, "
        "%80, %81, %82, %83, %84, %85, %86, %87, %88, %89, %90, %91, %92, %93, %94, %95}, "
        "%96, %97, p, 1, 1, 0, 1;\n}\n"
        :
          "+f"(d[0]), "+f"(d[1]), "+f"(d[2]), "+f"(d[3]), "+f"(d[4]), "+f"(d[5]), "+f"(d[6]), "+f"(d[7]),
          "+f"(d[8]), "+f"(d[9]), "+f"(d[10]), "+f"(d[11]), "+f"(d[12]), "+f"(d[13]), "+f"(d[14]), "+f"(d[15]),
          "+f"(d[16]), "+f"(d[17]), "+f"(d[18]), "+f"(d[19]), "+f"(d[20]), "+f"(d[21]), "+f"(d[22]), "+f"(d[23]),
          "+f"(d[24]), "+f"(d[25]), "+f"(d[26]), "+f"(d[27]), "+f"(d[28]), "+f"(d[29]), "+f"(d[30]), "+f"(d[31]),
          "+f"(d[32]), "+f"(d[33]), "+f"(d[34]), "+f"(d[35]), "+f"(d[36]), "+f"(d[37]), "+f"(d[38]), "+f"(d[39]),
          "+f"(d[40]), "+f"(d[41]), "+f"(d[42]), "+f"(d[43]), "+f"(d[44]), "+f"(d[45]), "+f"(d[46]), "+f"(d[47]),
          "+f"(d[48]), "+f"(d[49]), "+f"(d[50]), "+f"(d[51]), "+f"(d[52]), "+f"(d[53]), "+f"(d[54]), "+f"(d[55]),
          "+f"(d[56]), "+f"(d[57]), "+f"(d[58]), "+f"(d[59]), "+f"(d[60]), "+f"(d[61]), "+f"(d[62]), "+f"(d[63]),
          "+f"(d[64]), "+f"(d[65]), "+f"(d[66]), "+f"(d[67]), "+f"(d[68]), "+f"(d[69]), "+f"(d[70]), "+f"(d[71]),
          "+f"(d[72]), "+f"(d[73]), "+f"(d[74]), "+f"(d[75]), "+f"(d[76]), "+f"(d[77]), "+f"(d[78]), "+f"(d[79]),
          "+f"(d[80]), "+f"(d[81]), "+f"(d[82]), "+f"(d[83]), "+f"(d[84]), "+f"(d[85]), "+f"(d[86]), "+f"(d[87]),
          "+f"(d[88]), "+f"(d[89]), "+f"(d[90]), "+f"(d[91]), "+f"(d[92]), "+f"(d[93]), "+f"(d[94]), "+f"(d[95])
        : "l"(descA), "l"(descB), "r"(scaleD));
}

__device__ __forceinline__ void wgmma_ss_n128_t1(float (&d)[64], uint64_t descA, uint64_t descB, int scaleD) {
    asm volatile("{\n.reg .pred p;\n"
        "setp.ne.b32 p, %66, 0;\n"
        "wgmma.mma_async.sync.aligned.m64n128k16.f32.bf16.bf16 "
        "{%0, %1, %2, %3, %4, %5, %6, %7, %8, %9, %10, %11, %12, %13, %14, %15, "
        "%16, %17, %18, %19, %20, %21, %22, %23, %24, %25, %26, %27, %28, %29, %30, %31, "
        "%32, %33, %34, %35, %36, %37, %38, %39, %40, %41, %42, %43, %44, %45, %46, %47, "
        "%48, %49, %50, %51, %52, %53, %54, %55, %56, %57, %58, %59, %60, %61, %62, %63}, "
        "%64, %65, p, 1, 1, 0, 1;\n}\n"
        :
          "+f"(d[0]), "+f"(d[1]), "+f"(d[2]), "+f"(d[3]), "+f"(d[4]), "+f"(d[5]), "+f"(d[6]), "+f"(d[7]),
          "+f"(d[8]), "+f"(d[9]), "+f"(d[10]), "+f"(d[11]), "+f"(d[12]), "+f"(d[13]), "+f"(d[14]), "+f"(d[15]),
          "+f"(d[16]), "+f"(d[17]), "+f"(d[18]), "+f"(d[19]), "+f"(d[20]), "+f"(d[21]), "+f"(d[22]), "+f"(d[23]),
          "+f"(d[24]), "+f"(d[25]), "+f"(d[26]), "+f"(d[27]), "+f"(d[28]), "+f"(d[29]), "+f"(d[30]), "+f"(d[31]),
          "+f"(d[32]), "+f"(d[33]), "+f"(d[34]), "+f"(d[35]), "+f"(d[36]), "+f"(d[37]), "+f"(d[38]), "+f"(d[39]),
          "+f"(d[40]), "+f"(d[41]), "+f"(d[42]), "+f"(d[43]), "+f"(d[44]), "+f"(d[45]), "+f"(d[46]), "+f"(d[47]),
          "+f"(d[48]), "+f"(d[49]), "+f"(d[50]), "+f"(d[51]), "+f"(d[52]), "+f"(d[53]), "+f"(d[54]), "+f"(d[55]),
          "+f"(d[56]), "+f"(d[57]), "+f"(d[58]), "+f"(d[59]), "+f"(d[60]), "+f"(d[61]), "+f"(d[62]), "+f"(d[63])
        : "l"(descA), "l"(descB), "r"(scaleD));
}

constexpr int S_LEN = 2048;
constexpr int D_MODEL = 640;
constexpr int N_HEADS = 32;
constexpr int D_HEAD = 128;
constexpr int S_KV = 2048;
constexpr int WIN = 512;
constexpr int D_FF = 1728;
constexpr float LN_EPS = 1e-5f;

#define TS(kid, slot)

__device__ float g_mod[6 * D_MODEL];
__device__ __align__(1024) __nv_bfloat16 g_h[S_LEN * D_MODEL];
__device__ __align__(1024) __nv_bfloat16 g_o[S_LEN * N_HEADS * D_HEAD];
__device__ __align__(1024) __nv_bfloat16 g_part[4 * S_LEN * D_MODEL];
__device__ __align__(1024) __nv_bfloat16 g_x1[S_LEN * D_MODEL];
__device__ __align__(1024) __nv_bfloat16 g_h2[S_LEN * D_MODEL];
__device__ __align__(1024) __nv_bfloat16 g_act[S_LEN * D_FF];

constexpr int F_MODAB = 0, F_MODALL = 1, F_H = 2, F_P = 18, F_H2 = 34, F_A = 50, F_O = 66, F_COUNT = 130;
__device__ unsigned g_flags[F_COUNT * 32];
__device__ unsigned g_epoch;
__device__ unsigned g_exit;

__device__ __forceinline__ void flag_signal(int f) {
    asm volatile("red.release.gpu.global.add.u32 [%0], 1;" ::"l"(g_flags + f * 32) : "memory");
}
__device__ __forceinline__ void flag_wait(int f, unsigned target) {
    unsigned n = 0;
    while (true) {
        unsigned v;
        asm volatile("ld.acquire.gpu.global.u32 %0, [%1];" : "=r"(v) : "l"(g_flags + f * 32) : "memory");
        if ((int)(v - target) >= 0) break;
        ++n;
        if (n > (1u << 22)) { g_abort = 1; break; }
        if ((n & 255u) == 0 && g_abort) break;
    }
}

struct Maps {
    CUtensorMap h, wq, k, v, o_st, o_a, wo, part_st, h2, g128, u128, g64, u64, act_st64, act_st24, act_a, wd;
};

constexpr int SM_DATA = 229376;
constexpr int SM_STAGING = 196608;
constexpr int SM_TOTAL = SM_DATA + 1024 + 512;
constexpr int B1F = 0, B1E = 6, B2F = 12, B2E = 16, B4F = 20, B4E = 24, B5F = 28, B5E = 33, BD1 = 38, BD2 = 39, BD4 = 40, B_COUNT = 41;
constexpr int P1_STAGE = 32768, P2_STAGE = 57344, P4_STAGE = 49152, P5_STAGE = 40960;

__device__ __forceinline__ float rcp_approx(float x) { float y; asm("rcp.approx.ftz.f32 %0, %1;" : "=f"(y) : "f"(x)); return y; }
__device__ __forceinline__ float silu_mul(float g, float u) { return g * rcp_approx(1.f + ex2(-1.4426950408889634f * g)) * u; }
__device__ __forceinline__ uint2 ldcg_u2(const void* p) { return __ldcg(reinterpret_cast<const uint2*>(p)); }

__device__ __noinline__ void ln_rows(const uint2 (&xr)[2][5], const float* __restrict__ shift, const float* __restrict__ scale1p,
                                     __nv_bfloat16* __restrict__ dst, int lane) {
    float4 sh[5], sc[5];
#pragma unroll
    for (int i = 0; i < 5; i++) {
        sh[i] = __ldcg(reinterpret_cast<const float4*>(shift + (lane + 32 * i) * 4));
        sc[i] = __ldcg(reinterpret_cast<const float4*>(scale1p + (lane + 32 * i) * 4));
    }
    float mean[2], rstd[2];
#pragma unroll
    for (int rr = 0; rr < 2; rr++) {
        float s = 0.f;
#pragma unroll
        for (int i = 0; i < 5; i++) s += (bf16lo(xr[rr][i].x) + bf16hi(xr[rr][i].x)) + (bf16lo(xr[rr][i].y) + bf16hi(xr[rr][i].y));
#pragma unroll
        for (int o = 16; o > 0; o >>= 1) s += __shfl_xor_sync(0xffffffffu, s, o);
        mean[rr] = s * (1.f / D_MODEL);
    }
#pragma unroll
    for (int rr = 0; rr < 2; rr++) {
        float q = 0.f;
#pragma unroll
        for (int i = 0; i < 5; i++) {
            const float d0 = bf16lo(xr[rr][i].x) - mean[rr], d1 = bf16hi(xr[rr][i].x) - mean[rr];
            const float d2 = bf16lo(xr[rr][i].y) - mean[rr], d3 = bf16hi(xr[rr][i].y) - mean[rr];
            q += (d0 * d0 + d1 * d1) + (d2 * d2 + d3 * d3);
        }
#pragma unroll
        for (int o = 16; o > 0; o >>= 1) q += __shfl_xor_sync(0xffffffffu, q, o);
        rstd[rr] = rsqrtf(q * (1.f / D_MODEL) + LN_EPS);
    }
#pragma unroll
    for (int rr = 0; rr < 2; rr++) {
#pragma unroll
        for (int i = 0; i < 5; i++) {
            uint2 u;
            u.x = pack_bf16((bf16lo(xr[rr][i].x) - mean[rr]) * rstd[rr] * sc[i].x + sh[i].x, (bf16hi(xr[rr][i].x) - mean[rr]) * rstd[rr] * sc[i].y + sh[i].y);
            u.y = pack_bf16((bf16lo(xr[rr][i].y) - mean[rr]) * rstd[rr] * sc[i].z + sh[i].z, (bf16hi(xr[rr][i].y) - mean[rr]) * rstd[rr] * sc[i].w + sh[i].w);
            *reinterpret_cast<uint2*>(dst + (size_t)rr * D_MODEL + (lane + 32 * i) * 4) = u;
        }
    }
}

__global__ void __cluster_dims__(2, 1, 1) __launch_bounds__(384, 1)
mega_kernel(const __grid_constant__ Maps tm, const __nv_bfloat16* __restrict__ x, const __nv_bfloat16* __restrict__ cvec,
            const __nv_bfloat16* __restrict__ w_mod, __nv_bfloat16* __restrict__ out) {
    extern __shared__ uint8_t smem_raw[];
    const uint32_t base = (smem_u32(smem_raw) + 1023u) & ~1023u;
    const uint32_t bars = base + SM_DATA;
    const uint32_t rank = cluster_ctarank();
    const int cid = blockIdx.x >> 1;
    const int p = cid & 7, j = cid >> 3;
    const int mt = p * 2 + (int)rank;
    const int m0 = mt * 128;
    const int wg = threadIdx.x >> 7;
    unsigned epoch;
    asm volatile("ld.volatile.global.u32 %0, [%1];" : "=r"(epoch) : "l"(&g_epoch));

    if (threadIdx.x == 0) {
        for (int i = 0; i < 6; i++) { mbar_init(bars + 8 * (B1F + i), 1); mbar_init(bars + 8 * (B1E + i), 4); }
        for (int i = 0; i < 4; i++) { mbar_init(bars + 8 * (B2F + i), 1); mbar_init(bars + 8 * (B2E + i), 4); }
        for (int i = 0; i < 4; i++) { mbar_init(bars + 8 * (B4F + i), 1); mbar_init(bars + 8 * (B4E + i), 4); }
        for (int i = 0; i < 5; i++) { mbar_init(bars + 8 * (B5F + i), 1); mbar_init(bars + 8 * (B5E + i), 2); }
        mbar_init(bars + 8 * BD1, 4); mbar_init(bars + 8 * BD2, 4); mbar_init(bars + 8 * BD4, 4);
        fence_mbar_init();
    }
    __syncthreads();
    cluster_sync();

    if (wg == 2) {
        reg_dealloc<40>();
        if (threadIdx.x == 256) {
            {
                uint32_t st = 0, ph = 1;
                bool first = true;
#pragma unroll 1
                for (int hp = 0; hp < 2; hp++) {
                    const int head0 = j * 4 + hp * 2;
                    if (first) {
#pragma unroll 1
                        for (int s = 1; s < 6; s++) {
                            if (s == 3) continue;
                            const int kb = s < 3 ? s - 1 : s - 2;
                            mbar_expect_tx(bars + 8 * (B1F + s), P1_STAGE);
#pragma unroll 1
                            for (int c = 0; c < 2; c++) {
                                const int chunk = 2 * (int)rank + c;
                                tma_load_2d_mc(base + s * P1_STAGE + chunk * 8192, &tm.wq, head0 * 128 + chunk * 64, kb * 64, bars + 8 * (B1F + s), 3);
                            }
                        }
                        flag_wait(F_H + mt, (epoch + 1) * 8);
                        fence_proxy_async_all();
#pragma unroll 1
                        for (int s = 0; s < 6; s += 3) {
                            mbar_expect_tx(bars + 8 * (B1F + s), P1_STAGE);
                            tma_load_2d(base + s * P1_STAGE, &tm.h, (s / 3 * 2) * 64, m0, bars + 8 * (B1F + s));
                            tma_load_2d(base + s * P1_STAGE + 16384, &tm.h, (s / 3 * 2 + 1) * 64, m0, bars + 8 * (B1F + s));
                        }
                        ph = 0;
                    }
#pragma unroll 1
                    for (int kk2 = first ? 2 : 0; kk2 < 5; kk2++) {
                        mbar_wait(bars + 8 * (B1E + st), ph);
                        mbar_expect_tx(bars + 8 * (B1F + st), P1_STAGE);
                        tma_load_2d(base + st * P1_STAGE, &tm.h, (2 * kk2) * 64, m0, bars + 8 * (B1F + st));
                        tma_load_2d(base + st * P1_STAGE + 16384, &tm.h, (2 * kk2 + 1) * 64, m0, bars + 8 * (B1F + st));
                        if (++st == 6) { st = 0; ph ^= 1; }
#pragma unroll 1
                        for (int u = 0; u < 2; u++) {
                            mbar_wait(bars + 8 * (B1E + st), ph);
                            mbar_expect_tx(bars + 8 * (B1F + st), P1_STAGE);
                            const int kb = 2 * kk2 + u;
#pragma unroll 1
                            for (int c = 0; c < 2; c++) {
                                const int chunk = 2 * (int)rank + c;
                                tma_load_2d_mc(base + st * P1_STAGE + chunk * 8192, &tm.wq, head0 * 128 + chunk * 64, kb * 64, bars + 8 * (B1F + st), 3);
                            }
                            if (++st == 6) { st = 0; ph ^= 1; }
                        }
                    }
                    first = false;
#pragma unroll 1
                    for (int t = 0; t <= 8; t++) {
                        if (t < 8) {
                            mbar_wait(bars + 8 * (B1E + st), ph);
                            mbar_expect_tx(bars + 8 * (B1F + st), P1_STAGE);
                            const int row = (head0 + (t >> 2)) * S_KV + (S_KV - WIN) + (t & 3) * 128;
                            tma_load_2d_mc(base + st * P1_STAGE + rank * 16384, &tm.k, rank * 64, row, bars + 8 * (B1F + st), 3);
                            if (++st == 6) { st = 0; ph ^= 1; }
                        }
                        if (t > 0) {
                            mbar_wait(bars + 8 * (B1E + st), ph);
                            mbar_expect_tx(bars + 8 * (B1F + st), P1_STAGE);
                            const int tv = t - 1;
                            const int row = (head0 + (tv >> 2)) * S_KV + (S_KV - WIN) + (tv & 3) * 128;
                            tma_load_2d_mc(base + st * P1_STAGE + rank * 16384, &tm.v, rank * 64, row, bars + 8 * (B1F + st), 3);
                            if (++st == 6) { st = 0; ph ^= 1; }
                        }
                    }
                }
            }
            {
                const int kq = j >> 1, n0 = (j & 1) * 320;
                mbar_wait(bars + 8 * BD1, 0);
#pragma unroll 1
                for (int i = 0; i < 4; i++) {
                    mbar_expect_tx(bars + 8 * (B2F + i), P2_STAGE);
                    const int k0 = kq * 1024 + i * 64;
#pragma unroll 1
                    for (int c = 0; c < 5; c++)
                        if (((c + i) & 1) == (int)rank) tma_load_2d_mc(base + i * P2_STAGE + 16384 + c * 8192, &tm.wo, n0 + c * 64, k0, bars + 8 * (B2F + i), 3);
                }
                flag_wait(F_O + mt * 4 + kq, (epoch + 1) * 4);
                fence_proxy_async_all();
#pragma unroll 1
                for (int i = 0; i < 4; i++) tma_load_2d(base + i * P2_STAGE, &tm.o_a, kq * 1024 + i * 64, m0, bars + 8 * (B2F + i));
                uint32_t st = 0, ph = 0;
#pragma unroll 1
                for (int i = 4; i < 16; i++) {
                    mbar_wait(bars + 8 * (B2E + st), ph);
                    mbar_expect_tx(bars + 8 * (B2F + st), P2_STAGE);
                    const uint32_t dst = base + st * P2_STAGE;
                    const int k0 = kq * 1024 + i * 64;
                    tma_load_2d(dst, &tm.o_a, k0, m0, bars + 8 * (B2F + st));
#pragma unroll 1
                    for (int c = 0; c < 5; c++)
                        if (((c + i) & 1) == (int)rank) tma_load_2d_mc(dst + 16384 + c * 8192, &tm.wo, n0 + c * 64, k0, bars + 8 * (B2F + st), 3);
                    if (++st == 4) { st = 0; ph ^= 1; }
                }
            }
            {
                const int f0 = j * 216;
                const CUtensorMap* t128 = rank == 0 ? &tm.g128 : &tm.u128;
                const CUtensorMap* t64 = rank == 0 ? &tm.g64 : &tm.u64;
                mbar_wait(bars + 8 * BD2, 0);
#pragma unroll 1
                for (int i = 0; i < 4; i++) {
                    mbar_expect_tx(bars + 8 * (B4F + i), 16384 + 32768);
                    const uint32_t dst = base + i * P4_STAGE;
                    tma_load_2d_mc(dst + 16384 + rank * 16384, t128, f0, i * 64, bars + 8 * (B4F + i), 3);
                    tma_load_2d_mc(dst + 16384 + rank * 16384 + 8192, t128, f0 + 64, i * 64, bars + 8 * (B4F + i), 3);
                }
                flag_wait(F_H2 + mt, (epoch + 1) * 8);
                fence_proxy_async_all();
#pragma unroll 1
                for (int i = 0; i < 4; i++) tma_load_2d(base + i * P4_STAGE, &tm.h2, i * 64, m0, bars + 8 * (B4F + i));
                uint32_t st = 0, ph = 0;
#pragma unroll 1
                for (int i = 4; i < 20; i++) {
                    const int kb = i < 10 ? i : i - 10;
                    mbar_wait(bars + 8 * (B4E + st), ph);
                    const uint32_t dst = base + st * P4_STAGE;
                    if (i < 10) {
                        mbar_expect_tx(bars + 8 * (B4F + st), 16384 + 32768);
                        tma_load_2d(dst, &tm.h2, kb * 64, m0, bars + 8 * (B4F + st));
                        tma_load_2d_mc(dst + 16384 + rank * 16384, t128, f0, kb * 64, bars + 8 * (B4F + st), 3);
                        tma_load_2d_mc(dst + 16384 + rank * 16384 + 8192, t128, f0 + 64, kb * 64, bars + 8 * (B4F + st), 3);
                    } else {
                        mbar_expect_tx(bars + 8 * (B4F + st), 16384 + 24576);
                        tma_load_2d(dst, &tm.h2, kb * 64, m0, bars + 8 * (B4F + st));
#pragma unroll 1
                        for (int c = 0; c < 3; c++)
                            tma_load_2d_mc(dst + 16384 + rank * 12288 + c * 4096, t64, f0 + 128 + c * 32, kb * 64, bars + 8 * (B4F + st), 3);
                    }
                    if (++st == 4) { st = 0; ph ^= 1; }
                }
            }
            {
                const int mt5 = p * 2 + (j >> 2), n0 = (j & 3) * 160;
                const int kb0 = rank == 0 ? 0 : 14, nkb = rank == 0 ? 14 : 13;
                mbar_wait(bars + 8 * BD4, 0);
#pragma unroll 1
                for (int i = 0; i < 5; i++) {
                    mbar_expect_tx(bars + 8 * (B5F + i), P5_STAGE);
#pragma unroll 1
                    for (int c = 0; c < 3; c++)
                        tma_load_2d(base + i * P5_STAGE + 16384 + c * 8192, &tm.wd, n0 + c * 64, (kb0 + i) * 64, bars + 8 * (B5F + i));
                }
                flag_wait(F_A + mt5, (epoch + 1) * 16);
                fence_proxy_async_all();
#pragma unroll 1
                for (int i = 0; i < 5; i++) tma_load_2d(base + i * P5_STAGE, &tm.act_a, (kb0 + i) * 64, mt5 * 128, bars + 8 * (B5F + i));
                uint32_t st = 0, ph = 0;
#pragma unroll 1
                for (int i = 5; i < nkb; i++) {
                    mbar_wait(bars + 8 * (B5E + st), ph);
                    mbar_expect_tx(bars + 8 * (B5F + st), P5_STAGE);
                    const uint32_t dst = base + st * P5_STAGE;
                    const int k0 = (kb0 + i) * 64;
                    tma_load_2d(dst, &tm.act_a, k0, mt5 * 128, bars + 8 * (B5F + st));
#pragma unroll 1
                    for (int c = 0; c < 3; c++) tma_load_2d(dst + 16384 + c * 8192, &tm.wd, n0 + c * 64, k0, bars + 8 * (B5F + st));
                    if (++st == 5) { st = 0; ph ^= 1; }
                }
            }
        }
        __syncwarp();
        asm volatile("barrier.cluster.arrive.release.aligned; // producer\n barrier.cluster.wait.acquire.aligned;" ::: "memory");
        asm volatile("barrier.cluster.arrive.release.aligned; // producer2\n barrier.cluster.wait.acquire.aligned;" ::: "memory");
    } else {
        reg_alloc<232>();
        const int tid = threadIdx.x & 127;
        const int warp = tid >> 5, lane = tid & 31;
        const int cw = threadIdx.x >> 5;
        const uint32_t mystage = base + SM_STAGING + wg * 16384;
        auto arrive_both = [&](uint32_t bar) {
            if (tid == 0) mbar_arrive_cluster(bar, 0);
            if (tid == 32) mbar_arrive_cluster(bar, 1);
        };
        TS(0, 0);
        {
            uint2 xr[2][5];
#pragma unroll
            for (int rr = 0; rr < 2; rr++)
#pragma unroll
                for (int i = 0; i < 5; i++)
                    xr[rr][i] = __ldg(reinterpret_cast<const uint2*>(x + (size_t)(m0 + j * 16 + cw * 2 + rr) * D_MODEL + (lane + 32 * i) * 4));
            if (blockIdx.x < 120) {
                float* red = reinterpret_cast<float*>(smem_raw + (base - smem_u32(smem_raw)) + SM_STAGING);
                const int col0 = blockIdx.x * 32 + (lane & 3) * 8;
                float acc[8];
#pragma unroll
                for (int i = 0; i < 8; i++) acc[i] = 0.f;
                uint4 w[10];
                unsigned short cr[10];
#pragma unroll
                for (int i = 0; i < 10; i++) cr[i] = __ldg(reinterpret_cast<const unsigned short*>(cvec) + cw * 80 + i * 8 + (lane >> 2));
#pragma unroll
                for (int i = 0; i < 10; i++)
                    w[i] = __ldg(reinterpret_cast<const uint4*>(w_mod + (size_t)(cw * 80 + i * 8 + (lane >> 2)) * (6 * D_MODEL) + col0));
#pragma unroll
                for (int i = 0; i < 10; i++) {
                    const float s = bf16_round(silu_mul(__uint_as_float((uint32_t)cr[i] << 16), 1.f));
                    acc[0] += s * bf16lo(w[i].x); acc[1] += s * bf16hi(w[i].x);
                    acc[2] += s * bf16lo(w[i].y); acc[3] += s * bf16hi(w[i].y);
                    acc[4] += s * bf16lo(w[i].z); acc[5] += s * bf16hi(w[i].z);
                    acc[6] += s * bf16lo(w[i].w); acc[7] += s * bf16hi(w[i].w);
                }
#pragma unroll
                for (int i = 0; i < 8; i++) {
                    acc[i] += __shfl_xor_sync(0xffffffffu, acc[i], 4);
                    acc[i] += __shfl_xor_sync(0xffffffffu, acc[i], 8);
                    acc[i] += __shfl_xor_sync(0xffffffffu, acc[i], 16);
                }
                if (lane < 4) {
#pragma unroll
                    for (int i = 0; i < 8; i++) red[cw * 32 + lane * 8 + i] = acc[i];
                }
                TS(6, 0);
                bar_sync(5, 256);
                TS(6, 1);
                if (threadIdx.x < 32) {
                    float t = 0.f;
#pragma unroll
                    for (int i = 0; i < 8; i++) t += red[i * 32 + threadIdx.x];
                    t = bf16_round(t);
                    const int chunk = blockIdx.x / 20;
                    if (chunk == 1 || chunk == 4) t = bf16_round(1.f + t);
                    g_mod[blockIdx.x * 32 + threadIdx.x] = t;
                    __syncwarp();
                    TS(6, 2);
                    if (threadIdx.x == 0) flag_signal(blockIdx.x < 40 ? F_MODAB : F_MODALL);
                    TS(6, 3);
                }
            }
            if (threadIdx.x == 0) flag_wait(F_MODAB, (epoch + 1) * 40);
            bar_sync(5, 256);
            TS(0, 1);
            ln_rows(xr, g_mod, g_mod + D_MODEL, g_h + (size_t)(m0 + j * 16 + cw * 2) * D_MODEL, lane);
            TS(6, 4);
            bar_sync(5, 256);
            TS(6, 5);
            if (threadIdx.x == 0) flag_signal(F_H + mt);
        }
        TS(0, 2);
        {
            const float cscale = 0.08838834764831845f * 1.4426950408889634f;
            uint32_t st = 0, ph = 0;
            auto wait_full = [&]() -> uint32_t {
                mbar_wait(bars + 8 * (B1F + st), ph);
                return base + st * P1_STAGE;
            };
            auto release = [&](uint32_t s) { arrive_both(bars + 8 * (B1E + s)); };
            auto advance = [&]() { if (++st == 6) { st = 0; ph ^= 1; } };
            auto turn_wait = [&]() { bar_sync(3 + wg, 256); };
            auto turn_pass = [&]() { bar_arrive(3 + (wg ^ 1), 256); };
            if (wg == 1) bar_arrive(3, 256);

            for (int hp = 0; hp < 2; hp++) {
                const int head0 = j * 4 + hp * 2;
                uint32_t q[8][4];
                {
                    float acc[128];
#pragma unroll
                    for (int i = 0; i < 128; i++) acc[i] = 0.f;
                    for (int kk2 = 0; kk2 < 5; kk2++) {
                        const uint32_t hbuf = wait_full();
                        if (kk2 == 0 && hp == 0) TS(0, 3);
                        const uint32_t sth = st;
                        advance();
#pragma unroll
                        for (int u = 0; u < 2; u++) {
                            const uint32_t wbuf = wait_full();
                            const uint32_t stw = st;
                            advance();
                            wgmma_fence();
#pragma unroll
                            for (int k = 0; k < 4; k++) {
                                uint64_t da = make_desc(hbuf + u * 16384 + wg * 8192 + k * 32, 16, 1024, 1);
                                uint64_t db = make_desc(wbuf + k * 2048, 8192, 1024, 1);
                                wgmma_ss_n256_t1(acc, da, db, 1);
                            }
                            wgmma_commit();
                            wgmma_wait<0>();
                            release(stw);
                        }
                        release(sth);
                    }
                    fence_regs(acc);
                    if (tid == 0) tma_store_wait_read<0>();
                    bar_sync(1 + wg, 128);
#pragma unroll
                    for (int i = 0; i < 8; i++) {
                        q[i][0] = pack_bf16(acc[8 * i + 0], acc[8 * i + 1]);
                        q[i][1] = pack_bf16(acc[8 * i + 2], acc[8 * i + 3]);
                        q[i][2] = pack_bf16(acc[8 * i + 4], acc[8 * i + 5]);
                        q[i][3] = pack_bf16(acc[8 * i + 6], acc[8 * i + 7]);
                        uint32_t b0 = pack_bf16(acc[64 + 8 * i + 0], acc[64 + 8 * i + 1]);
                        uint32_t b1 = pack_bf16(acc[64 + 8 * i + 2], acc[64 + 8 * i + 3]);
                        uint32_t b2 = pack_bf16(acc[64 + 8 * i + 4], acc[64 + 8 * i + 5]);
                        uint32_t b3 = pack_bf16(acc[64 + 8 * i + 6], acc[64 + 8 * i + 7]);
                        asm volatile("st.shared.v4.b32 [%0], {%1, %2, %3, %4};" ::"r"(mystage + (i * 128 + tid) * 16), "r"(b0), "r"(b1),
                                     "r"(b2), "r"(b3) : "memory");
                    }
                }
                float o[64], s[64], e[64];
                uint32_t pp[8][4];
                float mm0, mm1, l0, l1, a0, a1, lo0, lo1;
#pragma unroll
                for (int i = 0; i < 64; i++) { o[i] = 0.f; }

                auto issue_s = [&]() -> uint32_t {
                    const uint32_t kbuf = wait_full();
                    const uint32_t stk = st;
                    advance();
                    wgmma_fence();
#pragma unroll
                    for (int k = 0; k < 8; k++) {
                        uint64_t db = make_desc(kbuf + (k >> 2) * 16384 + (k & 3) * 32, 16, 1024, 1);
                        if (k == 0) wgmma_rs_n128_t0_z(s, q[k], db);
                        else wgmma_rs_n128_t0(s, q[k], db, 1);
                    }
                    wgmma_commit();
                    return stk;
                };
                auto issue_pv = [&](bool fresh) -> uint32_t {
                    const uint32_t vbuf = wait_full();
                    const uint32_t stv = st;
                    advance();
                    wgmma_fence();
#pragma unroll
                    for (int k = 0; k < 8; k++) {
                        uint64_t db = make_desc(vbuf + k * 2048, 16384, 1024, 1);
                        wgmma_rs_n128_t1(o, pp[k], db, (!fresh) || k != 0);
                    }
                    wgmma_commit();
                    return stv;
                };
                auto softmax = [&](bool first) {
                    float mx0 = fmaxf(s[0], s[1]), mx1 = fmaxf(s[2], s[3]);
#pragma unroll
                    for (int jj = 1; jj < 16; jj++) {
                        mx0 = fmaxf(mx0, fmaxf(s[4 * jj], s[4 * jj + 1]));
                        mx1 = fmaxf(mx1, fmaxf(s[4 * jj + 2], s[4 * jj + 3]));
                    }
                    mx0 = fmaxf(mx0, __shfl_xor_sync(0xffffffffu, mx0, 1));
                    mx0 = fmaxf(mx0, __shfl_xor_sync(0xffffffffu, mx0, 2));
                    mx1 = fmaxf(mx1, __shfl_xor_sync(0xffffffffu, mx1, 1));
                    mx1 = fmaxf(mx1, __shfl_xor_sync(0xffffffffu, mx1, 2));
                    if (first) {
                        lo0 = l0; lo1 = l1;
                        mm0 = mx0; mm1 = mx1; l0 = 0.f; l1 = 0.f; a0 = 0.f; a1 = 0.f;
                    } else {
                        float mn0 = fmaxf(mm0, mx0), mn1 = fmaxf(mm1, mx1);
                        a0 = ex2((mm0 - mn0) * cscale); a1 = ex2((mm1 - mn1) * cscale);
                        mm0 = mn0; mm1 = mn1;
                    }
                    const float mc0 = mm0 * cscale, mc1 = mm1 * cscale;
                    float r0 = 0.f, r1 = 0.f;
#pragma unroll
                    for (int jj = 0; jj < 16; jj++) {
                        e[4 * jj] = ex2(fmaf(s[4 * jj], cscale, -mc0));
                        e[4 * jj + 1] = ex2(fmaf(s[4 * jj + 1], cscale, -mc0));
                        e[4 * jj + 2] = ex2(fmaf(s[4 * jj + 2], cscale, -mc1));
                        e[4 * jj + 3] = ex2(fmaf(s[4 * jj + 3], cscale, -mc1));
                        r0 += e[4 * jj] + e[4 * jj + 1];
                        r1 += e[4 * jj + 2] + e[4 * jj + 3];
                    }
                    l0 = l0 * a0 + r0; l1 = l1 * a1 + r1;
                };
                auto convert_p = [&]() {
#pragma unroll
                    for (int i = 0; i < 8; i++) {
                        pp[i][0] = pack_bf16(e[8 * i + 0], e[8 * i + 1]);
                        pp[i][1] = pack_bf16(e[8 * i + 2], e[8 * i + 3]);
                        pp[i][2] = pack_bf16(e[8 * i + 4], e[8 * i + 5]);
                        pp[i][3] = pack_bf16(e[8 * i + 6], e[8 * i + 7]);
                    }
                };
                auto store_o = [&](float ls0, float ls1, int head, bool last) {
                    float s0 = ls0 + __shfl_xor_sync(0xffffffffu, ls0, 1); s0 += __shfl_xor_sync(0xffffffffu, s0, 2);
                    float s1 = ls1 + __shfl_xor_sync(0xffffffffu, ls1, 1); s1 += __shfl_xor_sync(0xffffffffu, s1, 2);
                    const float i0 = 1.f / s0, i1 = 1.f / s1;
                    if (tid == 0) tma_store_wait_read<0>();
                    bar_sync(1 + wg, 128);
#pragma unroll
                    for (int jj = 0; jj < 16; jj += 2) {
                        const int mi = lane >> 3;
                        const int row = warp * 16 + (mi & 1) * 8 + (lane & 7);
                        const int grp = jj + (mi >> 1);
                        const uint32_t addr = mystage + (grp >> 3) * 8192 + row * 128 + (((grp & 7) ^ (row & 7)) << 4);
                        stmatrix_x4(addr, pack_bf16(o[4 * jj] * i0, o[4 * jj + 1] * i0), pack_bf16(o[4 * jj + 2] * i1, o[4 * jj + 3] * i1),
                                    pack_bf16(o[4 * jj + 4] * i0, o[4 * jj + 5] * i0), pack_bf16(o[4 * jj + 6] * i1, o[4 * jj + 7] * i1));
                    }
                    fence_proxy_async();
                    bar_sync(1 + wg, 128);
                    if (tid == 0) {
                        tma_store_2d(&tm.o_st, mystage, head * 128, m0 + wg * 64);
                        tma_store_2d(&tm.o_st, mystage + 8192, head * 128 + 64, m0 + wg * 64);
                        tma_store_commit();
                        if (last) {
                            tma_store_wait<0>();
                            mbar_arrive_cluster(bars + 8 * BD1, 0);
                            mbar_arrive_cluster(bars + 8 * BD1, 1);
                            flag_signal(F_O + mt * 4 + (j >> 1));
                        }
                    }
                };

                l0 = 0.f; l1 = 0.f;
                {
                    turn_wait();
                    uint32_t stk = issue_s();
                    turn_pass();
                    wgmma_wait<0>();
                    fence_regs(s);
                    release(stk);
                    softmax(true);
                    convert_p();
                }
#pragma unroll 1
                for (int t = 1; t < 8; t++) {
                    const bool first = (t == 4);
                    if (t == 4) {
#pragma unroll
                        for (int i = 0; i < 8; i++) {
                            asm volatile("ld.shared.v4.b32 {%0, %1, %2, %3}, [%4];" : "=r"(q[i][0]), "=r"(q[i][1]), "=r"(q[i][2]), "=r"(q[i][3])
                                         : "r"(mystage + (i * 128 + tid) * 16) : "memory");
                        }
                    }
                    turn_wait();
                    uint32_t stk = issue_s();
                    uint32_t stv = issue_pv(t == 1 || t == 5);
                    turn_pass();
                    wgmma_wait<1>();
                    fence_regs(s);
                    release(stk);
                    softmax(first);
                    asm volatile("{\n.reg .pred p;\nsetp.lt.f32 p, %0, 0fBF800000;\n@p st.shared.f32 [%1], %0;\n}\n" ::"f"(l0 + l1), "r"(mystage) : "memory");
                    wgmma_wait<0>();
                    fence_regs(o);
                    release(stv);
                    if (first) {
                        store_o(lo0, lo1, head0, false);
                    } else {
#pragma unroll
                        for (int jj = 0; jj < 16; jj++) {
                            o[4 * jj] *= a0; o[4 * jj + 1] *= a0; o[4 * jj + 2] *= a1; o[4 * jj + 3] *= a1;
                        }
                    }
                    convert_p();
                }
                {
                    turn_wait();
                    uint32_t stv = issue_pv(false);
                    turn_pass();
                    wgmma_wait<0>();
                    fence_regs(o);
                    release(stv);
                    store_o(l0, l1, head0 + 1, hp == 1);
                }
            }
        }
        TS(0, 4);
        {
            const int kq = j >> 1, n0 = (j & 1) * 320;
            float acc0[96], acc1[64];
#pragma unroll
            for (int i = 0; i < 96; i++) acc0[i] = 0.f;
#pragma unroll
            for (int i = 0; i < 64; i++) acc1[i] = 0.f;
            uint32_t st = 0, ph = 0, prev = 0;
            for (int i = 0; i < 16; i++) {
                mbar_wait(bars + 8 * (B2F + st), ph);
                if (i == 0) TS(0, 5);
                const uint32_t buf = base + st * P2_STAGE;
                wgmma_fence();
#pragma unroll
                for (int k = 0; k < 4; k++) {
                    uint64_t da = make_desc(buf + wg * 8192 + k * 32, 16, 1024, 1);
                    wgmma_ss_n192_t1(acc0, da, make_desc(buf + 16384 + k * 2048, 8192, 1024, 1), 1);
                    wgmma_ss_n128_t1(acc1, da, make_desc(buf + 16384 + 3 * 8192 + k * 2048, 8192, 1024, 1), 1);
                }
                wgmma_commit();
                if (i > 0) { wgmma_wait<1>(); arrive_both(bars + 8 * (B2E + prev)); }
                prev = st;
                if (++st == 4) { st = 0; ph ^= 1; }
            }
            wgmma_wait<0>();
            fence_regs(acc0); fence_regs(acc1);
            TS(0, 6);
            bar_sync(5, 256);
            TS(4, 0);
            const uint32_t stg = base + wg * 40960;
            const int mi = lane >> 3;
            const int row = warp * 16 + (mi & 1) * 8 + (lane & 7);
#pragma unroll
            for (int jj = 0; jj < 24; jj += 2) {
                const int grp = jj + (mi >> 1);
                stmatrix_x4(stg + (grp >> 3) * 8192 + row * 128 + (((grp & 7) ^ (row & 7)) << 4),
                            pack_bf16(acc0[4 * jj], acc0[4 * jj + 1]), pack_bf16(acc0[4 * jj + 2], acc0[4 * jj + 3]),
                            pack_bf16(acc0[4 * jj + 4], acc0[4 * jj + 5]), pack_bf16(acc0[4 * jj + 6], acc0[4 * jj + 7]));
            }
#pragma unroll
            for (int jj = 0; jj < 16; jj += 2) {
                const int grp = jj + (mi >> 1);
                stmatrix_x4(stg + (3 + (grp >> 3)) * 8192 + row * 128 + (((grp & 7) ^ (row & 7)) << 4),
                            pack_bf16(acc1[4 * jj], acc1[4 * jj + 1]), pack_bf16(acc1[4 * jj + 2], acc1[4 * jj + 3]),
                            pack_bf16(acc1[4 * jj + 4], acc1[4 * jj + 5]), pack_bf16(acc1[4 * jj + 6], acc1[4 * jj + 7]));
            }
            TS(4, 1);
            fence_proxy_async();
            bar_sync(1 + wg, 128);
            TS(4, 2);
            if (tid == 0) {
#pragma unroll
                for (int c = 0; c < 5; c++) tma_store_2d(&tm.part_st, stg + c * 8192, n0 + c * 64, kq * S_LEN + m0 + wg * 64);
                tma_store_commit();
                TS(4, 3);
                tma_store_wait<0>();
                TS(4, 4);
                mbar_arrive_cluster(bars + 8 * BD2, 0);
                mbar_arrive_cluster(bars + 8 * BD2, 1);
                flag_signal(F_P + mt);
            }
        }
        TS(0, 7);
        {
            uint2 xr[2][5];
#pragma unroll
            for (int rr = 0; rr < 2; rr++)
#pragma unroll
                for (int i = 0; i < 5; i++)
                    xr[rr][i] = __ldg(reinterpret_cast<const uint2*>(x + (size_t)(m0 + j * 16 + cw * 2 + rr) * D_MODEL + (lane + 32 * i) * 4));
            if (threadIdx.x == 0) { flag_wait(F_MODALL, (epoch + 1) * 80); flag_wait(F_P + mt, (epoch + 1) * 16); }
            bar_sync(5, 256);
            TS(0, 8);
            uint2 pr[2][4][5];
            float4 gv[5];
#pragma unroll
            for (int rr = 0; rr < 2; rr++)
#pragma unroll
                for (int s = 0; s < 4; s++)
#pragma unroll
                    for (int i = 0; i < 5; i++)
                        pr[rr][s][i] = ldcg_u2(g_part + ((size_t)s * S_LEN + m0 + j * 16 + cw * 2 + rr) * D_MODEL + (lane + 32 * i) * 4);
#pragma unroll
            for (int i = 0; i < 5; i++) gv[i] = __ldcg(reinterpret_cast<const float4*>(g_mod + 2 * D_MODEL + (lane + 32 * i) * 4));
#pragma unroll
            for (int rr = 0; rr < 2; rr++) {
#pragma unroll
                for (int i = 0; i < 5; i++) {
                    float a0 = (bf16lo(pr[rr][0][i].x) + bf16lo(pr[rr][1][i].x)) + (bf16lo(pr[rr][2][i].x) + bf16lo(pr[rr][3][i].x));
                    float a1 = (bf16hi(pr[rr][0][i].x) + bf16hi(pr[rr][1][i].x)) + (bf16hi(pr[rr][2][i].x) + bf16hi(pr[rr][3][i].x));
                    float a2 = (bf16lo(pr[rr][0][i].y) + bf16lo(pr[rr][1][i].y)) + (bf16lo(pr[rr][2][i].y) + bf16lo(pr[rr][3][i].y));
                    float a3 = (bf16hi(pr[rr][0][i].y) + bf16hi(pr[rr][1][i].y)) + (bf16hi(pr[rr][2][i].y) + bf16hi(pr[rr][3][i].y));
                    xr[rr][i].x = pack_bf16(bf16lo(xr[rr][i].x) + gv[i].x * a0, bf16hi(xr[rr][i].x) + gv[i].y * a1);
                    xr[rr][i].y = pack_bf16(bf16lo(xr[rr][i].y) + gv[i].z * a2, bf16hi(xr[rr][i].y) + gv[i].w * a3);
                    *reinterpret_cast<uint2*>(g_x1 + (size_t)(m0 + j * 16 + cw * 2 + rr) * D_MODEL + (lane + 32 * i) * 4) = xr[rr][i];
                }
            }
            TS(5, 0);
            ln_rows(xr, g_mod + 3 * D_MODEL, g_mod + 4 * D_MODEL, g_h2 + (size_t)(m0 + j * 16 + cw * 2) * D_MODEL, lane);
            TS(5, 1);
            bar_sync(5, 256);
            TS(5, 2);
            if (threadIdx.x == 0) flag_signal(F_H2 + mt);
        }
        TS(0, 9);
        {
            const int f0 = j * 216;
            uint32_t st = 0, ph = 0, prev = 0;
            {
                float acc[128];
#pragma unroll
                for (int i = 0; i < 128; i++) acc[i] = 0.f;
                for (int i = 0; i < 10; i++) {
                    mbar_wait(bars + 8 * (B4F + st), ph);
                    if (i == 0) TS(0, 10);
                    const uint32_t buf = base + st * P4_STAGE;
                    wgmma_fence();
#pragma unroll
                    for (int k = 0; k < 4; k++) {
                        uint64_t da = make_desc(buf + wg * 8192 + k * 32, 16, 1024, 1);
                        uint64_t db = make_desc(buf + 16384 + k * 2048, 8192, 1024, 1);
                        wgmma_ss_n256_t1(acc, da, db, 1);
                    }
                    wgmma_commit();
                    if (i > 0) { wgmma_wait<1>(); arrive_both(bars + 8 * (B4E + prev)); }
                    prev = st;
                    if (++st == 4) { st = 0; ph ^= 1; }
                }
                wgmma_wait<0>();
                arrive_both(bars + 8 * (B4E + prev));
                fence_regs(acc);
                TS(2, 0);
#pragma unroll
                for (int jj = 0; jj < 16; jj += 2) {
                    const int mi = lane >> 3;
                    const int row = warp * 16 + (mi & 1) * 8 + (lane & 7);
                    const int grp = jj + (mi >> 1);
                    const uint32_t addr = mystage + (grp >> 3) * 8192 + row * 128 + (((grp & 7) ^ (row & 7)) << 4);
                    stmatrix_x4(addr, pack_bf16(silu_mul(acc[4 * jj], acc[64 + 4 * jj]), silu_mul(acc[4 * jj + 1], acc[64 + 4 * jj + 1])),
                                pack_bf16(silu_mul(acc[4 * jj + 2], acc[64 + 4 * jj + 2]), silu_mul(acc[4 * jj + 3], acc[64 + 4 * jj + 3])),
                                pack_bf16(silu_mul(acc[4 * jj + 4], acc[64 + 4 * jj + 4]), silu_mul(acc[4 * jj + 5], acc[64 + 4 * jj + 5])),
                                pack_bf16(silu_mul(acc[4 * jj + 6], acc[64 + 4 * jj + 6]), silu_mul(acc[4 * jj + 7], acc[64 + 4 * jj + 7])));
                }
                fence_proxy_async();
                bar_sync(1 + wg, 128);
                TS(2, 1);
                if (tid == 0) {
                    tma_store_2d(&tm.act_st64, mystage, f0, m0 + wg * 64);
                    tma_store_2d(&tm.act_st64, mystage + 8192, f0 + 64, m0 + wg * 64);
                    tma_store_commit();
                }
                TS(2, 2);
            }
            {
                float acc[92];
#pragma unroll
                for (int i = 0; i < 92; i++) acc[i] = 0.f;
                for (int i = 0; i < 10; i++) {
                    mbar_wait(bars + 8 * (B4F + st), ph);
                    const uint32_t buf = base + st * P4_STAGE;
                    wgmma_fence();
#pragma unroll
                    for (int k = 0; k < 4; k++) {
                        uint64_t da = make_desc(buf + wg * 8192 + k * 32, 16, 1024, 1);
                        uint64_t db = make_desc(buf + 16384 + k * 1024, 4096, 512, 2);
                        wgmma_ss_n184_t1(acc, da, db, 1);
                    }
                    wgmma_commit();
                    if (i > 0) { wgmma_wait<1>(); arrive_both(bars + 8 * (B4E + prev)); }
                    prev = st;
                    if (++st == 4) { st = 0; ph ^= 1; }
                }
                wgmma_wait<0>();
                fence_regs(acc);
                TS(0, 11);
                if (tid == 0) tma_store_wait_read<0>();
                bar_sync(1 + wg, 128);
                TS(2, 3);
#pragma unroll
                for (int jj = 0; jj < 8; jj += 2) {
                    const int mi = lane >> 3;
                    const int row = warp * 16 + (mi & 1) * 8 + (lane & 7);
                    const int grp = jj + (mi >> 1);
                    const uint32_t addr = mystage + row * 128 + ((grp ^ (row & 7)) << 4);
                    stmatrix_x4(addr, pack_bf16(silu_mul(acc[4 * jj], acc[48 + 4 * jj]), silu_mul(acc[4 * jj + 1], acc[48 + 4 * jj + 1])),
                                pack_bf16(silu_mul(acc[4 * jj + 2], acc[48 + 4 * jj + 2]), silu_mul(acc[4 * jj + 3], acc[48 + 4 * jj + 3])),
                                pack_bf16(silu_mul(acc[4 * jj + 4], acc[48 + 4 * jj + 4]), silu_mul(acc[4 * jj + 5], acc[48 + 4 * jj + 5])),
                                pack_bf16(silu_mul(acc[4 * jj + 6], acc[48 + 4 * jj + 6]), silu_mul(acc[4 * jj + 7], acc[48 + 4 * jj + 7])));
                }
                {
                    const int mi = lane >> 3;
                    const int row = warp * 16 + (mi & 1) * 8 + (lane & 7);
                    const uint32_t addr = mystage + 8192 + row * 48 + (mi >> 1) * 16;
                    stmatrix_x4(addr, pack_bf16(silu_mul(acc[32], acc[80]), silu_mul(acc[33], acc[81])),
                                pack_bf16(silu_mul(acc[34], acc[82]), silu_mul(acc[35], acc[83])),
                                pack_bf16(silu_mul(acc[36], acc[84]), silu_mul(acc[37], acc[85])),
                                pack_bf16(silu_mul(acc[38], acc[86]), silu_mul(acc[39], acc[87])));
                    const uint32_t addr2 = mystage + 8192 + (warp * 16 + ((lane >> 3) & 1) * 8 + (lane & 7)) * 48 + 32;
                    asm volatile("stmatrix.sync.aligned.m8n8.x2.shared.b16 [%0], {%1, %2};" ::"r"(addr2),
                                 "r"(pack_bf16(silu_mul(acc[40], acc[88]), silu_mul(acc[41], acc[89]))),
                                 "r"(pack_bf16(silu_mul(acc[42], acc[90]), silu_mul(acc[43], acc[91]))) : "memory");
                }
                fence_proxy_async();
                bar_sync(1 + wg, 128);
                TS(2, 4);
                if (tid == 0) {
                    tma_store_2d(&tm.act_st64, mystage, f0 + 128, m0 + wg * 64);
                    tma_store_2d(&tm.act_st24, mystage + 8192, f0 + 192, m0 + wg * 64);
                    tma_store_commit();
                    TS(2, 5);
                    tma_store_wait<0>();
                    TS(2, 6);
                    mbar_arrive_cluster(bars + 8 * BD4, 0);
                    mbar_arrive_cluster(bars + 8 * BD4, 1);
                    TS(2, 7);
                    flag_signal(F_A + mt);
                    TS(2, 8);
                }
            }
        }
        TS(0, 12);
        {
            const int m5 = (p * 2 + (j >> 2)) * 128, n0 = (j & 3) * 160;
            const int nkb = rank == 0 ? 14 : 13;
            float acc[80];
#pragma unroll
            for (int i = 0; i < 80; i++) acc[i] = 0.f;
            uint32_t st = 0, ph = 0, prev = 0;
            for (int i = 0; i < nkb; i++) {
                mbar_wait(bars + 8 * (B5F + st), ph);
                if (i == 0) TS(0, 13);
                const uint32_t buf = base + st * P5_STAGE;
                wgmma_fence();
#pragma unroll
                for (int k = 0; k < 4; k++) {
                    uint64_t da = make_desc(buf + wg * 8192 + k * 32, 16, 1024, 1);
                    wgmma_ss_n160_t1(acc, da, make_desc(buf + 16384 + k * 2048, 8192, 1024, 1), 1);
                }
                wgmma_commit();
                if (i > 0) {
                    wgmma_wait<1>();
                    if (tid == 0) mbar_arrive(bars + 8 * (B5E + prev));
                }
                prev = st;
                if (++st == 5) { st = 0; ph ^= 1; }
            }
            wgmma_wait<0>();
            fence_regs(acc);
            TS(0, 14);
            cluster_sync();
            TS(3, 0);
            {
                const uint32_t dst = mapa(base, rank ^ 1) + wg * 20480 + tid * 16;
                if (rank == 0) {
#pragma unroll
                    for (int i = 0; i < 10; i++)
                        asm volatile("st.shared::cluster.v4.f32 [%0], {%1, %2, %3, %4};" ::"r"(dst + i * 2048), "f"(acc[40 + 4 * i]), "f"(acc[40 + 4 * i + 1]),
                                     "f"(acc[40 + 4 * i + 2]), "f"(acc[40 + 4 * i + 3]) : "memory");
                } else {
#pragma unroll
                    for (int i = 0; i < 10; i++)
                        asm volatile("st.shared::cluster.v4.f32 [%0], {%1, %2, %3, %4};" ::"r"(dst + i * 2048), "f"(acc[4 * i]), "f"(acc[4 * i + 1]),
                                     "f"(acc[4 * i + 2]), "f"(acc[4 * i + 3]) : "memory");
                }
            }
            TS(3, 1);
            const int cbase = n0 + (int)rank * 80;
            uint4 xv[5];
#pragma unroll
            for (int it = 0; it < 5; it++) {
                const int idx = it * 256 + (int)threadIdx.x;
                const int row = idx / 10, ch = idx - row * 10;
                xv[it] = __ldcg(reinterpret_cast<const uint4*>(g_x1 + (size_t)(m5 + row) * D_MODEL + cbase + ch * 8));
            }
            float2 gbv[10];
#pragma unroll
            for (int jj = 0; jj < 10; jj++) gbv[jj] = __ldcg(reinterpret_cast<const float2*>(g_mod + 5 * D_MODEL + cbase + jj * 8 + (lane & 3) * 2));
            TS(3, 2);
            cluster_sync();
            TS(3, 3);
            {
                const uint32_t tile = base + 40960;
#pragma unroll
                for (int jj = 0; jj < 10; jj += 2) {
                    float4 o0, o1;
                    asm volatile("ld.shared.v4.f32 {%0, %1, %2, %3}, [%4];" : "=f"(o0.x), "=f"(o0.y), "=f"(o0.z), "=f"(o0.w) : "r"(base + wg * 20480 + tid * 16 + jj * 2048));
                    asm volatile("ld.shared.v4.f32 {%0, %1, %2, %3}, [%4];" : "=f"(o1.x), "=f"(o1.y), "=f"(o1.z), "=f"(o1.w) : "r"(base + wg * 20480 + tid * 16 + (jj + 1) * 2048));
                    const float2 g0 = gbv[jj], g1 = gbv[jj + 1];
                    float a[8];
#pragma unroll
                    for (int ee = 0; ee < 8; ee++) a[ee] = rank == 0 ? acc[4 * jj + ee] : acc[40 + 4 * jj + ee];
                    const int mi = lane >> 3;
                    const int row = wg * 64 + warp * 16 + (mi & 1) * 8 + (lane & 7);
                    const uint32_t addr = tile + row * 176 + (jj + (mi >> 1)) * 16;
                    stmatrix_x4(addr, pack_bf16(g0.x * bf16_round(a[0] + o0.x), g0.y * bf16_round(a[1] + o0.y)),
                                pack_bf16(g0.x * bf16_round(a[2] + o0.z), g0.y * bf16_round(a[3] + o0.w)),
                                pack_bf16(g1.x * bf16_round(a[4] + o1.x), g1.y * bf16_round(a[5] + o1.y)),
                                pack_bf16(g1.x * bf16_round(a[6] + o1.z), g1.y * bf16_round(a[7] + o1.w)));
                }
                TS(3, 4);
                bar_sync(5, 256);
                TS(3, 5);
#pragma unroll
                for (int it = 0; it < 5; it++) {
                    const int idx = it * 256 + (int)threadIdx.x;
                    const int row = idx / 10, ch = idx - row * 10;
                    uint4 tv;
                    asm volatile("ld.shared.v4.b32 {%0, %1, %2, %3}, [%4];" : "=r"(tv.x), "=r"(tv.y), "=r"(tv.z), "=r"(tv.w) : "r"(tile + row * 176 + ch * 16));
                    uint4 r;
                    r.x = pack_bf16(bf16lo(xv[it].x) + bf16lo(tv.x), bf16hi(xv[it].x) + bf16hi(tv.x));
                    r.y = pack_bf16(bf16lo(xv[it].y) + bf16lo(tv.y), bf16hi(xv[it].y) + bf16hi(tv.y));
                    r.z = pack_bf16(bf16lo(xv[it].z) + bf16lo(tv.z), bf16hi(xv[it].z) + bf16hi(tv.z));
                    r.w = pack_bf16(bf16lo(xv[it].w) + bf16lo(tv.w), bf16hi(xv[it].w) + bf16hi(tv.w));
                    *reinterpret_cast<uint4*>(out + (size_t)(m5 + row) * D_MODEL + cbase + ch * 8) = r;
                }
            }
            TS(0, 15);
            if (threadIdx.x == 0) {
                const unsigned old = atomicAdd(&g_exit, 1u);
                if (old == (epoch + 1) * 128u - 1u) {
                    asm volatile("st.volatile.global.u32 [%0], %1;" ::"l"(&g_epoch), "r"(epoch + 1) : "memory");
                }
            }
        }
    }
}

typedef CUresult (*PFN_encodeTiled)(CUtensorMap*, CUtensorMapDataType, cuuint32_t, void*, const cuuint64_t*, const cuuint64_t*,
                                    const cuuint32_t*, const cuuint32_t*, CUtensorMapInterleave, CUtensorMapSwizzle,
                                    CUtensorMapL2promotion, CUtensorMapFloatOOBfill);

static PFN_encodeTiled get_encode() {
    static PFN_encodeTiled fn = nullptr;
    if (!fn) {
        void* p = nullptr;
        cudaDriverEntryPointQueryResult qr;
        cudaGetDriverEntryPoint("cuTensorMapEncodeTiled", &p, cudaEnableDefault, &qr);
        fn = (PFN_encodeTiled)p;
    }
    return fn;
}

static CUtensorMap make_map(const void* ptr, uint64_t rows, uint64_t cols, uint32_t box_rows, uint32_t box_cols, CUtensorMapSwizzle swz) {
    CUtensorMap m;
    cuuint64_t dims[2] = {cols, rows};
    cuuint64_t strides[1] = {cols * 2};
    cuuint32_t box[2] = {box_cols, box_rows};
    cuuint32_t es[2] = {1, 1};
    get_encode()(&m, CU_TENSOR_MAP_DATA_TYPE_BFLOAT16, 2, const_cast<void*>(ptr), dims, strides, box, es, CU_TENSOR_MAP_INTERLEAVE_NONE,
                 swz, CU_TENSOR_MAP_L2_PROMOTION_L2_256B, CU_TENSOR_MAP_FLOAT_OOB_FILL_NONE);
    return m;
}

extern "C" void kernel_launch(void* const* d_in, const int* in_sizes, int n_in, void* d_out, int out_size) {
    (void)in_sizes; (void)n_in; (void)out_size;
    const __nv_bfloat16* x = (const __nv_bfloat16*)d_in[0];
    const __nv_bfloat16* kc = (const __nv_bfloat16*)d_in[1];
    const __nv_bfloat16* vc = (const __nv_bfloat16*)d_in[2];
    const __nv_bfloat16* wq = (const __nv_bfloat16*)d_in[3];
    const __nv_bfloat16* wo = (const __nv_bfloat16*)d_in[4];
    const __nv_bfloat16* wg = (const __nv_bfloat16*)d_in[6];
    const __nv_bfloat16* wu = (const __nv_bfloat16*)d_in[7];
    const __nv_bfloat16* wd = (const __nv_bfloat16*)d_in[8];
    const __nv_bfloat16* c = (const __nv_bfloat16*)d_in[9];
    const __nv_bfloat16* wmod = (const __nv_bfloat16*)d_in[10];
    __nv_bfloat16* out = (__nv_bfloat16*)d_out;

    static bool init = false;
    static void *p_h, *p_o, *p_x1, *p_h2, *p_act, *p_part;
    if (!init) {
        cudaFuncSetAttribute(mega_kernel, cudaFuncAttributeMaxDynamicSharedMemorySize, SM_TOTAL);
        cudaGetSymbolAddress(&p_h, g_h);
        cudaGetSymbolAddress(&p_o, g_o);
        cudaGetSymbolAddress(&p_x1, g_x1);
        cudaGetSymbolAddress(&p_h2, g_h2);
        cudaGetSymbolAddress(&p_act, g_act);
        cudaGetSymbolAddress(&p_part, g_part);
        init = true;
    }
    const CUtensorMapSwizzle S128 = CU_TENSOR_MAP_SWIZZLE_128B, S64 = CU_TENSOR_MAP_SWIZZLE_64B;
    Maps tm;
    tm.h = make_map(p_h, S_LEN, D_MODEL, 128, 64, S128);
    tm.wq = make_map(wq, D_MODEL, N_HEADS * D_HEAD, 64, 64, S128);
    tm.k = make_map(kc, N_HEADS * S_KV, D_HEAD, 128, 64, S128);
    tm.v = make_map(vc, N_HEADS * S_KV, D_HEAD, 128, 64, S128);
    tm.o_st = make_map(p_o, S_LEN, N_HEADS * D_HEAD, 64, 64, S128);
    tm.o_a = make_map(p_o, S_LEN, N_HEADS * D_HEAD, 128, 64, S128);
    tm.wo = make_map(wo, N_HEADS * D_HEAD, D_MODEL, 64, 64, S128);
    tm.part_st = make_map(p_part, 4 * S_LEN, D_MODEL, 64, 64, S128);
    tm.h2 = make_map(p_h2, S_LEN, D_MODEL, 128, 64, S128);
    tm.g128 = make_map(wg, D_MODEL, D_FF, 64, 64, S128);
    tm.u128 = make_map(wu, D_MODEL, D_FF, 64, 64, S128);
    tm.g64 = make_map(wg, D_MODEL, D_FF, 64, 32, S64);
    tm.u64 = make_map(wu, D_MODEL, D_FF, 64, 32, S64);
    tm.act_st64 = make_map(p_act, S_LEN, D_FF, 64, 64, S128);
    tm.act_st24 = make_map(p_act, S_LEN, D_FF, 64, 24, CU_TENSOR_MAP_SWIZZLE_NONE);
    tm.act_a = make_map(p_act, S_LEN, D_FF, 128, 64, S128);
    tm.wd = make_map(wd, D_FF, D_MODEL, 64, 64, S128);

    cudaLaunchConfig_t cfg = {};
    cfg.gridDim = dim3(128);
    cfg.blockDim = dim3(384);
    cfg.dynamicSmemBytes = SM_TOTAL;
    cfg.stream = cudaStreamPerThread;
    cfg.attrs = nullptr;
    cfg.numAttrs = 0;
    cudaLaunchKernelEx(&cfg, mega_kernel, tm, x, c, wmod, out);
}
```

```cpp
#include <cuda_runtime.h>
#include <cuda_bf16.h>
#include <cuda.h>
#include <stdint.h>

__device__ __forceinline__ uint32_t smem_u32(const void* p) { return (uint32_t)__cvta_generic_to_shared(p); }

__device__ __forceinline__ void mbar_init(uint32_t bar, uint32_t count) {
    asm volatile("mbarrier.init.shared::cta.b64 [%0], %1;" ::"r"(bar), "r"(count) : "memory");
}
__device__ __forceinline__ void mbar_expect_tx(uint32_t bar, uint32_t bytes) {
    asm volatile("mbarrier.arrive.expect_tx.shared::cta.b64 _, [%0], %1;" ::"r"(bar), "r"(bytes) : "memory");
}
__device__ __forceinline__ void mbar_arrive(uint32_t bar) {
    asm volatile("mbarrier.arrive.shared::cta.b64 _, [%0];" ::"r"(bar) : "memory");
}
__device__ __forceinline__ void mbar_arrive_cluster(uint32_t bar, uint32_t cta) {
    asm volatile(
        "{\n.reg .b32 ra;\n"
        "mapa.shared::cluster.u32 ra, %0, %1;\n"
        "mbarrier.arrive.shared::cluster.b64 _, [ra];\n}\n" ::"r"(bar), "r"(cta)
        : "memory");
}
__device__ __forceinline__ bool mbar_try_wait(uint32_t bar, uint32_t parity) {
    uint32_t ok;
    asm volatile(
        "{\n.reg .pred p;\n"
        "mbarrier.try_wait.parity.shared::cta.b64 p, [%1], %2;\n"
        "selp.u32 %0, 1, 0, p;\n}\n"
        : "=r"(ok)
        : "r"(bar), "r"(parity)
        : "memory");
    return ok != 0;
}
__device__ __forceinline__ bool mbar_try_wait_cluster(uint32_t bar, uint32_t parity) {
    uint32_t ok;
    asm volatile(
        "{\n.reg .pred p;\n"
        "mbarrier.try_wait.parity.shared::cta.b64 p, [%1], %2;\n"
        "selp.u32 %0, 1, 0, p;\n}\n"
        : "=r"(ok)
        : "r"(bar), "r"(parity)
        : "memory");
    return ok != 0;
}
__device__ volatile int g_abort = 0;
__device__ __forceinline__ void mbar_wait(uint32_t bar, uint32_t parity) {
    uint32_t n = 0;
    while (!mbar_try_wait(bar, parity)) {
        if (++n > (1u << 20)) break;
    }
}
__device__ __forceinline__ void mbar_wait_cluster(uint32_t bar, uint32_t parity) { mbar_wait(bar, parity); }
__device__ __forceinline__ void fence_mbar_init() { asm volatile("fence.mbarrier_init.release.cluster;" ::: "memory"); }
__device__ __forceinline__ void fence_proxy_async() { asm volatile("fence.proxy.async.shared::cta;" ::: "memory"); }
__device__ __forceinline__ void fence_proxy_async_all() { asm volatile("fence.proxy.async;" ::: "memory"); }
__device__ __forceinline__ void cluster_arrive() { asm volatile("barrier.cluster.arrive.release.aligned;" ::: "memory"); }
__device__ __forceinline__ void cluster_wait() { asm volatile("barrier.cluster.wait.acquire.aligned;" ::: "memory"); }
__device__ __forceinline__ void cluster_sync() { cluster_arrive(); cluster_wait(); }
__device__ __forceinline__ uint32_t cluster_ctarank() {
    uint32_t r;
    asm volatile("mov.u32 %0, %%cluster_ctarank;" : "=r"(r));
    return r;
}
__device__ __forceinline__ void bar_sync(int id, int n) { asm volatile("bar.sync %0, %1;" ::"r"(id), "r"(n) : "memory"); }
__device__ __forceinline__ void bar_arrive(int id, int n) { asm volatile("bar.arrive %0, %1;" ::"r"(id), "r"(n) : "memory"); }
__device__ __forceinline__ void pdl_wait() { asm volatile("griddepcontrol.wait;" ::: "memory"); }
__device__ __forceinline__ void pdl_launch() { asm volatile("griddepcontrol.launch_dependents;" ::: "memory"); }

__device__ __forceinline__ void tma_prefetch_desc(const CUtensorMap* m) {
    asm volatile("prefetch.tensormap [%0];" ::"l"(m) : "memory");
}
__device__ __forceinline__ void tma_load_2d(uint32_t dst, const CUtensorMap* m, int c0, int c1, uint32_t bar) {
    asm volatile(
        "cp.async.bulk.tensor.2d.shared::cluster.global.mbarrier::complete_tx::bytes [%0], [%1, {%3, %4}], [%2];"
        ::"r"(dst), "l"(m), "r"(bar), "r"(c0), "r"(c1)
        : "memory");
}
__device__ __forceinline__ void tma_load_2d_mc(uint32_t dst, const CUtensorMap* m, int c0, int c1, uint32_t bar, uint16_t mask) {
    asm volatile(
        "cp.async.bulk.tensor.2d.shared::cluster.global.mbarrier::complete_tx::bytes.multicast::cluster [%0], [%1, {%3, %4}], [%2], %5;"
        ::"r"(dst), "l"(m), "r"(bar), "r"(c0), "r"(c1), "h"(mask)
        : "memory");
}
__device__ __forceinline__ void tma_store_2d(const CUtensorMap* m, uint32_t src, int c0, int c1) {
    asm volatile("cp.async.bulk.tensor.2d.global.shared::cta.bulk_group [%0, {%2, %3}], [%1];"
                 ::"l"(m), "r"(src), "r"(c0), "r"(c1)
                 : "memory");
}
__device__ __forceinline__ void tma_store_commit() { asm volatile("cp.async.bulk.commit_group;" ::: "memory"); }
template <int N> __device__ __forceinline__ void tma_store_wait_read() {
    asm volatile("cp.async.bulk.wait_group.read %0;" ::"n"(N) : "memory");
}
template <int N> __device__ __forceinline__ void tma_store_wait() {
    asm volatile("cp.async.bulk.wait_group %0;" ::"n"(N) : "memory");
}

__device__ __forceinline__ void wgmma_fence() { asm volatile("wgmma.fence.sync.aligned;" ::: "memory"); }
__device__ __forceinline__ void wgmma_commit() { asm volatile("wgmma.commit_group.sync.aligned;" ::: "memory"); }
template <int N> __device__ __forceinline__ void wgmma_wait() {
    asm volatile("wgmma.wait_group.sync.aligned %0;" ::"n"(N) : "memory");
}
template <int R> __device__ __forceinline__ void reg_alloc() { asm volatile("setmaxnreg.inc.sync.aligned.u32 %0;" ::"n"(R)); }
template <int R> __device__ __forceinline__ void reg_dealloc() { asm volatile("setmaxnreg.dec.sync.aligned.u32 %0;" ::"n"(R)); }

template <int N> __device__ __forceinline__ void fence_regs(float (&r)[N]) {
#pragma unroll
    for (int i = 0; i < N; i++) asm volatile("" : "+f"(r[i])::"memory");
}
template <int N> __device__ __forceinline__ void fence_regs_u(uint32_t (&r)[N][4]) {
#pragma unroll
    for (int i = 0; i < N; i++) {
#pragma unroll
        for (int j = 0; j < 4; j++) asm volatile("" : "+r"(r[i][j])::"memory");
    }
}

__device__ __forceinline__ uint64_t make_desc(uint32_t addr, uint32_t lbo_bytes, uint32_t sbo_bytes, uint32_t swz) {
    return (uint64_t)((addr & 0x3FFFF) >> 4) | ((uint64_t)(lbo_bytes >> 4) << 16) | ((uint64_t)(sbo_bytes >> 4) << 32) |
           ((uint64_t)swz << 62);
}

__device__ __forceinline__ uint32_t pack_bf16(float lo, float hi) {
    uint32_t r;
    asm("cvt.rn.bf16x2.f32 %0, %1, %2;" : "=r"(r) : "f"(hi), "f"(lo));
    return r;
}
__device__ __forceinline__ float bf16_round(float x) { return __bfloat162float(__float2bfloat16_rn(x)); }
__device__ __forceinline__ float bf16lo(uint32_t v) { return __uint_as_float(v << 16); }
__device__ __forceinline__ float bf16hi(uint32_t v) { return __uint_as_float(v & 0xffff0000u); }
__device__ __forceinline__ float ex2(float x) {
    float y;
    asm("ex2.approx.ftz.f32 %0, %1;" : "=f"(y) : "f"(x));
    return y;
}
__device__ __forceinline__ void stmatrix_x4(uint32_t addr, uint32_t r0, uint32_t r1, uint32_t r2, uint32_t r3) {
    asm volatile("stmatrix.sync.aligned.m8n8.x4.shared.b16 [%0], {%1, %2, %3, %4};" ::"r"(addr), "r"(r0), "r"(r1), "r"(r2), "r"(r3)
                 : "memory");
}
__device__ __forceinline__ uint32_t mapa(uint32_t addr, uint32_t cta) {
    uint32_t r;
    asm volatile("mapa.shared::cluster.u32 %0, %1, %2;" : "=r"(r) : "r"(addr), "r"(cta));
    return r;
}
__device__ __forceinline__ void st_cluster_v2(uint32_t addr, float a, float b) {
    asm volatile("st.shared::cluster.v2.f32 [%0], {%1, %2};" ::"r"(addr), "f"(a), "f"(b) : "memory");
}
__device__ __forceinline__ void wgmma_ss_n256_t1(float (&d)[128], uint64_t descA, uint64_t descB, int scaleD) {
    asm volatile("{\n.reg .pred p;\n"
        "setp.ne.b32 p, %130, 0;\n"
        "wgmma.mma_async.sync.aligned.m64n256k16.f32.bf16.bf16 "
        "{%0, %1, %2, %3, %4, %5, %6, %7, %8, %9, %10, %11, %12, %13, %14, %15, "
        "%16, %17, %18, %19, %20, %21, %22, %23, %24, %25, %26, %27, %28, %29, %30, %31, "
        "%32, %33, %34, %35, %36, %37, %38, %39, %40, %41, %42, %43, %44, %45, %46, %47, "
        "%48, %49, %50, %51, %52, %53, %54, %55, %56, %57, %58, %59, %60, %61, %62, %63, "
        "%64, %65, %66, %67, %68, %69, %70, %71, %72, %73, %74, %75, %76, %77, %78, %79, "
        "%80, %81, %82, %83, %84, %85, %86, %87, %88, %89, %90, %91, %92, %93, %94, %95, "
        "%96, %97, %98, %99, %100, %101, %102, %103, %104, %105, %106, %107, %108, %109, %110, %111, "
        "%112, %113, %114, %115, %116, %117, %118, %119, %120, %121, %122, %123, %124, %125, %126, %127}, "
        "%128, %129, p, 1, 1, 0, 1;\n}\n"
        :
          "+f"(d[0]), "+f"(d[1]), "+f"(d[2]), "+f"(d[3]), "+f"(d[4]), "+f"(d[5]), "+f"(d[6]), "+f"(d[7]),
          "+f"(d[8]), "+f"(d[9]), "+f"(d[10]), "+f"(d[11]), "+f"(d[12]), "+f"(d[13]), "+f"(d[14]), "+f"(d[15]),
          "+f"(d[16]), "+f"(d[17]), "+f"(d[18]), "+f"(d[19]), "+f"(d[20]), "+f"(d[21]), "+f"(d[22]), "+f"(d[23]),
          "+f"(d[24]), "+f"(d[25]), "+f"(d[26]), "+f"(d[27]), "+f"(d[28]), "+f"(d[29]), "+f"(d[30]), "+f"(d[31]),
          "+f"(d[32]), "+f"(d[33]), "+f"(d[34]), "+f"(d[35]), "+f"(d[36]), "+f"(d[37]), "+f"(d[38]), "+f"(d[39]),
          "+f"(d[40]), "+f"(d[41]), "+f"(d[42]), "+f"(d[43]), "+f"(d[44]), "+f"(d[45]), "+f"(d[46]), "+f"(d[47]),
          "+f"(d[48]), "+f"(d[49]), "+f"(d[50]), "+f"(d[51]), "+f"(d[52]), "+f"(d[53]), "+f"(d[54]), "+f"(d[55]),
          "+f"(d[56]), "+f"(d[57]), "+f"(d[58]), "+f"(d[59]), "+f"(d[60]), "+f"(d[61]), "+f"(d[62]), "+f"(d[63]),
          "+f"(d[64]), "+f"(d[65]), "+f"(d[66]), "+f"(d[67]), "+f"(d[68]), "+f"(d[69]), "+f"(d[70]), "+f"(d[71]),
          "+f"(d[72]), "+f"(d[73]), "+f"(d[74]), "+f"(d[75]), "+f"(d[76]), "+f"(d[77]), "+f"(d[78]), "+f"(d[79]),
          "+f"(d[80]), "+f"(d[81]), "+f"(d[82]), "+f"(d[83]), "+f"(d[84]), "+f"(d[85]), "+f"(d[86]), "+f"(d[87]),
          "+f"(d[88]), "+f"(d[89]), "+f"(d[90]), "+f"(d[91]), "+f"(d[92]), "+f"(d[93]), "+f"(d[94]), "+f"(d[95]),
          "+f"(d[96]), "+f"(d[97]), "+f"(d[98]), "+f"(d[99]), "+f"(d[100]), "+f"(d[101]), "+f"(d[102]), "+f"(d[103]),
          "+f"(d[104]), "+f"(d[105]), "+f"(d[106]), "+f"(d[107]), "+f"(d[108]), "+f"(d[109]), "+f"(d[110]), "+f"(d[111]),
          "+f"(d[112]), "+f"(d[113]), "+f"(d[114]), "+f"(d[115]), "+f"(d[116]), "+f"(d[117]), "+f"(d[118]), "+f"(d[119]),
          "+f"(d[120]), "+f"(d[121]), "+f"(d[122]), "+f"(d[123]), "+f"(d[124]), "+f"(d[125]), "+f"(d[126]), "+f"(d[127])
        : "l"(descA), "l"(descB), "r"(scaleD));
}

__device__ __forceinline__ void wgmma_ss_n256_t1_z(float (&d)[128], uint64_t descA, uint64_t descB) {
    asm volatile("{\n.reg .pred p;\n"
        "setp.ne.b32 p, 0, 0;\n"
        "wgmma.mma_async.sync.aligned.m64n256k16.f32.bf16.bf16 "
        "{%0, %1, %2, %3, %4, %5, %6, %7, %8, %9, %10, %11, %12, %13, %14, %15, "
        "%16, %17, %18, %19, %20, %21, %22, %23, %24, %25, %26, %27, %28, %29, %30, %31, "
        "%32, %33, %34, %35, %36, %37, %38, %39, %40, %41, %42, %43, %44, %45, %46, %47, "
        "%48, %49, %50, %51, %52, %53, %54, %55, %56, %57, %58, %59, %60, %61, %62, %63, "
        "%64, %65, %66, %67, %68, %69, %70, %71, %72, %73, %74, %75, %76, %77, %78, %79, "
        "%80, %81, %82, %83, %84, %85, %86, %87, %88, %89, %90, %91, %92, %93, %94, %95, "
        "%96, %97, %98, %99, %100, %101, %102, %103, %104, %105, %106, %107, %108, %109, %110, %111, "
        "%112, %113, %114, %115, %116, %117, %118, %119, %120, %121, %122, %123, %124, %125, %126, %127}, "
        "%128, %129, p, 1, 1, 0, 1;\n}\n"
        :
          "=f"(d[0]), "=f"(d[1]), "=f"(d[2]), "=f"(d[3]), "=f"(d[4]), "=f"(d[5]), "=f"(d[6]), "=f"(d[7]),
          "=f"(d[8]), "=f"(d[9]), "=f"(d[10]), "=f"(d[11]), "=f"(d[12]), "=f"(d[13]), "=f"(d[14]), "=f"(d[15]),
          "=f"(d[16]), "=f"(d[17]), "=f"(d[18]), "=f"(d[19]), "=f"(d[20]), "=f"(d[21]), "=f"(d[22]), "=f"(d[23]),
          "=f"(d[24]), "=f"(d[25]), "=f"(d[26]), "=f"(d[27]), "=f"(d[28]), "=f"(d[29]), "=f"(d[30]), "=f"(d[31]),
          "=f"(d[32]), "=f"(d[33]), "=f"(d[34]), "=f"(d[35]), "=f"(d[36]), "=f"(d[37]), "=f"(d[38]), "=f"(d[39]),
          "=f"(d[40]), "=f"(d[41]), "=f"(d[42]), "=f"(d[43]), "=f"(d[44]), "=f"(d[45]), "=f"(d[46]), "=f"(d[47]),
          "=f"(d[48]), "=f"(d[49]), "=f"(d[50]), "=f"(d[51]), "=f"(d[52]), "=f"(d[53]), "=f"(d[54]), "=f"(d[55]),
          "=f"(d[56]), "=f"(d[57]), "=f"(d[58]), "=f"(d[59]), "=f"(d[60]), "=f"(d[61]), "=f"(d[62]), "=f"(d[63]),
          "=f"(d[64]), "=f"(d[65]), "=f"(d[66]), "=f"(d[67]), "=f"(d[68]), "=f"(d[69]), "=f"(d[70]), "=f"(d[71]),
          "=f"(d[72]), "=f"(d[73]), "=f"(d[74]), "=f"(d[75]), "=f"(d[76]), "=f"(d[77]), "=f"(d[78]), "=f"(d[79]),
          "=f"(d[80]), "=f"(d[81]), "=f"(d[82]), "=f"(d[83]), "=f"(d[84]), "=f"(d[85]), "=f"(d[86]), "=f"(d[87]),
          "=f"(d[88]), "=f"(d[89]), "=f"(d[90]), "=f"(d[91]), "=f"(d[92]), "=f"(d[93]), "=f"(d[94]), "=f"(d[95]),
          "=f"(d[96]), "=f"(d[97]), "=f"(d[98]), "=f"(d[99]), "=f"(d[100]), "=f"(d[101]), "=f"(d[102]), "=f"(d[103]),
          "=f"(d[104]), "=f"(d[105]), "=f"(d[106]), "=f"(d[107]), "=f"(d[108]), "=f"(d[109]), "=f"(d[110]), "=f"(d[111]),
          "=f"(d[112]), "=f"(d[113]), "=f"(d[114]), "=f"(d[115]), "=f"(d[116]), "=f"(d[117]), "=f"(d[118]), "=f"(d[119]),
          "=f"(d[120]), "=f"(d[121]), "=f"(d[122]), "=f"(d[123]), "=f"(d[124]), "=f"(d[125]), "=f"(d[126]), "=f"(d[127])
        : "l"(descA), "l"(descB));
}

__device__ __forceinline__ void wgmma_rs_n128_t0(float (&d)[64], const uint32_t (&a)[4], uint64_t descB, int scaleD) {
    asm volatile("{\n.reg .pred p;\n"
        "setp.ne.b32 p, %69, 0;\n"
        "wgmma.mma_async.sync.aligned.m64n128k16.f32.bf16.bf16 "
        "{%0, %1, %2, %3, %4, %5, %6, %7, %8, %9, %10, %11, %12, %13, %14, %15, "
        "%16, %17, %18, %19, %20, %21, %22, %23, %24, %25, %26, %27, %28, %29, %30, %31, "
        "%32, %33, %34, %35, %36, %37, %38, %39, %40, %41, %42, %43, %44, %45, %46, %47, "
        "%48, %49, %50, %51, %52, %53, %54, %55, %56, %57, %58, %59, %60, %61, %62, %63}, "
        "{%64, %65, %66, %67}, %68, p, 1, 1, 0;\n}\n"
        :
          "+f"(d[0]), "+f"(d[1]), "+f"(d[2]), "+f"(d[3]), "+f"(d[4]), "+f"(d[5]), "+f"(d[6]), "+f"(d[7]),
          "+f"(d[8]), "+f"(d[9]), "+f"(d[10]), "+f"(d[11]), "+f"(d[12]), "+f"(d[13]), "+f"(d[14]), "+f"(d[15]),
          "+f"(d[16]), "+f"(d[17]), "+f"(d[18]), "+f"(d[19]), "+f"(d[20]), "+f"(d[21]), "+f"(d[22]), "+f"(d[23]),
          "+f"(d[24]), "+f"(d[25]), "+f"(d[26]), "+f"(d[27]), "+f"(d[28]), "+f"(d[29]), "+f"(d[30]), "+f"(d[31]),
          "+f"(d[32]), "+f"(d[33]), "+f"(d[34]), "+f"(d[35]), "+f"(d[36]), "+f"(d[37]), "+f"(d[38]), "+f"(d[39]),
          "+f"(d[40]), "+f"(d[41]), "+f"(d[42]), "+f"(d[43]), "+f"(d[44]), "+f"(d[45]), "+f"(d[46]), "+f"(d[47]),
          "+f"(d[48]), "+f"(d[49]), "+f"(d[50]), "+f"(d[51]), "+f"(d[52]), "+f"(d[53]), "+f"(d[54]), "+f"(d[55]),
          "+f"(d[56]), "+f"(d[57]), "+f"(d[58]), "+f"(d[59]), "+f"(d[60]), "+f"(d[61]), "+f"(d[62]), "+f"(d[63])
        : "r"(a[0]), "r"(a[1]), "r"(a[2]), "r"(a[3]), "l"(descB), "r"(scaleD));
}

__device__ __forceinline__ void wgmma_rs_n128_t0_z(float (&d)[64], const uint32_t (&a)[4], uint64_t descB) {
    asm volatile("{\n.reg .pred p;\n"
        "setp.ne.b32 p, 0, 0;\n"
        "wgmma.mma_async.sync.aligned.m64n128k16.f32.bf16.bf16 "
        "{%0, %1, %2, %3, %4, %5, %6, %7, %8, %9, %10, %11, %12, %13, %14, %15, "
        "%16, %17, %18, %19, %20, %21, %22, %23, %24, %25, %26, %27, %28, %29, %30, %31, "
        "%32, %33, %34, %35, %36, %37, %38, %39, %40, %41, %42, %43, %44, %45, %46, %47, "
        "%48, %49, %50, %51, %52, %53, %54, %55, %56, %57, %58, %59, %60, %61, %62, %63}, "
        "{%64, %65, %66, %67}, %68, p, 1, 1, 0;\n}\n"
        :
          "=f"(d[0]), "=f"(d[1]), "=f"(d[2]), "=f"(d[3]), "=f"(d[4]), "=f"(d[5]), "=f"(d[6]), "=f"(d[7]),
          "=f"(d[8]), "=f"(d[9]), "=f"(d[10]), "=f"(d[11]), "=f"(d[12]), "=f"(d[13]), "=f"(d[14]), "=f"(d[15]),
          "=f"(d[16]), "=f"(d[17]), "=f"(d[18]), "=f"(d[19]), "=f"(d[20]), "=f"(d[21]), "=f"(d[22]), "=f"(d[23]),
          "=f"(d[24]), "=f"(d[25]), "=f"(d[26]), "=f"(d[27]), "=f"(d[28]), "=f"(d[29]), "=f"(d[30]), "=f"(d[31]),
          "=f"(d[32]), "=f"(d[33]), "=f"(d[34]), "=f"(d[35]), "=f"(d[36]), "=f"(d[37]), "=f"(d[38]), "=f"(d[39]),
          "=f"(d[40]), "=f"(d[41]), "=f"(d[42]), "=f"(d[43]), "=f"(d[44]), "=f"(d[45]), "=f"(d[46]), "=f"(d[47]),
          "=f"(d[48]), "=f"(d[49]), "=f"(d[50]), "=f"(d[51]), "=f"(d[52]), "=f"(d[53]), "=f"(d[54]), "=f"(d[55]),
          "=f"(d[56]), "=f"(d[57]), "=f"(d[58]), "=f"(d[59]), "=f"(d[60]), "=f"(d[61]), "=f"(d[62]), "=f"(d[63])
        : "r"(a[0]), "r"(a[1]), "r"(a[2]), "r"(a[3]), "l"(descB));
}

__device__ __forceinline__ void wgmma_rs_n128_t1(float (&d)[64], const uint32_t (&a)[4], uint64_t descB, int scaleD) {
    asm volatile("{\n.reg .pred p;\n"
        "setp.ne.b32 p, %69, 0;\n"
        "wgmma.mma_async.sync.aligned.m64n128k16.f32.bf16.bf16 "
        "{%0, %1, %2, %3, %4, %5, %6, %7, %8, %9, %10, %11, %12, %13, %14, %15, "
        "%16, %17, %18, %19, %20, %21, %22, %23, %24, %25, %26, %27, %28, %29, %30, %31, "
        "%32, %33, %34, %35, %36, %37, %38, %39, %40, %41, %42, %43, %44, %45, %46, %47, "
        "%48, %49, %50, %51, %52, %53, %54, %55, %56, %57, %58, %59, %60, %61, %62, %63}, "
        "{%64, %65, %66, %67}, %68, p, 1, 1, 1;\n}\n"
        :
          "+f"(d[0]), "+f"(d[1]), "+f"(d[2]), "+f"(d[3]), "+f"(d[4]), "+f"(d[5]), "+f"(d[6]), "+f"(d[7]),
          "+f"(d[8]), "+f"(d[9]), "+f"(d[10]), "+f"(d[11]), "+f"(d[12]), "+f"(d[13]), "+f"(d[14]), "+f"(d[15]),
          "+f"(d[16]), "+f"(d[17]), "+f"(d[18]), "+f"(d[19]), "+f"(d[20]), "+f"(d[21]), "+f"(d[22]), "+f"(d[23]),
          "+f"(d[24]), "+f"(d[25]), "+f"(d[26]), "+f"(d[27]), "+f"(d[28]), "+f"(d[29]), "+f"(d[30]), "+f"(d[31]),
          "+f"(d[32]), "+f"(d[33]), "+f"(d[34]), "+f"(d[35]), "+f"(d[36]), "+f"(d[37]), "+f"(d[38]), "+f"(d[39]),
          "+f"(d[40]), "+f"(d[41]), "+f"(d[42]), "+f"(d[43]), "+f"(d[44]), "+f"(d[45]), "+f"(d[46]), "+f"(d[47]),
          "+f"(d[48]), "+f"(d[49]), "+f"(d[50]), "+f"(d[51]), "+f"(d[52]), "+f"(d[53]), "+f"(d[54]), "+f"(d[55]),
          "+f"(d[56]), "+f"(d[57]), "+f"(d[58]), "+f"(d[59]), "+f"(d[60]), "+f"(d[61]), "+f"(d[62]), "+f"(d[63])
        : "r"(a[0]), "r"(a[1]), "r"(a[2]), "r"(a[3]), "l"(descB), "r"(scaleD));
}

__device__ __forceinline__ void wgmma_rs_n128_t1_z(float (&d)[64], const uint32_t (&a)[4], uint64_t descB) {
    asm volatile("{\n.reg .pred p;\n"
        "setp.ne.b32 p, 0, 0;\n"
        "wgmma.mma_async.sync.aligned.m64n128k16.f32.bf16.bf16 "
        "{%0, %1, %2, %3, %4, %5, %6, %7, %8, %9, %10, %11, %12, %13, %14, %15, "
        "%16, %17, %18, %19, %20, %21, %22, %23, %24, %25, %26, %27, %28, %29, %30, %31, "
        "%32, %33, %34, %35, %36, %37, %38, %39, %40, %41, %42, %43, %44, %45, %46, %47, "
        "%48, %49, %50, %51, %52, %53, %54, %55, %56, %57, %58, %59, %60, %61, %62, %63}, "
        "{%64, %65, %66, %67}, %68, p, 1, 1, 1;\n}\n"
        :
          "=f"(d[0]), "=f"(d[1]), "=f"(d[2]), "=f"(d[3]), "=f"(d[4]), "=f"(d[5]), "=f"(d[6]), "=f"(d[7]),
          "=f"(d[8]), "=f"(d[9]), "=f"(d[10]), "=f"(d[11]), "=f"(d[12]), "=f"(d[13]), "=f"(d[14]), "=f"(d[15]),
          "=f"(d[16]), "=f"(d[17]), "=f"(d[18]), "=f"(d[19]), "=f"(d[20]), "=f"(d[21]), "=f"(d[22]), "=f"(d[23]),
          "=f"(d[24]), "=f"(d[25]), "=f"(d[26]), "=f"(d[27]), "=f"(d[28]), "=f"(d[29]), "=f"(d[30]), "=f"(d[31]),
          "=f"(d[32]), "=f"(d[33]), "=f"(d[34]), "=f"(d[35]), "=f"(d[36]), "=f"(d[37]), "=f"(d[38]), "=f"(d[39]),
          "=f"(d[40]), "=f"(d[41]), "=f"(d[42]), "=f"(d[43]), "=f"(d[44]), "=f"(d[45]), "=f"(d[46]), "=f"(d[47]),
          "=f"(d[48]), "=f"(d[49]), "=f"(d[50]), "=f"(d[51]), "=f"(d[52]), "=f"(d[53]), "=f"(d[54]), "=f"(d[55]),
          "=f"(d[56]), "=f"(d[57]), "=f"(d[58]), "=f"(d[59]), "=f"(d[60]), "=f"(d[61]), "=f"(d[62]), "=f"(d[63])
        : "r"(a[0]), "r"(a[1]), "r"(a[2]), "r"(a[3]), "l"(descB));
}

__device__ __forceinline__ void wgmma_ss_n160_t1(float (&d)[80], uint64_t descA, uint64_t descB, int scaleD) {
    asm volatile("{\n.reg .pred p;\n"
        "setp.ne.b32 p, %82, 0;\n"
        "wgmma.mma_async.sync.aligned.m64n160k16.f32.bf16.bf16 "
        "{%0, %1, %2, %3, %4, %5, %6, %7, %8, %9, %10, %11, %12, %13, %14, %15, "
        "%16, %17, %18, %19, %20, %21, %22, %23, %24, %25, %26, %27, %28, %29, %30, %31, "
        "%32, %33, %34, %35, %36, %37, %38, %39, %40, %41, %42, %43, %44, %45, %46, %47, "
        "%48, %49, %50, %51, %52, %53, %54, %55, %56, %57, %58, %59, %60, %61, %62, %63, "
        "%64, %65, %66, %67, %68, %69, %70, %71, %72, %73, %74, %75, %76, %77, %78, %79}, "
        "%80, %81, p, 1, 1, 0, 1;\n}\n"
        :
          "+f"(d[0]), "+f"(d[1]), "+f"(d[2]), "+f"(d[3]), "+f"(d[4]), "+f"(d[5]), "+f"(d[6]), "+f"(d[7]),
          "+f"(d[8]), "+f"(d[9]), "+f"(d[10]), "+f"(d[11]), "+f"(d[12]), "+f"(d[13]), "+f"(d[14]), "+f"(d[15]),
          "+f"(d[16]), "+f"(d[17]), "+f"(d[18]), "+f"(d[19]), "+f"(d[20]), "+f"(d[21]), "+f"(d[22]), "+f"(d[23]),
          "+f"(d[24]), "+f"(d[25]), "+f"(d[26]), "+f"(d[27]), "+f"(d[28]), "+f"(d[29]), "+f"(d[30]), "+f"(d[31]),
          "+f"(d[32]), "+f"(d[33]), "+f"(d[34]), "+f"(d[35]), "+f"(d[36]), "+f"(d[37]), "+f"(d[38]), "+f"(d[39]),
          "+f"(d[40]), "+f"(d[41]), "+f"(d[42]), "+f"(d[43]), "+f"(d[44]), "+f"(d[45]), "+f"(d[46]), "+f"(d[47]),
          "+f"(d[48]), "+f"(d[49]), "+f"(d[50]), "+f"(d[51]), "+f"(d[52]), "+f"(d[53]), "+f"(d[54]), "+f"(d[55]),
          "+f"(d[56]), "+f"(d[57]), "+f"(d[58]), "+f"(d[59]), "+f"(d[60]), "+f"(d[61]), "+f"(d[62]), "+f"(d[63]),
          "+f"(d[64]), "+f"(d[65]), "+f"(d[66]), "+f"(d[67]), "+f"(d[68]), "+f"(d[69]), "+f"(d[70]), "+f"(d[71]),
          "+f"(d[72]), "+f"(d[73]), "+f"(d[74]), "+f"(d[75]), "+f"(d[76]), "+f"(d[77]), "+f"(d[78]), "+f"(d[79])
        : "l"(descA), "l"(descB), "r"(scaleD));
}

__device__ __forceinline__ void wgmma_ss_n184_t1(float (&d)[92], uint64_t descA, uint64_t descB, int scaleD) {
    asm volatile("{\n.reg .pred p;\n"
        "setp.ne.b32 p, %94, 0;\n"
        "wgmma.mma_async.sync.aligned.m64n184k16.f32.bf16.bf16 "
        "{%0, %1, %2, %3, %4, %5, %6, %7, %8, %9, %10, %11, %12, %13, %14, %15, "
        "%16, %17, %18, %19, %20, %21, %22, %23, %24, %25, %26, %27, %28, %29, %30, %31, "
        "%32, %33, %34, %35, %36, %37, %38, %39, %40, %41, %42, %43, %44, %45, %46, %47, "
        "%48, %49, %50, %51, %52, %53, %54, %55, %56, %57, %58, %59, %60, %61, %62, %63, "
        "%64, %65, %66, %67, %68, %69, %70, %71, %72, %73, %74, %75, %76, %77, %78, %79, "
        "%80, %81, %82, %83, %84, %85, %86, %87, %88, %89, %90, %91}, "
        "%92, %93, p, 1, 1, 0, 1;\n}\n"
        :
          "+f"(d[0]), "+f"(d[1]), "+f"(d[2]), "+f"(d[3]), "+f"(d[4]), "+f"(d[5]), "+f"(d[6]), "+f"(d[7]),
          "+f"(d[8]), "+f"(d[9]), "+f"(d[10]), "+f"(d[11]), "+f"(d[12]), "+f"(d[13]), "+f"(d[14]), "+f"(d[15]),
          "+f"(d[16]), "+f"(d[17]), "+f"(d[18]), "+f"(d[19]), "+f"(d[20]), "+f"(d[21]), "+f"(d[22]), "+f"(d[23]),
          "+f"(d[24]), "+f"(d[25]), "+f"(d[26]), "+f"(d[27]), "+f"(d[28]), "+f"(d[29]), "+f"(d[30]), "+f"(d[31]),
          "+f"(d[32]), "+f"(d[33]), "+f"(d[34]), "+f"(d[35]), "+f"(d[36]), "+f"(d[37]), "+f"(d[38]), "+f"(d[39]),
          "+f"(d[40]), "+f"(d[41]), "+f"(d[42]), "+f"(d[43]), "+f"(d[44]), "+f"(d[45]), "+f"(d[46]), "+f"(d[47]),
          "+f"(d[48]), "+f"(d[49]), "+f"(d[50]), "+f"(d[51]), "+f"(d[52]), "+f"(d[53]), "+f"(d[54]), "+f"(d[55]),
          "+f"(d[56]), "+f"(d[57]), "+f"(d[58]), "+f"(d[59]), "+f"(d[60]), "+f"(d[61]), "+f"(d[62]), "+f"(d[63]),
          "+f"(d[64]), "+f"(d[65]), "+f"(d[66]), "+f"(d[67]), "+f"(d[68]), "+f"(d[69]), "+f"(d[70]), "+f"(d[71]),
          "+f"(d[72]), "+f"(d[73]), "+f"(d[74]), "+f"(d[75]), "+f"(d[76]), "+f"(d[77]), "+f"(d[78]), "+f"(d[79]),
          "+f"(d[80]), "+f"(d[81]), "+f"(d[82]), "+f"(d[83]), "+f"(d[84]), "+f"(d[85]), "+f"(d[86]), "+f"(d[87]),
          "+f"(d[88]), "+f"(d[89]), "+f"(d[90]), "+f"(d[91])
        : "l"(descA), "l"(descB), "r"(scaleD));
}

__device__ __forceinline__ void wgmma_ss_n192_t1(float (&d)[96], uint64_t descA, uint64_t descB, int scaleD) {
    asm volatile("{\n.reg .pred p;\n"
        "setp.ne.b32 p, %98, 0;\n"
        "wgmma.mma_async.sync.aligned.m64n192k16.f32.bf16.bf16 "
        "{%0, %1, %2, %3, %4, %5, %6, %7, %8, %9, %10, %11, %12, %13, %14, %15, "
        "%16, %17, %18, %19, %20, %21, %22, %23, %24, %25, %26, %27, %28, %29, %30, %31, "
        "%32, %33, %34, %35, %36, %37, %38, %39, %40, %41, %42, %43, %44, %45, %46, %47, "
        "%48, %49, %50, %51, %52, %53, %54, %55, %56, %57, %58, %59, %60, %61, %62, %63, "
        "%64, %65, %66, %67, %68, %69, %70, %71, %72, %73, %74, %75, %76, %77, %78, %79, "
        "%80, %81, %82, %83, %84, %85, %86, %87, %88, %89, %90, %91, %92, %93, %94, %95}, "
        "%96, %97, p, 1, 1, 0, 1;\n}\n"
        :
          "+f"(d[0]), "+f"(d[1]), "+f"(d[2]), "+f"(d[3]), "+f"(d[4]), "+f"(d[5]), "+f"(d[6]), "+f"(d[7]),
          "+f"(d[8]), "+f"(d[9]), "+f"(d[10]), "+f"(d[11]), "+f"(d[12]), "+f"(d[13]), "+f"(d[14]), "+f"(d[15]),
          "+f"(d[16]), "+f"(d[17]), "+f"(d[18]), "+f"(d[19]), "+f"(d[20]), "+f"(d[21]), "+f"(d[22]), "+f"(d[23]),
          "+f"(d[24]), "+f"(d[25]), "+f"(d[26]), "+f"(d[27]), "+f"(d[28]), "+f"(d[29]), "+f"(d[30]), "+f"(d[31]),
          "+f"(d[32]), "+f"(d[33]), "+f"(d[34]), "+f"(d[35]), "+f"(d[36]), "+f"(d[37]), "+f"(d[38]), "+f"(d[39]),
          "+f"(d[40]), "+f"(d[41]), "+f"(d[42]), "+f"(d[43]), "+f"(d[44]), "+f"(d[45]), "+f"(d[46]), "+f"(d[47]),
          "+f"(d[48]), "+f"(d[49]), "+f"(d[50]), "+f"(d[51]), "+f"(d[52]), "+f"(d[53]), "+f"(d[54]), "+f"(d[55]),
          "+f"(d[56]), "+f"(d[57]), "+f"(d[58]), "+f"(d[59]), "+f"(d[60]), "+f"(d[61]), "+f"(d[62]), "+f"(d[63]),
          "+f"(d[64]), "+f"(d[65]), "+f"(d[66]), "+f"(d[67]), "+f"(d[68]), "+f"(d[69]), "+f"(d[70]), "+f"(d[71]),
          "+f"(d[72]), "+f"(d[73]), "+f"(d[74]), "+f"(d[75]), "+f"(d[76]), "+f"(d[77]), "+f"(d[78]), "+f"(d[79]),
          "+f"(d[80]), "+f"(d[81]), "+f"(d[82]), "+f"(d[83]), "+f"(d[84]), "+f"(d[85]), "+f"(d[86]), "+f"(d[87]),
          "+f"(d[88]), "+f"(d[89]), "+f"(d[90]), "+f"(d[91]), "+f"(d[92]), "+f"(d[93]), "+f"(d[94]), "+f"(d[95])
        : "l"(descA), "l"(descB), "r"(scaleD));
}

__device__ __forceinline__ void wgmma_ss_n128_t1(float (&d)[64], uint64_t descA, uint64_t descB, int scaleD) {
    asm volatile("{\n.reg .pred p;\n"
        "setp.ne.b32 p, %66, 0;\n"
        "wgmma.mma_async.sync.aligned.m64n128k16.f32.bf16.bf16 "
        "{%0, %1, %2, %3, %4, %5, %6, %7, %8, %9, %10, %11, %12, %13, %14, %15, "
        "%16, %17, %18, %19, %20, %21, %22, %23, %24, %25, %26, %27, %28, %29, %30, %31, "
        "%32, %33, %34, %35, %36, %37, %38, %39, %40, %41, %42, %43, %44, %45, %46, %47, "
        "%48, %49, %50, %51, %52, %53, %54, %55, %56, %57, %58, %59, %60, %61, %62, %63}, "
        "%64, %65, p, 1, 1, 0, 1;\n}\n"
        :
          "+f"(d[0]), "+f"(d[1]), "+f"(d[2]), "+f"(d[3]), "+f"(d[4]), "+f"(d[5]), "+f"(d[6]), "+f"(d[7]),
          "+f"(d[8]), "+f"(d[9]), "+f"(d[10]), "+f"(d[11]), "+f"(d[12]), "+f"(d[13]), "+f"(d[14]), "+f"(d[15]),
          "+f"(d[16]), "+f"(d[17]), "+f"(d[18]), "+f"(d[19]), "+f"(d[20]), "+f"(d[21]), "+f"(d[22]), "+f"(d[23]),
          "+f"(d[24]), "+f"(d[25]), "+f"(d[26]), "+f"(d[27]), "+f"(d[28]), "+f"(d[29]), "+f"(d[30]), "+f"(d[31]),
          "+f"(d[32]), "+f"(d[33]), "+f"(d[34]), "+f"(d[35]), "+f"(d[36]), "+f"(d[37]), "+f"(d[38]), "+f"(d[39]),
          "+f"(d[40]), "+f"(d[41]), "+f"(d[42]), "+f"(d[43]), "+f"(d[44]), "+f"(d[45]), "+f"(d[46]), "+f"(d[47]),
          "+f"(d[48]), "+f"(d[49]), "+f"(d[50]), "+f"(d[51]), "+f"(d[52]), "+f"(d[53]), "+f"(d[54]), "+f"(d[55]),
          "+f"(d[56]), "+f"(d[57]), "+f"(d[58]), "+f"(d[59]), "+f"(d[60]), "+f"(d[61]), "+f"(d[62]), "+f"(d[63])
        : "l"(descA), "l"(descB), "r"(scaleD));
}

constexpr int S_LEN = 2048;
constexpr int D_MODEL = 640;
constexpr int N_HEADS = 32;
constexpr int D_HEAD = 128;
constexpr int S_KV = 2048;
constexpr int WIN = 512;
constexpr int D_FF = 1728;
constexpr float LN_EPS = 1e-5f;

#define TS(kid, slot)

__device__ float g_mod[6 * D_MODEL];
__device__ __align__(1024) __nv_bfloat16 g_h[S_LEN * D_MODEL];
__device__ __align__(1024) __nv_bfloat16 g_o[S_LEN * N_HEADS * D_HEAD];
__device__ __align__(1024) __nv_bfloat16 g_part[4 * S_LEN * D_MODEL];
__device__ __align__(1024) __nv_bfloat16 g_x1[S_LEN * D_MODEL];
__device__ __align__(1024) __nv_bfloat16 g_h2[S_LEN * D_MODEL];
__device__ __align__(1024) __nv_bfloat16 g_act[S_LEN * D_FF];

constexpr int F_MODAB = 0, F_MODALL = 1, F_H = 2, F_P = 18, F_H2 = 34, F_A = 50, F_O = 66, F_COUNT = 130;
__device__ unsigned g_flags[F_COUNT * 32];
__device__ unsigned g_epoch;
__device__ unsigned g_exit;

__device__ __forceinline__ void flag_signal(int f) {
    asm volatile("red.release.gpu.global.add.u32 [%0], 1;" ::"l"(g_flags + f * 32) : "memory");
}
__device__ __forceinline__ void flag_signal_relaxed(int f) {
    asm volatile("red.relaxed.gpu.global.add.u32 [%0], 1;" ::"l"(g_flags + f * 32) : "memory");
}
__device__ __forceinline__ void flag_wait(int f, unsigned target) {
    unsigned n = 0;
    while (true) {
        unsigned v;
        asm volatile("ld.acquire.gpu.global.u32 %0, [%1];" : "=r"(v) : "l"(g_flags + f * 32) : "memory");
        if ((int)(v - target) >= 0) break;
        ++n;
        if (n > (1u << 22)) { g_abort = 1; break; }
        if ((n & 255u) == 0 && g_abort) break;
    }
}

struct Maps {
    CUtensorMap h, wq, k, v, o_st, o_a, wo, part_st, h2, g128, u128, g64, u64, act_st64, act_st24, act_a, wd;
};

constexpr int SM_DATA = 229376;
constexpr int SM_STAGING = 196608;
constexpr int SM_TOTAL = SM_DATA + 1024 + 512;
constexpr int B1F = 0, B1E = 6, B2F = 12, B2E = 16, B4F = 20, B4E = 24, B5F = 28, B5E = 33, BD1 = 38, BD2 = 39, BD4 = 40, BD1A = 41, BX = 42;
constexpr int P1_STAGE = 32768, P2_STAGE = 57344, P4_STAGE = 49152, P5_STAGE = 40960;

__device__ __forceinline__ float rcp_approx(float x) { float y; asm("rcp.approx.ftz.f32 %0, %1;" : "=f"(y) : "f"(x)); return y; }
__device__ __forceinline__ float silu_mul(float g, float u) { return g * rcp_approx(1.f + ex2(-1.4426950408889634f * g)) * u; }
__device__ __forceinline__ uint2 ldcg_u2(const void* p) { return __ldcg(reinterpret_cast<const uint2*>(p)); }

__device__ __forceinline__ void ln_rows(const uint2 (&xr)[2][5], const float* __restrict__ shift, const float* __restrict__ scale1p,
                                     __nv_bfloat16* __restrict__ dst, int lane) {
    float4 sh[5], sc[5];
#pragma unroll
    for (int i = 0; i < 5; i++) {
        sh[i] = __ldcg(reinterpret_cast<const float4*>(shift + (lane + 32 * i) * 4));
        sc[i] = __ldcg(reinterpret_cast<const float4*>(scale1p + (lane + 32 * i) * 4));
    }
    float mean[2], rstd[2];
#pragma unroll
    for (int rr = 0; rr < 2; rr++) {
        float s = 0.f;
#pragma unroll
        for (int i = 0; i < 5; i++) s += (bf16lo(xr[rr][i].x) + bf16hi(xr[rr][i].x)) + (bf16lo(xr[rr][i].y) + bf16hi(xr[rr][i].y));
#pragma unroll
        for (int o = 16; o > 0; o >>= 1) s += __shfl_xor_sync(0xffffffffu, s, o);
        mean[rr] = s * (1.f / D_MODEL);
    }
#pragma unroll
    for (int rr = 0; rr < 2; rr++) {
        float q = 0.f;
#pragma unroll
        for (int i = 0; i < 5; i++) {
            const float d0 = bf16lo(xr[rr][i].x) - mean[rr], d1 = bf16hi(xr[rr][i].x) - mean[rr];
            const float d2 = bf16lo(xr[rr][i].y) - mean[rr], d3 = bf16hi(xr[rr][i].y) - mean[rr];
            q += (d0 * d0 + d1 * d1) + (d2 * d2 + d3 * d3);
        }
#pragma unroll
        for (int o = 16; o > 0; o >>= 1) q += __shfl_xor_sync(0xffffffffu, q, o);
        rstd[rr] = rsqrtf(q * (1.f / D_MODEL) + LN_EPS);
    }
#pragma unroll
    for (int rr = 0; rr < 2; rr++) {
#pragma unroll
        for (int i = 0; i < 5; i++) {
            uint2 u;
            u.x = pack_bf16((bf16lo(xr[rr][i].x) - mean[rr]) * rstd[rr] * sc[i].x + sh[i].x, (bf16hi(xr[rr][i].x) - mean[rr]) * rstd[rr] * sc[i].y + sh[i].y);
            u.y = pack_bf16((bf16lo(xr[rr][i].y) - mean[rr]) * rstd[rr] * sc[i].z + sh[i].z, (bf16hi(xr[rr][i].y) - mean[rr]) * rstd[rr] * sc[i].w + sh[i].w);
            *reinterpret_cast<uint2*>(dst + (size_t)rr * D_MODEL + (lane + 32 * i) * 4) = u;
        }
    }
}

__global__ void __cluster_dims__(2, 1, 1) __launch_bounds__(384, 1)
mega_kernel(const __grid_constant__ Maps tm, const __nv_bfloat16* __restrict__ x, const __nv_bfloat16* __restrict__ cvec,
            const __nv_bfloat16* __restrict__ w_mod, __nv_bfloat16* __restrict__ out, const void* wo_p, const void* wg_p,
            const void* wu_p, const void* wd_p) {
    extern __shared__ uint8_t smem_raw[];
    const uint32_t base = (smem_u32(smem_raw) + 1023u) & ~1023u;
    const uint32_t bars = base + SM_DATA;
    const uint32_t rank = cluster_ctarank();
    const int cid = blockIdx.x >> 1;
    const int p = cid & 7, j = cid >> 3;
    const int mt = p * 2 + (int)rank;
    const int m0 = mt * 128;
    const int wg = threadIdx.x >> 7;
    unsigned epoch;
    asm volatile("ld.volatile.global.u32 %0, [%1];" : "=r"(epoch) : "l"(&g_epoch));

    if (threadIdx.x == 0) {
        for (int i = 0; i < 6; i++) { mbar_init(bars + 8 * (B1F + i), 1); mbar_init(bars + 8 * (B1E + i), 4); }
        for (int i = 0; i < 4; i++) { mbar_init(bars + 8 * (B2F + i), 1); mbar_init(bars + 8 * (B2E + i), 4); }
        for (int i = 0; i < 4; i++) { mbar_init(bars + 8 * (B4F + i), 1); mbar_init(bars + 8 * (B4E + i), 4); }
        for (int i = 0; i < 4; i++) { mbar_init(bars + 8 * (B5F + i), 1); mbar_init(bars + 8 * (B5E + i), 2); }
        mbar_init(bars + 8 * BD1, 4); mbar_init(bars + 8 * BD2, 4); mbar_init(bars + 8 * BD4, 4); mbar_init(bars + 8 * BD1A, 4);
        mbar_init(bars + 8 * BX, 1);
        mbar_expect_tx(bars + 8 * BX, 40960);
        fence_mbar_init();
    }
    __syncthreads();
    cluster_sync();

    if (wg == 2) {
        reg_dealloc<40>();
        if (threadIdx.x == 256) {
            {
                uint32_t st = 0, ph = 1;
                bool first = true;
#pragma unroll 1
                for (int hp = 0; hp < 2; hp++) {
                    const int head0 = j * 4 + hp * 2;
                    if (first) {
#pragma unroll 1
                        for (int s = 1; s < 6; s++) {
                            if (s == 3) continue;
                            const int kb = s < 3 ? s - 1 : s - 2;
                            mbar_expect_tx(bars + 8 * (B1F + s), P1_STAGE);
#pragma unroll 1
                            for (int c = 0; c < 2; c++) {
                                const int chunk = 2 * (int)rank + c;
                                tma_load_2d_mc(base + s * P1_STAGE + chunk * 8192, &tm.wq, head0 * 128 + chunk * 64, kb * 64, bars + 8 * (B1F + s), 3);
                            }
                        }
                        flag_wait(F_H + mt, (epoch + 1) * 8);
                        fence_proxy_async_all();
#pragma unroll 1
                        for (int s = 0; s < 6; s += 3) {
                            mbar_expect_tx(bars + 8 * (B1F + s), P1_STAGE);
                            tma_load_2d(base + s * P1_STAGE, &tm.h, (s / 3 * 2) * 64, m0, bars + 8 * (B1F + s));
                            tma_load_2d(base + s * P1_STAGE + 16384, &tm.h, (s / 3 * 2 + 1) * 64, m0, bars + 8 * (B1F + s));
                        }
                        ph = 0;
                    }
#pragma unroll 1
                    for (int kk2 = first ? 2 : 0; kk2 < 5; kk2++) {
                        mbar_wait(bars + 8 * (B1E + st), ph);
                        mbar_expect_tx(bars + 8 * (B1F + st), P1_STAGE);
                        tma_load_2d(base + st * P1_STAGE, &tm.h, (2 * kk2) * 64, m0, bars + 8 * (B1F + st));
                        tma_load_2d(base + st * P1_STAGE + 16384, &tm.h, (2 * kk2 + 1) * 64, m0, bars + 8 * (B1F + st));
                        if (++st == 6) { st = 0; ph ^= 1; }
#pragma unroll 1
                        for (int u = 0; u < 2; u++) {
                            mbar_wait(bars + 8 * (B1E + st), ph);
                            mbar_expect_tx(bars + 8 * (B1F + st), P1_STAGE);
                            const int kb = 2 * kk2 + u;
#pragma unroll 1
                            for (int c = 0; c < 2; c++) {
                                const int chunk = 2 * (int)rank + c;
                                tma_load_2d_mc(base + st * P1_STAGE + chunk * 8192, &tm.wq, head0 * 128 + chunk * 64, kb * 64, bars + 8 * (B1F + st), 3);
                            }
                            if (++st == 6) { st = 0; ph ^= 1; }
                        }
                    }
                    first = false;
#pragma unroll 1
                    for (int t = 0; t <= 8; t++) {
                        if (t < 8) {
                            mbar_wait(bars + 8 * (B1E + st), ph);
                            mbar_expect_tx(bars + 8 * (B1F + st), P1_STAGE);
                            const int row = (head0 + (t >> 2)) * S_KV + (S_KV - WIN) + (t & 3) * 128;
                            tma_load_2d_mc(base + st * P1_STAGE + rank * 16384, &tm.k, rank * 64, row, bars + 8 * (B1F + st), 3);
                            if (++st == 6) { st = 0; ph ^= 1; }
                        }
                        if (t > 0) {
                            mbar_wait(bars + 8 * (B1E + st), ph);
                            mbar_expect_tx(bars + 8 * (B1F + st), P1_STAGE);
                            const int tv = t - 1;
                            const int row = (head0 + (tv >> 2)) * S_KV + (S_KV - WIN) + (tv & 3) * 128;
                            tma_load_2d_mc(base + st * P1_STAGE + rank * 16384, &tm.v, rank * 64, row, bars + 8 * (B1F + st), 3);
                            if (++st == 6) { st = 0; ph ^= 1; }
                        }
                    }
                }
            }
            {
                const int kq = j >> 1, n0 = (j & 1) * 320;
                uint32_t st = 0, ph = 1;
#pragma unroll 1
                for (int i = 0; i < 16; i++) {
                    if (i == 0) mbar_wait(bars + 8 * BD1A, 0);
                    if (i == 3) mbar_wait(bars + 8 * BD1, 0);
                    if (i == 8) { flag_wait(F_O + mt * 4 + kq, (epoch + 1) * 4); fence_proxy_async_all(); }
                    mbar_wait(bars + 8 * (B2E + st), ph);
                    mbar_expect_tx(bars + 8 * (B2F + st), P2_STAGE);
                    const uint32_t dst = base + st * P2_STAGE;
                    const int k0 = kq * 1024 + ((i + (j & 1) * 8) & 15) * 64;
                    tma_load_2d(dst, &tm.o_a, k0, m0, bars + 8 * (B2F + st));
#pragma unroll 1
                    for (int c = 0; c < 5; c++)
                        if (((c + i) & 1) == (int)rank) tma_load_2d_mc(dst + 16384 + c * 8192, &tm.wo, n0 + c * 64, k0, bars + 8 * (B2F + st), 3);
                    if (++st == 4) { st = 0; ph ^= 1; }
                }
            }
            {
                const int f0 = j * 216;
                const CUtensorMap* t128 = rank == 0 ? &tm.g128 : &tm.u128;
                const CUtensorMap* t64 = rank == 0 ? &tm.g64 : &tm.u64;
                mbar_wait(bars + 8 * BD2, 0);
#pragma unroll 1
                for (int i = 0; i < 4; i++) {
                    mbar_expect_tx(bars + 8 * (B4F + i), 16384 + 32768);
                    const uint32_t dst = base + i * P4_STAGE;
                    tma_load_2d_mc(dst + 16384 + rank * 16384, t128, f0, i * 64, bars + 8 * (B4F + i), 3);
                    tma_load_2d_mc(dst + 16384 + rank * 16384 + 8192, t128, f0 + 64, i * 64, bars + 8 * (B4F + i), 3);
                }
                flag_wait(F_H2 + mt, (epoch + 1) * 8);
                fence_proxy_async_all();
#pragma unroll 1
                for (int i = 0; i < 4; i++) tma_load_2d(base + i * P4_STAGE, &tm.h2, i * 64, m0, bars + 8 * (B4F + i));
                uint32_t st = 0, ph = 0;
#pragma unroll 1
                for (int i = 4; i < 20; i++) {
                    const int kb = i < 10 ? i : i - 10;
                    mbar_wait(bars + 8 * (B4E + st), ph);
                    const uint32_t dst = base + st * P4_STAGE;
                    if (i < 10) {
                        mbar_expect_tx(bars + 8 * (B4F + st), 16384 + 32768);
                        tma_load_2d(dst, &tm.h2, kb * 64, m0, bars + 8 * (B4F + st));
                        tma_load_2d_mc(dst + 16384 + rank * 16384, t128, f0, kb * 64, bars + 8 * (B4F + st), 3);
                        tma_load_2d_mc(dst + 16384 + rank * 16384 + 8192, t128, f0 + 64, kb * 64, bars + 8 * (B4F + st), 3);
                    } else {
                        mbar_expect_tx(bars + 8 * (B4F + st), 16384 + 24576);
                        tma_load_2d(dst, &tm.h2, kb * 64, m0, bars + 8 * (B4F + st));
#pragma unroll 1
                        for (int c = 0; c < 3; c++)
                            tma_load_2d_mc(dst + 16384 + rank * 12288 + c * 4096, t64, f0 + 128 + c * 32, kb * 64, bars + 8 * (B4F + st), 3);
                    }
                    if (++st == 4) { st = 0; ph ^= 1; }
                }
            }
            {
                const int mt5 = p * 2 + (j >> 2), n0 = (j & 3) * 160;
                const int kb0 = rank == 0 ? 0 : 14, nkb = rank == 0 ? 14 : 13;
                mbar_wait(bars + 8 * BD4, 0);
#pragma unroll 1
                for (int i = 0; i < 4; i++) {
                    mbar_expect_tx(bars + 8 * (B5F + i), P5_STAGE);
#pragma unroll 1
                    for (int c = 0; c < 3; c++)
                        tma_load_2d(base + i * P5_STAGE + 16384 + c * 8192, &tm.wd, n0 + c * 64, (kb0 + i) * 64, bars + 8 * (B5F + i));
                }
                flag_wait(F_A + mt5, (epoch + 1) * 16);
                fence_proxy_async_all();
#pragma unroll 1
                for (int i = 0; i < 4; i++) tma_load_2d(base + i * P5_STAGE, &tm.act_a, (kb0 + i) * 64, mt5 * 128, bars + 8 * (B5F + i));
                uint32_t st = 0, ph = 0;
#pragma unroll 1
                for (int i = 4; i < nkb; i++) {
                    mbar_wait(bars + 8 * (B5E + st), ph);
                    mbar_expect_tx(bars + 8 * (B5F + st), P5_STAGE);
                    const uint32_t dst = base + st * P5_STAGE;
                    const int k0 = (kb0 + i) * 64;
                    tma_load_2d(dst, &tm.act_a, k0, mt5 * 128, bars + 8 * (B5F + st));
#pragma unroll 1
                    for (int c = 0; c < 3; c++) tma_load_2d(dst + 16384 + c * 8192, &tm.wd, n0 + c * 64, k0, bars + 8 * (B5F + st));
                    if (++st == 4) { st = 0; ph ^= 1; }
                }
            }
        }
        else if (threadIdx.x == 288) {
            mbar_wait(bars + 8 * B1F, 0);
            const char* pw[4] = {(const char*)wo_p, (const char*)wg_p, (const char*)wu_p, (const char*)wd_p};
#pragma unroll 1
            for (int t = 0; t < 4; t++) {
                const uint32_t bytes = t == 0 ? 40960u : 17280u;
                asm volatile("cp.async.bulk.prefetch.L2.global [%0], %1;" ::"l"(pw[t] + (size_t)blockIdx.x * bytes), "r"(bytes) : "memory");
            }
        }
        __syncwarp();
        asm volatile("barrier.cluster.arrive.relaxed.aligned; // producer\n barrier.cluster.wait.aligned;" ::: "memory");
    } else {
        reg_alloc<232>();
        const int tid = threadIdx.x & 127;
        const int warp = tid >> 5, lane = tid & 31;
        const int cw = threadIdx.x >> 5;
        const uint32_t mystage = base + SM_STAGING + wg * 16384;
        auto arrive_both = [&](uint32_t bar) {
            if (tid == 0) mbar_arrive_cluster(bar, 0);
            if (tid == 32) mbar_arrive_cluster(bar, 1);
        };
        TS(0, 0);
        {
            uint2 xr[2][5];
            uint4 w[10];
            unsigned short cr[10];
            const int mb = blockIdx.x < 120 ? blockIdx.x : 0;
#pragma unroll
            for (int i = 0; i < 10; i++) cr[i] = __ldg(reinterpret_cast<const unsigned short*>(cvec) + cw * 80 + i * 8 + (lane >> 2));
#pragma unroll
            for (int i = 0; i < 10; i++)
                w[i] = __ldg(reinterpret_cast<const uint4*>(w_mod + (size_t)(cw * 80 + i * 8 + (lane >> 2)) * (6 * D_MODEL) + mb * 32 + (lane & 3) * 8));
#pragma unroll
            for (int rr = 0; rr < 2; rr++)
#pragma unroll
                for (int i = 0; i < 5; i++)
                    xr[rr][i] = __ldg(reinterpret_cast<const uint2*>(x + (size_t)(m0 + j * 16 + cw * 2 + rr) * D_MODEL + (lane + 32 * i) * 4));
            if (blockIdx.x < 120) {
                float* red = reinterpret_cast<float*>(smem_raw + (base - smem_u32(smem_raw)) + SM_STAGING);
                float acc[8];
#pragma unroll
                for (int i = 0; i < 8; i++) acc[i] = 0.f;
#pragma unroll
                for (int i = 0; i < 10; i++) {
                    const float s = bf16_round(silu_mul(__uint_as_float((uint32_t)cr[i] << 16), 1.f));
                    acc[0] += s * bf16lo(w[i].x); acc[1] += s * bf16hi(w[i].x);
                    acc[2] += s * bf16lo(w[i].y); acc[3] += s * bf16hi(w[i].y);
                    acc[4] += s * bf16lo(w[i].z); acc[5] += s * bf16hi(w[i].z);
                    acc[6] += s * bf16lo(w[i].w); acc[7] += s * bf16hi(w[i].w);
                }
#pragma unroll
                for (int i = 0; i < 8; i++) {
                    acc[i] += __shfl_xor_sync(0xffffffffu, acc[i], 4);
                    acc[i] += __shfl_xor_sync(0xffffffffu, acc[i], 8);
                    acc[i] += __shfl_xor_sync(0xffffffffu, acc[i], 16);
                }
                if (lane < 4) {
#pragma unroll
                    for (int i = 0; i < 8; i++) red[cw * 32 + lane * 8 + i] = acc[i];
                }
                TS(6, 0);
                bar_sync(5, 256);
                TS(6, 1);
                if (threadIdx.x < 32) {
                    float t = 0.f;
#pragma unroll
                    for (int i = 0; i < 8; i++) t += red[i * 32 + threadIdx.x];
                    t = bf16_round(t);
                    const int chunk = blockIdx.x / 20;
                    if (chunk == 1 || chunk == 4) t = bf16_round(1.f + t);
                    g_mod[blockIdx.x * 32 + threadIdx.x] = t;
                    __syncwarp();
                    TS(6, 2);
                    if (threadIdx.x == 0) flag_signal(blockIdx.x < 40 ? F_MODAB : F_MODALL);
                    TS(6, 3);
                }
            }
            if (threadIdx.x == 0) flag_wait(F_MODAB, (epoch + 1) * 40);
            bar_sync(5, 256);
            TS(0, 1);
            ln_rows(xr, g_mod, g_mod + D_MODEL, g_h + (size_t)(m0 + j * 16 + cw * 2) * D_MODEL, lane);
            TS(6, 4);
            bar_sync(5, 256);
            TS(6, 5);
            if (threadIdx.x == 0) flag_signal(F_H + mt);
        }
        TS(0, 2);
        {
            const float cscale = 0.08838834764831845f * 1.4426950408889634f;
            uint32_t st = 0, ph = 0;
            auto wait_full = [&]() -> uint32_t {
                mbar_wait(bars + 8 * (B1F + st), ph);
                return base + st * P1_STAGE;
            };
            auto release = [&](uint32_t s) { arrive_both(bars + 8 * (B1E + s)); };
            auto advance = [&]() { if (++st == 6) { st = 0; ph ^= 1; } };
            auto turn_wait = [&]() { bar_sync(3 + wg, 256); };
            auto turn_pass = [&]() { bar_arrive(3 + (wg ^ 1), 256); };
            if (wg == 1) bar_arrive(3, 256);

            for (int hp = 0; hp < 2; hp++) {
                const int head0 = j * 4 + hp * 2;
                uint32_t q[8][4];
                {
                    float acc[128];
#pragma unroll
                    for (int i = 0; i < 128; i++) acc[i] = 0.f;
                    for (int kk2 = 0; kk2 < 5; kk2++) {
                        const uint32_t hbuf = wait_full();
                        if (kk2 == 0 && hp == 0) TS(0, 3);
                        const uint32_t sth = st;
                        advance();
#pragma unroll
                        for (int u = 0; u < 2; u++) {
                            const uint32_t wbuf = wait_full();
                            const uint32_t stw = st;
                            advance();
                            wgmma_fence();
#pragma unroll
                            for (int k = 0; k < 4; k++) {
                                uint64_t da = make_desc(hbuf + u * 16384 + wg * 8192 + k * 32, 16, 1024, 1);
                                uint64_t db = make_desc(wbuf + k * 2048, 8192, 1024, 1);
                                wgmma_ss_n256_t1(acc, da, db, 1);
                            }
                            wgmma_commit();
                            wgmma_wait<0>();
                            release(stw);
                        }
                        release(sth);
                    }
                    fence_regs(acc);
                    if (tid == 0) tma_store_wait_read<0>();
                    bar_sync(1 + wg, 128);
#pragma unroll
                    for (int i = 0; i < 8; i++) {
                        q[i][0] = pack_bf16(acc[8 * i + 0], acc[8 * i + 1]);
                        q[i][1] = pack_bf16(acc[8 * i + 2], acc[8 * i + 3]);
                        q[i][2] = pack_bf16(acc[8 * i + 4], acc[8 * i + 5]);
                        q[i][3] = pack_bf16(acc[8 * i + 6], acc[8 * i + 7]);
                        uint32_t b0 = pack_bf16(acc[64 + 8 * i + 0], acc[64 + 8 * i + 1]);
                        uint32_t b1 = pack_bf16(acc[64 + 8 * i + 2], acc[64 + 8 * i + 3]);
                        uint32_t b2 = pack_bf16(acc[64 + 8 * i + 4], acc[64 + 8 * i + 5]);
                        uint32_t b3 = pack_bf16(acc[64 + 8 * i + 6], acc[64 + 8 * i + 7]);
                        asm volatile("st.shared.v4.b32 [%0], {%1, %2, %3, %4};" ::"r"(mystage + (i * 128 + tid) * 16), "r"(b0), "r"(b1),
                                     "r"(b2), "r"(b3) : "memory");
                    }
                }
                float o[64], s[64], e[64];
                uint32_t pp[8][4];
                float mm0, mm1, l0, l1, a0, a1, lo0, lo1;
#pragma unroll
                for (int i = 0; i < 64; i++) { o[i] = 0.f; }

                auto issue_s = [&]() -> uint32_t {
                    const uint32_t kbuf = wait_full();
                    const uint32_t stk = st;
                    advance();
                    wgmma_fence();
#pragma unroll
                    for (int k = 0; k < 8; k++) {
                        uint64_t db = make_desc(kbuf + (k >> 2) * 16384 + (k & 3) * 32, 16, 1024, 1);
                        if (k == 0) wgmma_rs_n128_t0_z(s, q[k], db);
                        else wgmma_rs_n128_t0(s, q[k], db, 1);
                    }
                    wgmma_commit();
                    return stk;
                };
                auto issue_pv = [&](bool fresh) -> uint32_t {
                    const uint32_t vbuf = wait_full();
                    const uint32_t stv = st;
                    advance();
                    wgmma_fence();
#pragma unroll
                    for (int k = 0; k < 8; k++) {
                        uint64_t db = make_desc(vbuf + k * 2048, 16384, 1024, 1);
                        wgmma_rs_n128_t1(o, pp[k], db, (!fresh) || k != 0);
                    }
                    wgmma_commit();
                    return stv;
                };
                auto softmax = [&](bool first) {
                    float mx0 = fmaxf(s[0], s[1]), mx1 = fmaxf(s[2], s[3]);
#pragma unroll
                    for (int jj = 1; jj < 16; jj++) {
                        mx0 = fmaxf(mx0, fmaxf(s[4 * jj], s[4 * jj + 1]));
                        mx1 = fmaxf(mx1, fmaxf(s[4 * jj + 2], s[4 * jj + 3]));
                    }
                    mx0 = fmaxf(mx0, __shfl_xor_sync(0xffffffffu, mx0, 1));
                    mx0 = fmaxf(mx0, __shfl_xor_sync(0xffffffffu, mx0, 2));
                    mx1 = fmaxf(mx1, __shfl_xor_sync(0xffffffffu, mx1, 1));
                    mx1 = fmaxf(mx1, __shfl_xor_sync(0xffffffffu, mx1, 2));
                    if (first) {
                        lo0 = l0; lo1 = l1;
                        mm0 = mx0; mm1 = mx1; l0 = 0.f; l1 = 0.f; a0 = 0.f; a1 = 0.f;
                    } else {
                        float mn0 = fmaxf(mm0, mx0), mn1 = fmaxf(mm1, mx1);
                        a0 = ex2((mm0 - mn0) * cscale); a1 = ex2((mm1 - mn1) * cscale);
                        mm0 = mn0; mm1 = mn1;
                    }
                    const float mc0 = mm0 * cscale, mc1 = mm1 * cscale;
                    float r0 = 0.f, r1 = 0.f;
#pragma unroll
                    for (int jj = 0; jj < 16; jj++) {
                        e[4 * jj] = ex2(fmaf(s[4 * jj], cscale, -mc0));
                        e[4 * jj + 1] = ex2(fmaf(s[4 * jj + 1], cscale, -mc0));
                        e[4 * jj + 2] = ex2(fmaf(s[4 * jj + 2], cscale, -mc1));
                        e[4 * jj + 3] = ex2(fmaf(s[4 * jj + 3], cscale, -mc1));
                        r0 += e[4 * jj] + e[4 * jj + 1];
                        r1 += e[4 * jj + 2] + e[4 * jj + 3];
                    }
                    l0 = l0 * a0 + r0; l1 = l1 * a1 + r1;
                };
                auto convert_p = [&]() {
#pragma unroll
                    for (int i = 0; i < 8; i++) {
                        pp[i][0] = pack_bf16(e[8 * i + 0], e[8 * i + 1]);
                        pp[i][1] = pack_bf16(e[8 * i + 2], e[8 * i + 3]);
                        pp[i][2] = pack_bf16(e[8 * i + 4], e[8 * i + 5]);
                        pp[i][3] = pack_bf16(e[8 * i + 6], e[8 * i + 7]);
                    }
                };
                auto store_o = [&](float ls0, float ls1, int head, bool last) {
                    float s0 = ls0 + __shfl_xor_sync(0xffffffffu, ls0, 1); s0 += __shfl_xor_sync(0xffffffffu, s0, 2);
                    float s1 = ls1 + __shfl_xor_sync(0xffffffffu, ls1, 1); s1 += __shfl_xor_sync(0xffffffffu, s1, 2);
                    const float i0 = 1.f / s0, i1 = 1.f / s1;
                    if (tid == 0) {
                        tma_store_wait<0>();
                        if (last) {
                            mbar_arrive_cluster(bars + 8 * BD1A, 0);
                            mbar_arrive_cluster(bars + 8 * BD1A, 1);
                        }
                    }
                    bar_sync(1 + wg, 128);
#pragma unroll
                    for (int jj = 0; jj < 16; jj += 2) {
                        const int mi = lane >> 3;
                        const int row = warp * 16 + (mi & 1) * 8 + (lane & 7);
                        const int grp = jj + (mi >> 1);
                        const uint32_t addr = mystage + (grp >> 3) * 8192 + row * 128 + (((grp & 7) ^ (row & 7)) << 4);
                        stmatrix_x4(addr, pack_bf16(o[4 * jj] * i0, o[4 * jj + 1] * i0), pack_bf16(o[4 * jj + 2] * i1, o[4 * jj + 3] * i1),
                                    pack_bf16(o[4 * jj + 4] * i0, o[4 * jj + 5] * i0), pack_bf16(o[4 * jj + 6] * i1, o[4 * jj + 7] * i1));
                    }
                    fence_proxy_async();
                    bar_sync(1 + wg, 128);
                    if (tid == 0) {
                        tma_store_2d(&tm.o_st, mystage, head * 128, m0 + wg * 64);
                        tma_store_2d(&tm.o_st, mystage + 8192, head * 128 + 64, m0 + wg * 64);
                        tma_store_commit();
                        if (last) {
                            tma_store_wait<0>();
                            mbar_arrive_cluster(bars + 8 * BD1, 0);
                            mbar_arrive_cluster(bars + 8 * BD1, 1);
                            flag_signal_relaxed(F_O + mt * 4 + (j >> 1));
                        }
                    }
                };

                l0 = 0.f; l1 = 0.f;
                {
                    turn_wait();
                    uint32_t stk = issue_s();
                    turn_pass();
                    wgmma_wait<0>();
                    fence_regs(s);
                    release(stk);
                    softmax(true);
                    convert_p();
                }
#pragma unroll 1
                for (int t = 1; t < 8; t++) {
                    const bool first = (t == 4);
                    if (t == 4) {
#pragma unroll
                        for (int i = 0; i < 8; i++) {
                            asm volatile("ld.shared.v4.b32 {%0, %1, %2, %3}, [%4];" : "=r"(q[i][0]), "=r"(q[i][1]), "=r"(q[i][2]), "=r"(q[i][3])
                                         : "r"(mystage + (i * 128 + tid) * 16) : "memory");
                        }
                    }
                    turn_wait();
                    uint32_t stk = issue_s();
                    uint32_t stv = issue_pv(t == 1 || t == 5);
                    turn_pass();
                    wgmma_wait<1>();
                    fence_regs(s);
                    release(stk);
                    softmax(first);
                    asm volatile("{\n.reg .pred p;\nsetp.lt.f32 p, %0, 0fBF800000;\n@p st.shared.f32 [%1], %0;\n}\n" ::"f"(l0 + l1), "r"(mystage) : "memory");
                    wgmma_wait<0>();
                    fence_regs(o);
                    release(stv);
                    if (first) {
                        store_o(lo0, lo1, head0, false);
                    } else {
#pragma unroll
                        for (int jj = 0; jj < 16; jj++) {
                            o[4 * jj] *= a0; o[4 * jj + 1] *= a0; o[4 * jj + 2] *= a1; o[4 * jj + 3] *= a1;
                        }
                    }
                    convert_p();
                }
                {
                    turn_wait();
                    uint32_t stv = issue_pv(false);
                    turn_pass();
                    wgmma_wait<0>();
                    fence_regs(o);
                    release(stv);
                    store_o(l0, l1, head0 + 1, hp == 1);
                }
            }
        }
        TS(0, 4);
        {
            const int kq = j >> 1, n0 = (j & 1) * 320;
            float acc0[96], acc1[64];
#pragma unroll
            for (int i = 0; i < 96; i++) acc0[i] = 0.f;
#pragma unroll
            for (int i = 0; i < 64; i++) acc1[i] = 0.f;
            uint32_t st = 0, ph = 0, prev = 0;
            for (int i = 0; i < 16; i++) {
                mbar_wait(bars + 8 * (B2F + st), ph);
                if (i == 0) TS(0, 5);
                const uint32_t buf = base + st * P2_STAGE;
                wgmma_fence();
#pragma unroll
                for (int k = 0; k < 4; k++) {
                    uint64_t da = make_desc(buf + wg * 8192 + k * 32, 16, 1024, 1);
                    wgmma_ss_n192_t1(acc0, da, make_desc(buf + 16384 + k * 2048, 8192, 1024, 1), 1);
                    wgmma_ss_n128_t1(acc1, da, make_desc(buf + 16384 + 3 * 8192 + k * 2048, 8192, 1024, 1), 1);
                }
                wgmma_commit();
                if (i > 0) { wgmma_wait<1>(); arrive_both(bars + 8 * (B2E + prev)); }
                prev = st;
                if (++st == 4) { st = 0; ph ^= 1; }
            }
            wgmma_wait<0>();
            fence_regs(acc0); fence_regs(acc1);
            TS(0, 6);
            bar_sync(5, 256);
            TS(4, 0);
            const uint32_t stg = base + wg * 40960;
            const int mi = lane >> 3;
            const int row = warp * 16 + (mi & 1) * 8 + (lane & 7);
#pragma unroll
            for (int jj = 0; jj < 24; jj += 2) {
                const int grp = jj + (mi >> 1);
                stmatrix_x4(stg + (grp >> 3) * 8192 + row * 128 + (((grp & 7) ^ (row & 7)) << 4),
                            pack_bf16(acc0[4 * jj], acc0[4 * jj + 1]), pack_bf16(acc0[4 * jj + 2], acc0[4 * jj + 3]),
                            pack_bf16(acc0[4 * jj + 4], acc0[4 * jj + 5]), pack_bf16(acc0[4 * jj + 6], acc0[4 * jj + 7]));
            }
#pragma unroll
            for (int jj = 0; jj < 16; jj += 2) {
                const int grp = jj + (mi >> 1);
                stmatrix_x4(stg + (3 + (grp >> 3)) * 8192 + row * 128 + (((grp & 7) ^ (row & 7)) << 4),
                            pack_bf16(acc1[4 * jj], acc1[4 * jj + 1]), pack_bf16(acc1[4 * jj + 2], acc1[4 * jj + 3]),
                            pack_bf16(acc1[4 * jj + 4], acc1[4 * jj + 5]), pack_bf16(acc1[4 * jj + 6], acc1[4 * jj + 7]));
            }
            TS(4, 1);
            fence_proxy_async();
            bar_sync(1 + wg, 128);
            TS(4, 2);
            if (tid == 0) {
#pragma unroll
                for (int c = 0; c < 5; c++) tma_store_2d(&tm.part_st, stg + c * 8192, n0 + c * 64, kq * S_LEN + m0 + wg * 64);
                tma_store_commit();
                TS(4, 3);
                tma_store_wait<0>();
                TS(4, 4);
                mbar_arrive_cluster(bars + 8 * BD2, 0);
                mbar_arrive_cluster(bars + 8 * BD2, 1);
                flag_signal_relaxed(F_P + mt);
            }
        }
        TS(0, 7);
        {
            uint2 xr[2][5];
#pragma unroll
            for (int rr = 0; rr < 2; rr++)
#pragma unroll
                for (int i = 0; i < 5; i++)
                    xr[rr][i] = __ldg(reinterpret_cast<const uint2*>(x + (size_t)(m0 + j * 16 + cw * 2 + rr) * D_MODEL + (lane + 32 * i) * 4));
            if (threadIdx.x == 0) { flag_wait(F_MODALL, (epoch + 1) * 80); flag_wait(F_P + mt, (epoch + 1) * 16); }
            bar_sync(5, 256);
            TS(0, 8);
            uint2 pr[2][4][5];
            float4 gv[5];
#pragma unroll
            for (int rr = 0; rr < 2; rr++)
#pragma unroll
                for (int s = 0; s < 4; s++)
#pragma unroll
                    for (int i = 0; i < 5; i++)
                        pr[rr][s][i] = ldcg_u2(g_part + ((size_t)s * S_LEN + m0 + j * 16 + cw * 2 + rr) * D_MODEL + (lane + 32 * i) * 4);
#pragma unroll
            for (int i = 0; i < 5; i++) gv[i] = __ldcg(reinterpret_cast<const float4*>(g_mod + 2 * D_MODEL + (lane + 32 * i) * 4));
#pragma unroll
            for (int rr = 0; rr < 2; rr++) {
#pragma unroll
                for (int i = 0; i < 5; i++) {
                    float a0 = (bf16lo(pr[rr][0][i].x) + bf16lo(pr[rr][1][i].x)) + (bf16lo(pr[rr][2][i].x) + bf16lo(pr[rr][3][i].x));
                    float a1 = (bf16hi(pr[rr][0][i].x) + bf16hi(pr[rr][1][i].x)) + (bf16hi(pr[rr][2][i].x) + bf16hi(pr[rr][3][i].x));
                    float a2 = (bf16lo(pr[rr][0][i].y) + bf16lo(pr[rr][1][i].y)) + (bf16lo(pr[rr][2][i].y) + bf16lo(pr[rr][3][i].y));
                    float a3 = (bf16hi(pr[rr][0][i].y) + bf16hi(pr[rr][1][i].y)) + (bf16hi(pr[rr][2][i].y) + bf16hi(pr[rr][3][i].y));
                    xr[rr][i].x = pack_bf16(bf16lo(xr[rr][i].x) + gv[i].x * a0, bf16hi(xr[rr][i].x) + gv[i].y * a1);
                    xr[rr][i].y = pack_bf16(bf16lo(xr[rr][i].y) + gv[i].z * a2, bf16hi(xr[rr][i].y) + gv[i].w * a3);
                    *reinterpret_cast<uint2*>(g_x1 + (size_t)(m0 + j * 16 + cw * 2 + rr) * D_MODEL + (lane + 32 * i) * 4) = xr[rr][i];
                }
            }
            TS(5, 0);
            ln_rows(xr, g_mod + 3 * D_MODEL, g_mod + 4 * D_MODEL, g_h2 + (size_t)(m0 + j * 16 + cw * 2) * D_MODEL, lane);
            TS(5, 1);
            bar_sync(5, 256);
            TS(5, 2);
            if (threadIdx.x == 0) flag_signal(F_H2 + mt);
        }
        TS(0, 9);
        {
            const int f0 = j * 216;
            uint32_t st = 0, ph = 0, prev = 0;
            {
                float acc[128];
#pragma unroll
                for (int i = 0; i < 128; i++) acc[i] = 0.f;
                for (int i = 0; i < 10; i++) {
                    mbar_wait(bars + 8 * (B4F + st), ph);
                    if (i == 0) TS(0, 10);
                    const uint32_t buf = base + st * P4_STAGE;
                    wgmma_fence();
#pragma unroll
                    for (int k = 0; k < 4; k++) {
                        uint64_t da = make_desc(buf + wg * 8192 + k * 32, 16, 1024, 1);
                        uint64_t db = make_desc(buf + 16384 + k * 2048, 8192, 1024, 1);
                        wgmma_ss_n256_t1(acc, da, db, 1);
                    }
                    wgmma_commit();
                    if (i > 0) { wgmma_wait<1>(); arrive_both(bars + 8 * (B4E + prev)); }
                    prev = st;
                    if (++st == 4) { st = 0; ph ^= 1; }
                }
                wgmma_wait<0>();
                arrive_both(bars + 8 * (B4E + prev));
                fence_regs(acc);
                TS(2, 0);
#pragma unroll
                for (int jj = 0; jj < 16; jj += 2) {
                    const int mi = lane >> 3;
                    const int row = warp * 16 + (mi & 1) * 8 + (lane & 7);
                    const int grp = jj + (mi >> 1);
                    const uint32_t addr = mystage + (grp >> 3) * 8192 + row * 128 + (((grp & 7) ^ (row & 7)) << 4);
                    stmatrix_x4(addr, pack_bf16(silu_mul(acc[4 * jj], acc[64 + 4 * jj]), silu_mul(acc[4 * jj + 1], acc[64 + 4 * jj + 1])),
                                pack_bf16(silu_mul(acc[4 * jj + 2], acc[64 + 4 * jj + 2]), silu_mul(acc[4 * jj + 3], acc[64 + 4 * jj + 3])),
                                pack_bf16(silu_mul(acc[4 * jj + 4], acc[64 + 4 * jj + 4]), silu_mul(acc[4 * jj + 5], acc[64 + 4 * jj + 5])),
                                pack_bf16(silu_mul(acc[4 * jj + 6], acc[64 + 4 * jj + 6]), silu_mul(acc[4 * jj + 7], acc[64 + 4 * jj + 7])));
                }
                fence_proxy_async();
                bar_sync(1 + wg, 128);
                TS(2, 1);
                if (tid == 0) {
                    tma_store_2d(&tm.act_st64, mystage, f0, m0 + wg * 64);
                    tma_store_2d(&tm.act_st64, mystage + 8192, f0 + 64, m0 + wg * 64);
                    tma_store_commit();
                }
                TS(2, 2);
            }
            {
                float acc[92];
#pragma unroll
                for (int i = 0; i < 92; i++) acc[i] = 0.f;
                for (int i = 0; i < 10; i++) {
                    mbar_wait(bars + 8 * (B4F + st), ph);
                    const uint32_t buf = base + st * P4_STAGE;
                    wgmma_fence();
#pragma unroll
                    for (int k = 0; k < 4; k++) {
                        uint64_t da = make_desc(buf + wg * 8192 + k * 32, 16, 1024, 1);
                        uint64_t db = make_desc(buf + 16384 + k * 1024, 4096, 512, 2);
                        wgmma_ss_n184_t1(acc, da, db, 1);
                    }
                    wgmma_commit();
                    if (i > 0) { wgmma_wait<1>(); arrive_both(bars + 8 * (B4E + prev)); }
                    prev = st;
                    if (++st == 4) { st = 0; ph ^= 1; }
                }
                wgmma_wait<0>();
                fence_regs(acc);
                TS(0, 11);
                if (tid == 0) tma_store_wait_read<0>();
                bar_sync(1 + wg, 128);
                TS(2, 3);
#pragma unroll
                for (int jj = 0; jj < 8; jj += 2) {
                    const int mi = lane >> 3;
                    const int row = warp * 16 + (mi & 1) * 8 + (lane & 7);
                    const int grp = jj + (mi >> 1);
                    const uint32_t addr = mystage + row * 128 + ((grp ^ (row & 7)) << 4);
                    stmatrix_x4(addr, pack_bf16(silu_mul(acc[4 * jj], acc[48 + 4 * jj]), silu_mul(acc[4 * jj + 1], acc[48 + 4 * jj + 1])),
                                pack_bf16(silu_mul(acc[4 * jj + 2], acc[48 + 4 * jj + 2]), silu_mul(acc[4 * jj + 3], acc[48 + 4 * jj + 3])),
                                pack_bf16(silu_mul(acc[4 * jj + 4], acc[48 + 4 * jj + 4]), silu_mul(acc[4 * jj + 5], acc[48 + 4 * jj + 5])),
                                pack_bf16(silu_mul(acc[4 * jj + 6], acc[48 + 4 * jj + 6]), silu_mul(acc[4 * jj + 7], acc[48 + 4 * jj + 7])));
                }
                {
                    const int mi = lane >> 3;
                    const int row = warp * 16 + (mi & 1) * 8 + (lane & 7);
                    const uint32_t addr = mystage + 8192 + row * 48 + (mi >> 1) * 16;
                    stmatrix_x4(addr, pack_bf16(silu_mul(acc[32], acc[80]), silu_mul(acc[33], acc[81])),
                                pack_bf16(silu_mul(acc[34], acc[82]), silu_mul(acc[35], acc[83])),
                                pack_bf16(silu_mul(acc[36], acc[84]), silu_mul(acc[37], acc[85])),
                                pack_bf16(silu_mul(acc[38], acc[86]), silu_mul(acc[39], acc[87])));
                    const uint32_t addr2 = mystage + 8192 + (warp * 16 + ((lane >> 3) & 1) * 8 + (lane & 7)) * 48 + 32;
                    asm volatile("stmatrix.sync.aligned.m8n8.x2.shared.b16 [%0], {%1, %2};" ::"r"(addr2),
                                 "r"(pack_bf16(silu_mul(acc[40], acc[88]), silu_mul(acc[41], acc[89]))),
                                 "r"(pack_bf16(silu_mul(acc[42], acc[90]), silu_mul(acc[43], acc[91]))) : "memory");
                }
                fence_proxy_async();
                bar_sync(1 + wg, 128);
                TS(2, 4);
                if (tid == 0) {
                    tma_store_2d(&tm.act_st64, mystage, f0 + 128, m0 + wg * 64);
                    tma_store_2d(&tm.act_st24, mystage + 8192, f0 + 192, m0 + wg * 64);
                    tma_store_commit();
                    TS(2, 5);
                    tma_store_wait<0>();
                    TS(2, 6);
                    mbar_arrive_cluster(bars + 8 * BD4, 0);
                    mbar_arrive_cluster(bars + 8 * BD4, 1);
                    TS(2, 7);
                    flag_signal_relaxed(F_A + mt);
                    TS(2, 8);
                }
            }
        }
        TS(0, 12);
        {
            const int m5 = (p * 2 + (j >> 2)) * 128, n0 = (j & 3) * 160;
            const int nkb = rank == 0 ? 14 : 13;
            float acc[80];
#pragma unroll
            for (int i = 0; i < 80; i++) acc[i] = 0.f;
            uint32_t st = 0, ph = 0, prev = 0;
            const int cbase = n0 + (int)rank * 80;
            for (int i = 0; i < nkb; i++) {
                mbar_wait(bars + 8 * (B5F + st), ph);
                if (i == 0) TS(0, 13);
                const uint32_t buf = base + st * P5_STAGE;
                wgmma_fence();
#pragma unroll
                for (int k = 0; k < 4; k++) {
                    uint64_t da = make_desc(buf + wg * 8192 + k * 32, 16, 1024, 1);
                    wgmma_ss_n160_t1(acc, da, make_desc(buf + 16384 + k * 2048, 8192, 1024, 1), 1);
                }
                wgmma_commit();
                if (i > 0) {
                    wgmma_wait<1>();
                    if (tid == 0) mbar_arrive(bars + 8 * (B5E + prev));
                }
                prev = st;
                if (++st == 4) { st = 0; ph ^= 1; }
            }
            uint4 xv[5];
            float2 gbv[10];
#pragma unroll
            for (int it = 0; it < 5; it++) {
                const int idx = it * 256 + (int)threadIdx.x;
                const int row = idx / 10, ch = idx - row * 10;
                xv[it] = __ldcg(reinterpret_cast<const uint4*>(g_x1 + (size_t)(m5 + row) * D_MODEL + cbase + ch * 8));
            }
#pragma unroll
            for (int jj = 0; jj < 10; jj++) gbv[jj] = __ldcg(reinterpret_cast<const float2*>(g_mod + 5 * D_MODEL + cbase + jj * 8 + (lane & 3) * 2));
            wgmma_wait<0>();
            fence_regs(acc);
            TS(0, 14);
            constexpr uint32_t XBUF = 4 * P5_STAGE;
            {
                const uint32_t dst = mapa(base + XBUF, rank ^ 1) + wg * 20480 + tid * 16;
                const uint32_t rbar = mapa(bars + 8 * BX, rank ^ 1);
                if (rank == 0) {
#pragma unroll
                    for (int i = 0; i < 10; i++)
                        asm volatile("st.async.shared::cluster.mbarrier::complete_tx::bytes.v4.f32 [%0], {%1, %2, %3, %4}, [%5];" ::"r"(dst + i * 2048),
                                     "f"(acc[40 + 4 * i]), "f"(acc[40 + 4 * i + 1]), "f"(acc[40 + 4 * i + 2]), "f"(acc[40 + 4 * i + 3]), "r"(rbar) : "memory");
                } else {
#pragma unroll
                    for (int i = 0; i < 10; i++)
                        asm volatile("st.async.shared::cluster.mbarrier::complete_tx::bytes.v4.f32 [%0], {%1, %2, %3, %4}, [%5];" ::"r"(dst + i * 2048),
                                     "f"(acc[4 * i]), "f"(acc[4 * i + 1]), "f"(acc[4 * i + 2]), "f"(acc[4 * i + 3]), "r"(rbar) : "memory");
                }
            }
            mbar_wait(bars + 8 * BX, 0);
            {
                const uint32_t tile = base + XBUF + 40960;
#pragma unroll
                for (int jj = 0; jj < 10; jj += 2) {
                    float4 o0, o1;
                    asm volatile("ld.shared.v4.f32 {%0, %1, %2, %3}, [%4];" : "=f"(o0.x), "=f"(o0.y), "=f"(o0.z), "=f"(o0.w) : "r"(base + XBUF + wg * 20480 + tid * 16 + jj * 2048));
                    asm volatile("ld.shared.v4.f32 {%0, %1, %2, %3}, [%4];" : "=f"(o1.x), "=f"(o1.y), "=f"(o1.z), "=f"(o1.w) : "r"(base + XBUF + wg * 20480 + tid * 16 + (jj + 1) * 2048));
                    const float2 g0 = gbv[jj], g1 = gbv[jj + 1];
                    float a[8];
#pragma unroll
                    for (int ee = 0; ee < 8; ee++) a[ee] = rank == 0 ? acc[4 * jj + ee] : acc[40 + 4 * jj + ee];
                    const int mi = lane >> 3;
                    const int row = wg * 64 + warp * 16 + (mi & 1) * 8 + (lane & 7);
                    const uint32_t addr = tile + row * 176 + (jj + (mi >> 1)) * 16;
                    stmatrix_x4(addr, pack_bf16(g0.x * bf16_round(a[0] + o0.x), g0.y * bf16_round(a[1] + o0.y)),
                                pack_bf16(g0.x * bf16_round(a[2] + o0.z), g0.y * bf16_round(a[3] + o0.w)),
                                pack_bf16(g1.x * bf16_round(a[4] + o1.x), g1.y * bf16_round(a[5] + o1.y)),
                                pack_bf16(g1.x * bf16_round(a[6] + o1.z), g1.y * bf16_round(a[7] + o1.w)));
                }
                bar_sync(5, 256);
#pragma unroll
                for (int it = 0; it < 5; it++) {
                    const int idx = it * 256 + (int)threadIdx.x;
                    const int row = idx / 10, ch = idx - row * 10;
                    uint4 tv;
                    asm volatile("ld.shared.v4.b32 {%0, %1, %2, %3}, [%4];" : "=r"(tv.x), "=r"(tv.y), "=r"(tv.z), "=r"(tv.w) : "r"(tile + row * 176 + ch * 16));
                    uint4 r;
                    r.x = pack_bf16(bf16lo(xv[it].x) + bf16lo(tv.x), bf16hi(xv[it].x) + bf16hi(tv.x));
                    r.y = pack_bf16(bf16lo(xv[it].y) + bf16lo(tv.y), bf16hi(xv[it].y) + bf16hi(tv.y));
                    r.z = pack_bf16(bf16lo(xv[it].z) + bf16lo(tv.z), bf16hi(xv[it].z) + bf16hi(tv.z));
                    r.w = pack_bf16(bf16lo(xv[it].w) + bf16lo(tv.w), bf16hi(xv[it].w) + bf16hi(tv.w));
                    *reinterpret_cast<uint4*>(out + (size_t)(m5 + row) * D_MODEL + cbase + ch * 8) = r;
                }
            }
            TS(0, 15);
            if (threadIdx.x == 0) {
                const unsigned old = atomicAdd(&g_exit, 1u);
                if (old == (epoch + 1) * 128u - 1u) {
                    asm volatile("st.volatile.global.u32 [%0], %1;" ::"l"(&g_epoch), "r"(epoch + 1) : "memory");
                }
            }
            asm volatile("barrier.cluster.arrive.relaxed.aligned;\n barrier.cluster.wait.aligned;" ::: "memory");
        }
    }
}

typedef CUresult (*PFN_encodeTiled)(CUtensorMap*, CUtensorMapDataType, cuuint32_t, void*, const cuuint64_t*, const cuuint64_t*,
                                    const cuuint32_t*, const cuuint32_t*, CUtensorMapInterleave, CUtensorMapSwizzle,
                                    CUtensorMapL2promotion, CUtensorMapFloatOOBfill);

static PFN_encodeTiled get_encode() {
    static PFN_encodeTiled fn = nullptr;
    if (!fn) {
        void* p = nullptr;
        cudaDriverEntryPointQueryResult qr;
        cudaGetDriverEntryPoint("cuTensorMapEncodeTiled", &p, cudaEnableDefault, &qr);
        fn = (PFN_encodeTiled)p;
    }
    return fn;
}

static CUtensorMap make_map(const void* ptr, uint64_t rows, uint64_t cols, uint32_t box_rows, uint32_t box_cols, CUtensorMapSwizzle swz) {
    CUtensorMap m;
    cuuint64_t dims[2] = {cols, rows};
    cuuint64_t strides[1] = {cols * 2};
    cuuint32_t box[2] = {box_cols, box_rows};
    cuuint32_t es[2] = {1, 1};
    get_encode()(&m, CU_TENSOR_MAP_DATA_TYPE_BFLOAT16, 2, const_cast<void*>(ptr), dims, strides, box, es, CU_TENSOR_MAP_INTERLEAVE_NONE,
                 swz, CU_TENSOR_MAP_L2_PROMOTION_L2_256B, CU_TENSOR_MAP_FLOAT_OOB_FILL_NONE);
    return m;
}

extern "C" void kernel_launch(void* const* d_in, const int* in_sizes, int n_in, void* d_out, int out_size) {
    (void)in_sizes; (void)n_in; (void)out_size;
    const __nv_bfloat16* x = (const __nv_bfloat16*)d_in[0];
    const __nv_bfloat16* kc = (const __nv_bfloat16*)d_in[1];
    const __nv_bfloat16* vc = (const __nv_bfloat16*)d_in[2];
    const __nv_bfloat16* wq = (const __nv_bfloat16*)d_in[3];
    const __nv_bfloat16* wo = (const __nv_bfloat16*)d_in[4];
    const __nv_bfloat16* wg = (const __nv_bfloat16*)d_in[6];
    const __nv_bfloat16* wu = (const __nv_bfloat16*)d_in[7];
    const __nv_bfloat16* wd = (const __nv_bfloat16*)d_in[8];
    const __nv_bfloat16* c = (const __nv_bfloat16*)d_in[9];
    const __nv_bfloat16* wmod = (const __nv_bfloat16*)d_in[10];
    __nv_bfloat16* out = (__nv_bfloat16*)d_out;

    static bool init = false;
    static void *p_h, *p_o, *p_x1, *p_h2, *p_act, *p_part;
    if (!init) {
        cudaFuncSetAttribute(mega_kernel, cudaFuncAttributeMaxDynamicSharedMemorySize, SM_TOTAL);
        cudaGetSymbolAddress(&p_h, g_h);
        cudaGetSymbolAddress(&p_o, g_o);
        cudaGetSymbolAddress(&p_x1, g_x1);
        cudaGetSymbolAddress(&p_h2, g_h2);
        cudaGetSymbolAddress(&p_act, g_act);
        cudaGetSymbolAddress(&p_part, g_part);
        init = true;
    }
    const CUtensorMapSwizzle S128 = CU_TENSOR_MAP_SWIZZLE_128B, S64 = CU_TENSOR_MAP_SWIZZLE_64B;
    Maps tm;
    tm.h = make_map(p_h, S_LEN, D_MODEL, 128, 64, S128);
    tm.wq = make_map(wq, D_MODEL, N_HEADS * D_HEAD, 64, 64, S128);
    tm.k = make_map(kc, N_HEADS * S_KV, D_HEAD, 128, 64, S128);
    tm.v = make_map(vc, N_HEADS * S_KV, D_HEAD, 128, 64, S128);
    tm.o_st = make_map(p_o, S_LEN, N_HEADS * D_HEAD, 64, 64, S128);
    tm.o_a = make_map(p_o, S_LEN, N_HEADS * D_HEAD, 128, 64, S128);
    tm.wo = make_map(wo, N_HEADS * D_HEAD, D_MODEL, 64, 64, S128);
    tm.part_st = make_map(p_part, 4 * S_LEN, D_MODEL, 64, 64, S128);
    tm.h2 = make_map(p_h2, S_LEN, D_MODEL, 128, 64, S128);
    tm.g128 = make_map(wg, D_MODEL, D_FF, 64, 64, S128);
    tm.u128 = make_map(wu, D_MODEL, D_FF, 64, 64, S128);
    tm.g64 = make_map(wg, D_MODEL, D_FF, 64, 32, S64);
    tm.u64 = make_map(wu, D_MODEL, D_FF, 64, 32, S64);
    tm.act_st64 = make_map(p_act, S_LEN, D_FF, 64, 64, S128);
    tm.act_st24 = make_map(p_act, S_LEN, D_FF, 64, 24, CU_TENSOR_MAP_SWIZZLE_NONE);
    tm.act_a = make_map(p_act, S_LEN, D_FF, 128, 64, S128);
    tm.wd = make_map(wd, D_FF, D_MODEL, 64, 64, S128);

    cudaLaunchConfig_t cfg = {};
    cfg.gridDim = dim3(128);
    cfg.blockDim = dim3(384);
    cfg.dynamicSmemBytes = SM_TOTAL;
    cfg.stream = cudaStreamPerThread;
    cfg.attrs = nullptr;
    cfg.numAttrs = 0;
    cudaLaunchKernelEx(&cfg, mega_kernel, tm, x, c, wmod, out, (const void*)wo, (const void*)wg, (const void*)wu, (const void*)wd);
}
```

```cpp
#include <cuda_runtime.h>
#include <cuda_bf16.h>
#include <cuda.h>
#include <stdint.h>

__device__ __forceinline__ uint32_t smem_u32(const void* p) { return (uint32_t)__cvta_generic_to_shared(p); }

__device__ __forceinline__ void mbar_init(uint32_t bar, uint32_t count) {
    asm volatile("mbarrier.init.shared::cta.b64 [%0], %1;" ::"r"(bar), "r"(count) : "memory");
}
__device__ __forceinline__ void mbar_expect_tx(uint32_t bar, uint32_t bytes) {
    asm volatile("mbarrier.arrive.expect_tx.shared::cta.b64 _, [%0], %1;" ::"r"(bar), "r"(bytes) : "memory");
}
__device__ __forceinline__ void mbar_arrive(uint32_t bar) {
    asm volatile("mbarrier.arrive.shared::cta.b64 _, [%0];" ::"r"(bar) : "memory");
}
__device__ __forceinline__ void mbar_arrive_cluster(uint32_t bar, uint32_t cta) {
    asm volatile(
        "{\n.reg .b32 ra;\n"
        "mapa.shared::cluster.u32 ra, %0, %1;\n"
        "mbarrier.arrive.shared::cluster.b64 _, [ra];\n}\n" ::"r"(bar), "r"(cta)
        : "memory");
}
__device__ __forceinline__ bool mbar_try_wait(uint32_t bar, uint32_t parity) {
    uint32_t ok;
    asm volatile(
        "{\n.reg .pred p;\n"
        "mbarrier.try_wait.parity.shared::cta.b64 p, [%1], %2;\n"
        "selp.u32 %0, 1, 0, p;\n}\n"
        : "=r"(ok)
        : "r"(bar), "r"(parity)
        : "memory");
    return ok != 0;
}
__device__ __forceinline__ bool mbar_try_wait_cluster(uint32_t bar, uint32_t parity) {
    uint32_t ok;
    asm volatile(
        "{\n.reg .pred p;\n"
        "mbarrier.try_wait.parity.shared::cta.b64 p, [%1], %2;\n"
        "selp.u32 %0, 1, 0, p;\n}\n"
        : "=r"(ok)
        : "r"(bar), "r"(parity)
        : "memory");
    return ok != 0;
}
__device__ volatile int g_abort = 0;
__device__ __forceinline__ void mbar_wait(uint32_t bar, uint32_t parity) {
    uint32_t n = 0;
    while (!mbar_try_wait(bar, parity)) {
        if (++n > (1u << 20)) break;
    }
}
__device__ __forceinline__ void mbar_wait_cluster(uint32_t bar, uint32_t parity) { mbar_wait(bar, parity); }
__device__ __forceinline__ void fence_mbar_init() { asm volatile("fence.mbarrier_init.release.cluster;" ::: "memory"); }
__device__ __forceinline__ void fence_proxy_async() { asm volatile("fence.proxy.async.shared::cta;" ::: "memory"); }
__device__ __forceinline__ void fence_proxy_async_all() { asm volatile("fence.proxy.async;" ::: "memory"); }
__device__ __forceinline__ void cluster_arrive() { asm volatile("barrier.cluster.arrive.release.aligned;" ::: "memory"); }
__device__ __forceinline__ void cluster_wait() { asm volatile("barrier.cluster.wait.acquire.aligned;" ::: "memory"); }
__device__ __forceinline__ void cluster_sync() { cluster_arrive(); cluster_wait(); }
__device__ __forceinline__ uint32_t cluster_ctarank() {
    uint32_t r;
    asm volatile("mov.u32 %0, %%cluster_ctarank;" : "=r"(r));
    return r;
}
__device__ __forceinline__ void bar_sync(int id, int n) { asm volatile("bar.sync %0, %1;" ::"r"(id), "r"(n) : "memory"); }
__device__ __forceinline__ void bar_arrive(int id, int n) { asm volatile("bar.arrive %0, %1;" ::"r"(id), "r"(n) : "memory"); }
__device__ __forceinline__ void pdl_wait() { asm volatile("griddepcontrol.wait;" ::: "memory"); }
__device__ __forceinline__ void pdl_launch() { asm volatile("griddepcontrol.launch_dependents;" ::: "memory"); }

__device__ __forceinline__ void tma_prefetch_desc(const CUtensorMap* m) {
    asm volatile("prefetch.tensormap [%0];" ::"l"(m) : "memory");
}
__device__ __forceinline__ void tma_load_2d(uint32_t dst, const CUtensorMap* m, int c0, int c1, uint32_t bar) {
    asm volatile(
        "cp.async.bulk.tensor.2d.shared::cluster.global.mbarrier::complete_tx::bytes [%0], [%1, {%3, %4}], [%2];"
        ::"r"(dst), "l"(m), "r"(bar), "r"(c0), "r"(c1)
        : "memory");
}
__device__ __forceinline__ void tma_load_2d_mc(uint32_t dst, const CUtensorMap* m, int c0, int c1, uint32_t bar, uint16_t mask) {
    asm volatile(
        "cp.async.bulk.tensor.2d.shared::cluster.global.mbarrier::complete_tx::bytes.multicast::cluster [%0], [%1, {%3, %4}], [%2], %5;"
        ::"r"(dst), "l"(m), "r"(bar), "r"(c0), "r"(c1), "h"(mask)
        : "memory");
}
__device__ __forceinline__ void tma_store_2d(const CUtensorMap* m, uint32_t src, int c0, int c1) {
    asm volatile("cp.async.bulk.tensor.2d.global.shared::cta.bulk_group [%0, {%2, %3}], [%1];"
                 ::"l"(m), "r"(src), "r"(c0), "r"(c1)
                 : "memory");
}
__device__ __forceinline__ void tma_store_commit() { asm volatile("cp.async.bulk.commit_group;" ::: "memory"); }
template <int N> __device__ __forceinline__ void tma_store_wait_read() {
    asm volatile("cp.async.bulk.wait_group.read %0;" ::"n"(N) : "memory");
}
template <int N> __device__ __forceinline__ void tma_store_wait() {
    asm volatile("cp.async.bulk.wait_group %0;" ::"n"(N) : "memory");
}

__device__ __forceinline__ void wgmma_fence() { asm volatile("wgmma.fence.sync.aligned;" ::: "memory"); }
__device__ __forceinline__ void wgmma_commit() { asm volatile("wgmma.commit_group.sync.aligned;" ::: "memory"); }
template <int N> __device__ __forceinline__ void wgmma_wait() {
    asm volatile("wgmma.wait_group.sync.aligned %0;" ::"n"(N) : "memory");
}
template <int R> __device__ __forceinline__ void reg_alloc() { asm volatile("setmaxnreg.inc.sync.aligned.u32 %0;" ::"n"(R)); }
template <int R> __device__ __forceinline__ void reg_dealloc() { asm volatile("setmaxnreg.dec.sync.aligned.u32 %0;" ::"n"(R)); }

template <int N> __device__ __forceinline__ void fence_regs(float (&r)[N]) {
#pragma unroll
    for (int i = 0; i < N; i++) asm volatile("" : "+f"(r[i])::"memory");
}
template <int N> __device__ __forceinline__ void fence_regs_u(uint32_t (&r)[N][4]) {
#pragma unroll
    for (int i = 0; i < N; i++) {
#pragma unroll
        for (int j = 0; j < 4; j++) asm volatile("" : "+r"(r[i][j])::"memory");
    }
}

__device__ __forceinline__ uint64_t make_desc(uint32_t addr, uint32_t lbo_bytes, uint32_t sbo_bytes, uint32_t swz) {
    return (uint64_t)((addr & 0x3FFFF) >> 4) | ((uint64_t)(lbo_bytes >> 4) << 16) | ((uint64_t)(sbo_bytes >> 4) << 32) |
           ((uint64_t)swz << 62);
}

__device__ __forceinline__ uint32_t pack_bf16(float lo, float hi) {
    uint32_t r;
    asm("cvt.rn.bf16x2.f32 %0, %1, %2;" : "=r"(r) : "f"(hi), "f"(lo));
    return r;
}
__device__ __forceinline__ float bf16_round(float x) { return __bfloat162float(__float2bfloat16_rn(x)); }
__device__ __forceinline__ float bf16lo(uint32_t v) { return __uint_as_float(v << 16); }
__device__ __forceinline__ float bf16hi(uint32_t v) { return __uint_as_float(v & 0xffff0000u); }
__device__ __forceinline__ float ex2(float x) {
    float y;
    asm("ex2.approx.ftz.f32 %0, %1;" : "=f"(y) : "f"(x));
    return y;
}
__device__ __forceinline__ void stmatrix_x4(uint32_t addr, uint32_t r0, uint32_t r1, uint32_t r2, uint32_t r3) {
    asm volatile("stmatrix.sync.aligned.m8n8.x4.shared.b16 [%0], {%1, %2, %3, %4};" ::"r"(addr), "r"(r0), "r"(r1), "r"(r2), "r"(r3)
                 : "memory");
}
__device__ __forceinline__ uint32_t mapa(uint32_t addr, uint32_t cta) {
    uint32_t r;
    asm volatile("mapa.shared::cluster.u32 %0, %1, %2;" : "=r"(r) : "r"(addr), "r"(cta));
    return r;
}
__device__ __forceinline__ void st_cluster_v2(uint32_t addr, float a, float b) {
    asm volatile("st.shared::cluster.v2.f32 [%0], {%1, %2};" ::"r"(addr), "f"(a), "f"(b) : "memory");
}
__device__ __forceinline__ void wgmma_ss_n256_t1(float (&d)[128], uint64_t descA, uint64_t descB, int scaleD) {
    asm volatile("{\n.reg .pred p;\n"
        "setp.ne.b32 p, %130, 0;\n"
        "wgmma.mma_async.sync.aligned.m64n256k16.f32.bf16.bf16 "
        "{%0, %1, %2, %3, %4, %5, %6, %7, %8, %9, %10, %11, %12, %13, %14, %15, "
        "%16, %17, %18, %19, %20, %21, %22, %23, %24, %25, %26, %27, %28, %29, %30, %31, "
        "%32, %33, %34, %35, %36, %37, %38, %39, %40, %41, %42, %43, %44, %45, %46, %47, "
        "%48, %49, %50, %51, %52, %53, %54, %55, %56, %57, %58, %59, %60, %61, %62, %63, "
        "%64, %65, %66, %67, %68, %69, %70, %71, %72, %73, %74, %75, %76, %77, %78, %79, "
        "%80, %81, %82, %83, %84, %85, %86, %87, %88, %89, %90, %91, %92, %93, %94, %95, "
        "%96, %97, %98, %99, %100, %101, %102, %103, %104, %105, %106, %107, %108, %109, %110, %111, "
        "%112, %113, %114, %115, %116, %117, %118, %119, %120, %121, %122, %123, %124, %125, %126, %127}, "
        "%128, %129, p, 1, 1, 0, 1;\n}\n"
        :
          "+f"(d[0]), "+f"(d[1]), "+f"(d[2]), "+f"(d[3]), "+f"(d[4]), "+f"(d[5]), "+f"(d[6]), "+f"(d[7]),
          "+f"(d[8]), "+f"(d[9]), "+f"(d[10]), "+f"(d[11]), "+f"(d[12]), "+f"(d[13]), "+f"(d[14]), "+f"(d[15]),
          "+f"(d[16]), "+f"(d[17]), "+f"(d[18]), "+f"(d[19]), "+f"(d[20]), "+f"(d[21]), "+f"(d[22]), "+f"(d[23]),
          "+f"(d[24]), "+f"(d[25]), "+f"(d[26]), "+f"(d[27]), "+f"(d[28]), "+f"(d[29]), "+f"(d[30]), "+f"(d[31]),
          "+f"(d[32]), "+f"(d[33]), "+f"(d[34]), "+f"(d[35]), "+f"(d[36]), "+f"(d[37]), "+f"(d[38]), "+f"(d[39]),
          "+f"(d[40]), "+f"(d[41]), "+f"(d[42]), "+f"(d[43]), "+f"(d[44]), "+f"(d[45]), "+f"(d[46]), "+f"(d[47]),
          "+f"(d[48]), "+f"(d[49]), "+f"(d[50]), "+f"(d[51]), "+f"(d[52]), "+f"(d[53]), "+f"(d[54]), "+f"(d[55]),
          "+f"(d[56]), "+f"(d[57]), "+f"(d[58]), "+f"(d[59]), "+f"(d[60]), "+f"(d[61]), "+f"(d[62]), "+f"(d[63]),
          "+f"(d[64]), "+f"(d[65]), "+f"(d[66]), "+f"(d[67]), "+f"(d[68]), "+f"(d[69]), "+f"(d[70]), "+f"(d[71]),
          "+f"(d[72]), "+f"(d[73]), "+f"(d[74]), "+f"(d[75]), "+f"(d[76]), "+f"(d[77]), "+f"(d[78]), "+f"(d[79]),
          "+f"(d[80]), "+f"(d[81]), "+f"(d[82]), "+f"(d[83]), "+f"(d[84]), "+f"(d[85]), "+f"(d[86]), "+f"(d[87]),
          "+f"(d[88]), "+f"(d[89]), "+f"(d[90]), "+f"(d[91]), "+f"(d[92]), "+f"(d[93]), "+f"(d[94]), "+f"(d[95]),
          "+f"(d[96]), "+f"(d[97]), "+f"(d[98]), "+f"(d[99]), "+f"(d[100]), "+f"(d[101]), "+f"(d[102]), "+f"(d[103]),
          "+f"(d[104]), "+f"(d[105]), "+f"(d[106]), "+f"(d[107]), "+f"(d[108]), "+f"(d[109]), "+f"(d[110]), "+f"(d[111]),
          "+f"(d[112]), "+f"(d[113]), "+f"(d[114]), "+f"(d[115]), "+f"(d[116]), "+f"(d[117]), "+f"(d[118]), "+f"(d[119]),
          "+f"(d[120]), "+f"(d[121]), "+f"(d[122]), "+f"(d[123]), "+f"(d[124]), "+f"(d[125]), "+f"(d[126]), "+f"(d[127])
        : "l"(descA), "l"(descB), "r"(scaleD));
}

__device__ __forceinline__ void wgmma_rs_n128_t0(float (&d)[64], const uint32_t (&a)[4], uint64_t descB, int scaleD) {
    asm volatile("{\n.reg .pred p;\n"
        "setp.ne.b32 p, %69, 0;\n"
        "wgmma.mma_async.sync.aligned.m64n128k16.f32.bf16.bf16 "
        "{%0, %1, %2, %3, %4, %5, %6, %7, %8, %9, %10, %11, %12, %13, %14, %15, "
        "%16, %17, %18, %19, %20, %21, %22, %23, %24, %25, %26, %27, %28, %29, %30, %31, "
        "%32, %33, %34, %35, %36, %37, %38, %39, %40, %41, %42, %43, %44, %45, %46, %47, "
        "%48, %49, %50, %51, %52, %53, %54, %55, %56, %57, %58, %59, %60, %61, %62, %63}, "
        "{%64, %65, %66, %67}, %68, p, 1, 1, 0;\n}\n"
        :
          "+f"(d[0]), "+f"(d[1]), "+f"(d[2]), "+f"(d[3]), "+f"(d[4]), "+f"(d[5]), "+f"(d[6]), "+f"(d[7]),
          "+f"(d[8]), "+f"(d[9]), "+f"(d[10]), "+f"(d[11]), "+f"(d[12]), "+f"(d[13]), "+f"(d[14]), "+f"(d[15]),
          "+f"(d[16]), "+f"(d[17]), "+f"(d[18]), "+f"(d[19]), "+f"(d[20]), "+f"(d[21]), "+f"(d[22]), "+f"(d[23]),
          "+f"(d[24]), "+f"(d[25]), "+f"(d[26]), "+f"(d[27]), "+f"(d[28]), "+f"(d[29]), "+f"(d[30]), "+f"(d[31]),
          "+f"(d[32]), "+f"(d[33]), "+f"(d[34]), "+f"(d[35]), "+f"(d[36]), "+f"(d[37]), "+f"(d[38]), "+f"(d[39]),
          "+f"(d[40]), "+f"(d[41]), "+f"(d[42]), "+f"(d[43]), "+f"(d[44]), "+f"(d[45]), "+f"(d[46]), "+f"(d[47]),
          "+f"(d[48]), "+f"(d[49]), "+f"(d[50]), "+f"(d[51]), "+f"(d[52]), "+f"(d[53]), "+f"(d[54]), "+f"(d[55]),
          "+f"(d[56]), "+f"(d[57]), "+f"(d[58]), "+f"(d[59]), "+f"(d[60]), "+f"(d[61]), "+f"(d[62]), "+f"(d[63])
        : "r"(a[0]), "r"(a[1]), "r"(a[2]), "r"(a[3]), "l"(descB), "r"(scaleD));
}

__device__ __forceinline__ void wgmma_rs_n128_t0_z(float (&d)[64], const uint32_t (&a)[4], uint64_t descB) {
    asm volatile("{\n.reg .pred p;\n"
        "setp.ne.b32 p, 0, 0;\n"
        "wgmma.mma_async.sync.aligned.m64n128k16.f32.bf16.bf16 "
        "{%0, %1, %2, %3, %4, %5, %6, %7, %8, %9, %10, %11, %12, %13, %14, %15, "
        "%16, %17, %18, %19, %20, %21, %22, %23, %24, %25, %26, %27, %28, %29, %30, %31, "
        "%32, %33, %34, %35, %36, %37, %38, %39, %40, %41, %42, %43, %44, %45, %46, %47, "
        "%48, %49, %50, %51, %52, %53, %54, %55, %56, %57, %58, %59, %60, %61, %62, %63}, "
        "{%64, %65, %66, %67}, %68, p, 1, 1, 0;\n}\n"
        :
          "=f"(d[0]), "=f"(d[1]), "=f"(d[2]), "=f"(d[3]), "=f"(d[4]), "=f"(d[5]), "=f"(d[6]), "=f"(d[7]),
          "=f"(d[8]), "=f"(d[9]), "=f"(d[10]), "=f"(d[11]), "=f"(d[12]), "=f"(d[13]), "=f"(d[14]), "=f"(d[15]),
          "=f"(d[16]), "=f"(d[17]), "=f"(d[18]), "=f"(d[19]), "=f"(d[20]), "=f"(d[21]), "=f"(d[22]), "=f"(d[23]),
          "=f"(d[24]), "=f"(d[25]), "=f"(d[26]), "=f"(d[27]), "=f"(d[28]), "=f"(d[29]), "=f"(d[30]), "=f"(d[31]),
          "=f"(d[32]), "=f"(d[33]), "=f"(d[34]), "=f"(d[35]), "=f"(d[36]), "=f"(d[37]), "=f"(d[38]), "=f"(d[39]),
          "=f"(d[40]), "=f"(d[41]), "=f"(d[42]), "=f"(d[43]), "=f"(d[44]), "=f"(d[45]), "=f"(d[46]), "=f"(d[47]),
          "=f"(d[48]), "=f"(d[49]), "=f"(d[50]), "=f"(d[51]), "=f"(d[52]), "=f"(d[53]), "=f"(d[54]), "=f"(d[55]),
          "=f"(d[56]), "=f"(d[57]), "=f"(d[58]), "=f"(d[59]), "=f"(d[60]), "=f"(d[61]), "=f"(d[62]), "=f"(d[63])
        : "r"(a[0]), "r"(a[1]), "r"(a[2]), "r"(a[3]), "l"(descB));
}

__device__ __forceinline__ void wgmma_rs_n128_t1(float (&d)[64], const uint32_t (&a)[4], uint64_t descB, int scaleD) {
    asm volatile("{\n.reg .pred p;\n"
        "setp.ne.b32 p, %69, 0;\n"
        "wgmma.mma_async.sync.aligned.m64n128k16.f32.bf16.bf16 "
        "{%0, %1, %2, %3, %4, %5, %6, %7, %8, %9, %10, %11, %12, %13, %14, %15, "
        "%16, %17, %18, %19, %20, %21, %22, %23, %24, %25, %26, %27, %28, %29, %30, %31, "
        "%32, %33, %34, %35, %36, %37, %38, %39, %40, %41, %42, %43, %44, %45, %46, %47, "
        "%48, %49, %50, %51, %52, %53, %54, %55, %56, %57, %58, %59, %60, %61, %62, %63}, "
        "{%64, %65, %66, %67}, %68, p, 1, 1, 1;\n}\n"
        :
          "+f"(d[0]), "+f"(d[1]), "+f"(d[2]), "+f"(d[3]), "+f"(d[4]), "+f"(d[5]), "+f"(d[6]), "+f"(d[7]),
          "+f"(d[8]), "+f"(d[9]), "+f"(d[10]), "+f"(d[11]), "+f"(d[12]), "+f"(d[13]), "+f"(d[14]), "+f"(d[15]),
          "+f"(d[16]), "+f"(d[17]), "+f"(d[18]), "+f"(d[19]), "+f"(d[20]), "+f"(d[21]), "+f"(d[22]), "+f"(d[23]),
          "+f"(d[24]), "+f"(d[25]), "+f"(d[26]), "+f"(d[27]), "+f"(d[28]), "+f"(d[29]), "+f"(d[30]), "+f"(d[31]),
          "+f"(d[32]), "+f"(d[33]), "+f"(d[34]), "+f"(d[35]), "+f"(d[36]), "+f"(d[37]), "+f"(d[38]), "+f"(d[39]),
          "+f"(d[40]), "+f"(d[41]), "+f"(d[42]), "+f"(d[43]), "+f"(d[44]), "+f"(d[45]), "+f"(d[46]), "+f"(d[47]),
          "+f"(d[48]), "+f"(d[49]), "+f"(d[50]), "+f"(d[51]), "+f"(d[52]), "+f"(d[53]), "+f"(d[54]), "+f"(d[55]),
          "+f"(d[56]), "+f"(d[57]), "+f"(d[58]), "+f"(d[59]), "+f"(d[60]), "+f"(d[61]), "+f"(d[62]), "+f"(d[63])
        : "r"(a[0]), "r"(a[1]), "r"(a[2]), "r"(a[3]), "l"(descB), "r"(scaleD));
}

__device__ __forceinline__ void wgmma_ss_n184_t1(float (&d)[92], uint64_t descA, uint64_t descB, int scaleD) {
    asm volatile("{\n.reg .pred p;\n"
        "setp.ne.b32 p, %94, 0;\n"
        "wgmma.mma_async.sync.aligned.m64n184k16.f32.bf16.bf16 "
        "{%0, %1, %2, %3, %4, %5, %6, %7, %8, %9, %10, %11, %12, %13, %14, %15, "
        "%16, %17, %18, %19, %20, %21, %22, %23, %24, %25, %26, %27, %28, %29, %30, %31, "
        "%32, %33, %34, %35, %36, %37, %38, %39, %40, %41, %42, %43, %44, %45, %46, %47, "
        "%48, %49, %50, %51, %52, %53, %54, %55, %56, %57, %58, %59, %60, %61, %62, %63, "
        "%64, %65, %66, %67, %68, %69, %70, %71, %72, %73, %74, %75, %76, %77, %78, %79, "
        "%80, %81, %82, %83, %84, %85, %86, %87, %88, %89, %90, %91}, "
        "%92, %93, p, 1, 1, 0, 1;\n}\n"
        :
          "+f"(d[0]), "+f"(d[1]), "+f"(d[2]), "+f"(d[3]), "+f"(d[4]), "+f"(d[5]), "+f"(d[6]), "+f"(d[7]),
          "+f"(d[8]), "+f"(d[9]), "+f"(d[10]), "+f"(d[11]), "+f"(d[12]), "+f"(d[13]), "+f"(d[14]), "+f"(d[15]),
          "+f"(d[16]), "+f"(d[17]), "+f"(d[18]), "+f"(d[19]), "+f"(d[20]), "+f"(d[21]), "+f"(d[22]), "+f"(d[23]),
          "+f"(d[24]), "+f"(d[25]), "+f"(d[26]), "+f"(d[27]), "+f"(d[28]), "+f"(d[29]), "+f"(d[30]), "+f"(d[31]),
          "+f"(d[32]), "+f"(d[33]), "+f"(d[34]), "+f"(d[35]), "+f"(d[36]), "+f"(d[37]), "+f"(d[38]), "+f"(d[39]),
          "+f"(d[40]), "+f"(d[41]), "+f"(d[42]), "+f"(d[43]), "+f"(d[44]), "+f"(d[45]), "+f"(d[46]), "+f"(d[47]),
          "+f"(d[48]), "+f"(d[49]), "+f"(d[50]), "+f"(d[51]), "+f"(d[52]), "+f"(d[53]), "+f"(d[54]), "+f"(d[55]),
          "+f"(d[56]), "+f"(d[57]), "+f"(d[58]), "+f"(d[59]), "+f"(d[60]), "+f"(d[61]), "+f"(d[62]), "+f"(d[63]),
          "+f"(d[64]), "+f"(d[65]), "+f"(d[66]), "+f"(d[67]), "+f"(d[68]), "+f"(d[69]), "+f"(d[70]), "+f"(d[71]),
          "+f"(d[72]), "+f"(d[73]), "+f"(d[74]), "+f"(d[75]), "+f"(d[76]), "+f"(d[77]), "+f"(d[78]), "+f"(d[79]),
          "+f"(d[80]), "+f"(d[81]), "+f"(d[82]), "+f"(d[83]), "+f"(d[84]), "+f"(d[85]), "+f"(d[86]), "+f"(d[87]),
          "+f"(d[88]), "+f"(d[89]), "+f"(d[90]), "+f"(d[91])
        : "l"(descA), "l"(descB), "r"(scaleD));
}

__device__ __forceinline__ void wgmma_ss_n192_t1(float (&d)[96], uint64_t descA, uint64_t descB, int scaleD) {
    asm volatile("{\n.reg .pred p;\n"
        "setp.ne.b32 p, %98, 0;\n"
        "wgmma.mma_async.sync.aligned.m64n192k16.f32.bf16.bf16 "
        "{%0, %1, %2, %3, %4, %5, %6, %7, %8, %9, %10, %11, %12, %13, %14, %15, "
        "%16, %17, %18, %19, %20, %21, %22, %23, %24, %25, %26, %27, %28, %29, %30, %31, "
        "%32, %33, %34, %35, %36, %37, %38, %39, %40, %41, %42, %43, %44, %45, %46, %47, "
        "%48, %49, %50, %51, %52, %53, %54, %55, %56, %57, %58, %59, %60, %61, %62, %63, "
        "%64, %65, %66, %67, %68, %69, %70, %71, %72, %73, %74, %75, %76, %77, %78, %79, "
        "%80, %81, %82, %83, %84, %85, %86, %87, %88, %89, %90, %91, %92, %93, %94, %95}, "
        "%96, %97, p, 1, 1, 0, 1;\n}\n"
        :
          "+f"(d[0]), "+f"(d[1]), "+f"(d[2]), "+f"(d[3]), "+f"(d[4]), "+f"(d[5]), "+f"(d[6]), "+f"(d[7]),
          "+f"(d[8]), "+f"(d[9]), "+f"(d[10]), "+f"(d[11]), "+f"(d[12]), "+f"(d[13]), "+f"(d[14]), "+f"(d[15]),
          "+f"(d[16]), "+f"(d[17]), "+f"(d[18]), "+f"(d[19]), "+f"(d[20]), "+f"(d[21]), "+f"(d[22]), "+f"(d[23]),
          "+f"(d[24]), "+f"(d[25]), "+f"(d[26]), "+f"(d[27]), "+f"(d[28]), "+f"(d[29]), "+f"(d[30]), "+f"(d[31]),
          "+f"(d[32]), "+f"(d[33]), "+f"(d[34]), "+f"(d[35]), "+f"(d[36]), "+f"(d[37]), "+f"(d[38]), "+f"(d[39]),
          "+f"(d[40]), "+f"(d[41]), "+f"(d[42]), "+f"(d[43]), "+f"(d[44]), "+f"(d[45]), "+f"(d[46]), "+f"(d[47]),
          "+f"(d[48]), "+f"(d[49]), "+f"(d[50]), "+f"(d[51]), "+f"(d[52]), "+f"(d[53]), "+f"(d[54]), "+f"(d[55]),
          "+f"(d[56]), "+f"(d[57]), "+f"(d[58]), "+f"(d[59]), "+f"(d[60]), "+f"(d[61]), "+f"(d[62]), "+f"(d[63]),
          "+f"(d[64]), "+f"(d[65]), "+f"(d[66]), "+f"(d[67]), "+f"(d[68]), "+f"(d[69]), "+f"(d[70]), "+f"(d[71]),
          "+f"(d[72]), "+f"(d[73]), "+f"(d[74]), "+f"(d[75]), "+f"(d[76]), "+f"(d[77]), "+f"(d[78]), "+f"(d[79]),
          "+f"(d[80]), "+f"(d[81]), "+f"(d[82]), "+f"(d[83]), "+f"(d[84]), "+f"(d[85]), "+f"(d[86]), "+f"(d[87]),
          "+f"(d[88]), "+f"(d[89]), "+f"(d[90]), "+f"(d[91]), "+f"(d[92]), "+f"(d[93]), "+f"(d[94]), "+f"(d[95])
        : "l"(descA), "l"(descB), "r"(scaleD));
}

__device__ __forceinline__ void wgmma_ss_n128_t1(float (&d)[64], uint64_t descA, uint64_t descB, int scaleD) {
    asm volatile("{\n.reg .pred p;\n"
        "setp.ne.b32 p, %66, 0;\n"
        "wgmma.mma_async.sync.aligned.m64n128k16.f32.bf16.bf16 "
        "{%0, %1, %2, %3, %4, %5, %6, %7, %8, %9, %10, %11, %12, %13, %14, %15, "
        "%16, %17, %18, %19, %20, %21, %22, %23, %24, %25, %26, %27, %28, %29, %30, %31, "
        "%32, %33, %34, %35, %36, %37, %38, %39, %40, %41, %42, %43, %44, %45, %46, %47, "
        "%48, %49, %50, %51, %52, %53, %54, %55, %56, %57, %58, %59, %60, %61, %62, %63}, "
        "%64, %65, p, 1, 1, 0, 1;\n}\n"
        :
          "+f"(d[0]), "+f"(d[1]), "+f"(d[2]), "+f"(d[3]), "+f"(d[4]), "+f"(d[5]), "+f"(d[6]), "+f"(d[7]),
          "+f"(d[8]), "+f"(d[9]), "+f"(d[10]), "+f"(d[11]), "+f"(d[12]), "+f"(d[13]), "+f"(d[14]), "+f"(d[15]),
          "+f"(d[16]), "+f"(d[17]), "+f"(d[18]), "+f"(d[19]), "+f"(d[20]), "+f"(d[21]), "+f"(d[22]), "+f"(d[23]),
          "+f"(d[24]), "+f"(d[25]), "+f"(d[26]), "+f"(d[27]), "+f"(d[28]), "+f"(d[29]), "+f"(d[30]), "+f"(d[31]),
          "+f"(d[32]), "+f"(d[33]), "+f"(d[34]), "+f"(d[35]), "+f"(d[36]), "+f"(d[37]), "+f"(d[38]), "+f"(d[39]),
          "+f"(d[40]), "+f"(d[41]), "+f"(d[42]), "+f"(d[43]), "+f"(d[44]), "+f"(d[45]), "+f"(d[46]), "+f"(d[47]),
          "+f"(d[48]), "+f"(d[49]), "+f"(d[50]), "+f"(d[51]), "+f"(d[52]), "+f"(d[53]), "+f"(d[54]), "+f"(d[55]),
          "+f"(d[56]), "+f"(d[57]), "+f"(d[58]), "+f"(d[59]), "+f"(d[60]), "+f"(d[61]), "+f"(d[62]), "+f"(d[63])
        : "l"(descA), "l"(descB), "r"(scaleD));
}

__device__ __forceinline__ void wgmma_ss_n32_t1(float (&d)[16], uint64_t descA, uint64_t descB, int scaleD) {
    asm volatile("{\n.reg .pred p;\n"
        "setp.ne.b32 p, %18, 0;\n"
        "wgmma.mma_async.sync.aligned.m64n32k16.f32.bf16.bf16 "
        "{%0, %1, %2, %3, %4, %5, %6, %7, %8, %9, %10, %11, %12, %13, %14, %15}, "
        "%16, %17, p, 1, 1, 0, 1;\n}\n"
        :
          "+f"(d[0]), "+f"(d[1]), "+f"(d[2]), "+f"(d[3]), "+f"(d[4]), "+f"(d[5]), "+f"(d[6]), "+f"(d[7]),
          "+f"(d[8]), "+f"(d[9]), "+f"(d[10]), "+f"(d[11]), "+f"(d[12]), "+f"(d[13]), "+f"(d[14]), "+f"(d[15])
        : "l"(descA), "l"(descB), "r"(scaleD));
}

constexpr int S_LEN = 2048;
constexpr int D_MODEL = 640;
constexpr int N_HEADS = 32;
constexpr int D_HEAD = 128;
constexpr int S_KV = 2048;
constexpr int WIN = 512;
constexpr int D_FF = 1728;
constexpr float LN_EPS = 1e-5f;

#define TS(kid, slot)

__device__ float g_mod[6 * D_MODEL];
__device__ __align__(1024) __nv_bfloat16 g_h[S_LEN * D_MODEL];
__device__ __align__(1024) __nv_bfloat16 g_o[S_LEN * N_HEADS * D_HEAD];
__device__ __align__(1024) __nv_bfloat16 g_part[4 * S_LEN * D_MODEL];
__device__ __align__(1024) __nv_bfloat16 g_x1[S_LEN * D_MODEL];
__device__ __align__(1024) __nv_bfloat16 g_h2[S_LEN * D_MODEL];
__device__ __align__(1024) __nv_bfloat16 g_act[S_LEN * D_FF];

constexpr int F_MODAB = 0, F_MODALL = 1, F_H = 2, F_P = 18, F_H2 = 34, F_A = 50, F_O = 66, F_COUNT = 130;
__device__ unsigned g_flags[F_COUNT * 32];
__device__ unsigned g_epoch;
__device__ unsigned g_exit;

__device__ __forceinline__ void flag_signal(int f) {
    asm volatile("red.release.gpu.global.add.u32 [%0], 1;" ::"l"(g_flags + f * 32) : "memory");
}
__device__ __forceinline__ void flag_signal_relaxed(int f) {
    asm volatile("red.relaxed.gpu.global.add.u32 [%0], 1;" ::"l"(g_flags + f * 32) : "memory");
}
__device__ __forceinline__ void flag_wait(int f, unsigned target) {
    unsigned n = 0;
    while (true) {
        unsigned v;
        asm volatile("ld.acquire.gpu.global.u32 %0, [%1];" : "=r"(v) : "l"(g_flags + f * 32) : "memory");
        if ((int)(v - target) >= 0) break;
        ++n;
        if (n > (1u << 22)) { g_abort = 1; break; }
        if ((n & 255u) == 0 && g_abort) break;
    }
}

struct Maps {
    CUtensorMap h, wq, k, v, o_st, o_a, wo, part_st, h2, g128, u128, g64, u64, act_st64, act_st24, act_a, wd, wd32;
};

constexpr int SM_DATA = 229376;
constexpr int SM_STAGING = 196608;
constexpr int SM_TOTAL = SM_DATA + 1024 + 512;
constexpr int B1F = 0, B1E = 6, B2F = 12, B2E = 16, B4F = 20, B4E = 24, B5F = 28, B5E = 33, BD1 = 38, BD2 = 39, BD4 = 40, BD1A = 41, BX = 42;
constexpr int P1_STAGE = 32768, P2_STAGE = 57344, P4_STAGE = 49152, P5_STAGE = 36864;

__device__ __forceinline__ float rcp_approx(float x) { float y; asm("rcp.approx.ftz.f32 %0, %1;" : "=f"(y) : "f"(x)); return y; }
__device__ __forceinline__ float silu_mul(float g, float u) { return g * rcp_approx(1.f + ex2(-1.4426950408889634f * g)) * u; }
__device__ __forceinline__ uint2 ldcg_u2(const void* p) { return __ldcg(reinterpret_cast<const uint2*>(p)); }

__device__ __forceinline__ void ln_rows(const uint2 (&xr)[2][5], const float* __restrict__ shift, const float* __restrict__ scale1p,
                                     __nv_bfloat16* __restrict__ dst, int lane) {
    float4 sh[5], sc[5];
#pragma unroll
    for (int i = 0; i < 5; i++) {
        sh[i] = __ldcg(reinterpret_cast<const float4*>(shift + (lane + 32 * i) * 4));
        sc[i] = __ldcg(reinterpret_cast<const float4*>(scale1p + (lane + 32 * i) * 4));
    }
    float mean[2], rstd[2];
#pragma unroll
    for (int rr = 0; rr < 2; rr++) {
        float s = 0.f;
#pragma unroll
        for (int i = 0; i < 5; i++) s += (bf16lo(xr[rr][i].x) + bf16hi(xr[rr][i].x)) + (bf16lo(xr[rr][i].y) + bf16hi(xr[rr][i].y));
#pragma unroll
        for (int o = 16; o > 0; o >>= 1) s += __shfl_xor_sync(0xffffffffu, s, o);
        mean[rr] = s * (1.f / D_MODEL);
    }
#pragma unroll
    for (int rr = 0; rr < 2; rr++) {
        float q = 0.f;
#pragma unroll
        for (int i = 0; i < 5; i++) {
            const float d0 = bf16lo(xr[rr][i].x) - mean[rr], d1 = bf16hi(xr[rr][i].x) - mean[rr];
            const float d2 = bf16lo(xr[rr][i].y) - mean[rr], d3 = bf16hi(xr[rr][i].y) - mean[rr];
            q += (d0 * d0 + d1 * d1) + (d2 * d2 + d3 * d3);
        }
#pragma unroll
        for (int o = 16; o > 0; o >>= 1) q += __shfl_xor_sync(0xffffffffu, q, o);
        rstd[rr] = rsqrtf(q * (1.f / D_MODEL) + LN_EPS);
    }
#pragma unroll
    for (int rr = 0; rr < 2; rr++) {
#pragma unroll
        for (int i = 0; i < 5; i++) {
            uint2 u;
            u.x = pack_bf16((bf16lo(xr[rr][i].x) - mean[rr]) * rstd[rr] * sc[i].x + sh[i].x, (bf16hi(xr[rr][i].x) - mean[rr]) * rstd[rr] * sc[i].y + sh[i].y);
            u.y = pack_bf16((bf16lo(xr[rr][i].y) - mean[rr]) * rstd[rr] * sc[i].z + sh[i].z, (bf16hi(xr[rr][i].y) - mean[rr]) * rstd[rr] * sc[i].w + sh[i].w);
            *reinterpret_cast<uint2*>(dst + (size_t)rr * D_MODEL + (lane + 32 * i) * 4) = u;
        }
    }
}

__global__ void __cluster_dims__(2, 1, 1) __launch_bounds__(384, 1)
mega_kernel(const __grid_constant__ Maps tm, const __nv_bfloat16* __restrict__ x, const __nv_bfloat16* __restrict__ cvec,
            const __nv_bfloat16* __restrict__ w_mod, __nv_bfloat16* __restrict__ out, const void* wo_p, const void* wg_p,
            const void* wu_p, const void* wd_p) {
    extern __shared__ uint8_t smem_raw[];
    const uint32_t base = (smem_u32(smem_raw) + 1023u) & ~1023u;
    const uint32_t bars = base + SM_DATA;
    const uint32_t rank = cluster_ctarank();
    const int cid = blockIdx.x >> 1;
    const int p = cid & 7, j = cid >> 3;
    const int mt = p * 2 + (int)rank;
    const int m0 = mt * 128;
    const int wg = threadIdx.x >> 7;
    unsigned epoch;
    asm volatile("ld.volatile.global.u32 %0, [%1];" : "=r"(epoch) : "l"(&g_epoch));

    if (threadIdx.x == 0) {
        for (int i = 0; i < 6; i++) { mbar_init(bars + 8 * (B1F + i), 1); mbar_init(bars + 8 * (B1E + i), 4); }
        for (int i = 0; i < 4; i++) { mbar_init(bars + 8 * (B2F + i), 1); mbar_init(bars + 8 * (B2E + i), 4); }
        for (int i = 0; i < 4; i++) { mbar_init(bars + 8 * (B4F + i), 1); mbar_init(bars + 8 * (B4E + i), 4); }
        for (int i = 0; i < 5; i++) { mbar_init(bars + 8 * (B5F + i), 1); mbar_init(bars + 8 * (B5E + i), 2); }
        mbar_init(bars + 8 * BD1, 4); mbar_init(bars + 8 * BD2, 4); mbar_init(bars + 8 * BD4, 4); mbar_init(bars + 8 * BD1A, 4);
        mbar_init(bars + 8 * BX, 1);
        mbar_expect_tx(bars + 8 * BX, 40960);
        fence_mbar_init();
    }
    __syncthreads();
    cluster_sync();

    if (wg == 2) {
        reg_dealloc<40>();
        if (threadIdx.x == 256) {
            {
                uint32_t st = 0, ph = 1;
                bool first = true;
#pragma unroll 1
                for (int hp = 0; hp < 2; hp++) {
                    const int head0 = j * 4 + hp * 2;
                    if (first) {
#pragma unroll 1
                        for (int s = 1; s < 6; s++) {
                            if (s == 3) continue;
                            const int kb = s < 3 ? s - 1 : s - 2;
                            mbar_expect_tx(bars + 8 * (B1F + s), P1_STAGE);
#pragma unroll 1
                            for (int c = 0; c < 2; c++) {
                                const int chunk = 2 * (int)rank + c;
                                tma_load_2d_mc(base + s * P1_STAGE + chunk * 8192, &tm.wq, head0 * 128 + chunk * 64, kb * 64, bars + 8 * (B1F + s), 3);
                            }
                        }
                        flag_wait(F_H + mt, (epoch + 1) * 8);
                        fence_proxy_async_all();
#pragma unroll 1
                        for (int s = 0; s < 6; s += 3) {
                            mbar_expect_tx(bars + 8 * (B1F + s), P1_STAGE);
                            tma_load_2d(base + s * P1_STAGE, &tm.h, (s / 3 * 2) * 64, m0, bars + 8 * (B1F + s));
                            tma_load_2d(base + s * P1_STAGE + 16384, &tm.h, (s / 3 * 2 + 1) * 64, m0, bars + 8 * (B1F + s));
                        }
                        ph = 0;
                    }
#pragma unroll 1
                    for (int kk2 = first ? 2 : 0; kk2 < 5; kk2++) {
                        mbar_wait(bars + 8 * (B1E + st), ph);
                        mbar_expect_tx(bars + 8 * (B1F + st), P1_STAGE);
                        tma_load_2d(base + st * P1_STAGE, &tm.h, (2 * kk2) * 64, m0, bars + 8 * (B1F + st));
                        tma_load_2d(base + st * P1_STAGE + 16384, &tm.h, (2 * kk2 + 1) * 64, m0, bars + 8 * (B1F + st));
                        if (++st == 6) { st = 0; ph ^= 1; }
#pragma unroll 1
                        for (int u = 0; u < 2; u++) {
                            mbar_wait(bars + 8 * (B1E + st), ph);
                            mbar_expect_tx(bars + 8 * (B1F + st), P1_STAGE);
                            const int kb = 2 * kk2 + u;
#pragma unroll 1
                            for (int c = 0; c < 2; c++) {
                                const int chunk = 2 * (int)rank + c;
                                tma_load_2d_mc(base + st * P1_STAGE + chunk * 8192, &tm.wq, head0 * 128 + chunk * 64, kb * 64, bars + 8 * (B1F + st), 3);
                            }
                            if (++st == 6) { st = 0; ph ^= 1; }
                        }
                    }
                    first = false;
#pragma unroll 1
                    for (int t = 0; t <= 8; t++) {
                        if (t < 8) {
                            mbar_wait(bars + 8 * (B1E + st), ph);
                            mbar_expect_tx(bars + 8 * (B1F + st), P1_STAGE);
                            const int row = (head0 + (t >> 2)) * S_KV + (S_KV - WIN) + (t & 3) * 128;
                            tma_load_2d_mc(base + st * P1_STAGE + rank * 16384, &tm.k, rank * 64, row, bars + 8 * (B1F + st), 3);
                            if (++st == 6) { st = 0; ph ^= 1; }
                        }
                        if (t > 0) {
                            mbar_wait(bars + 8 * (B1E + st), ph);
                            mbar_expect_tx(bars + 8 * (B1F + st), P1_STAGE);
                            const int tv = t - 1;
                            const int row = (head0 + (tv >> 2)) * S_KV + (S_KV - WIN) + (tv & 3) * 128;
                            tma_load_2d_mc(base + st * P1_STAGE + rank * 16384, &tm.v, rank * 64, row, bars + 8 * (B1F + st), 3);
                            if (++st == 6) { st = 0; ph ^= 1; }
                        }
                    }
                }
            }
            {
                const int kq = j >> 1, n0 = (j & 1) * 320;
                uint32_t st = 0, ph = 1;
#pragma unroll 1
                for (int i = 0; i < 16; i++) {
                    if (i == 0) mbar_wait(bars + 8 * BD1A, 0);
                    if (i == 3) mbar_wait(bars + 8 * BD1, 0);
                    if (i == 8) { flag_wait(F_O + mt * 4 + kq, (epoch + 1) * 4); fence_proxy_async_all(); }
                    mbar_wait(bars + 8 * (B2E + st), ph);
                    mbar_expect_tx(bars + 8 * (B2F + st), P2_STAGE);
                    const uint32_t dst = base + st * P2_STAGE;
                    const int k0 = kq * 1024 + ((i + (j & 1) * 8) & 15) * 64;
                    tma_load_2d(dst, &tm.o_a, k0, m0, bars + 8 * (B2F + st));
#pragma unroll 1
                    for (int c = 0; c < 5; c++)
                        if (((c + i) & 1) == (int)rank) tma_load_2d_mc(dst + 16384 + c * 8192, &tm.wo, n0 + c * 64, k0, bars + 8 * (B2F + st), 3);
                    if (++st == 4) { st = 0; ph ^= 1; }
                }
            }
            {
                const int f0 = j * 216;
                const CUtensorMap* t128 = rank == 0 ? &tm.g128 : &tm.u128;
                const CUtensorMap* t64 = rank == 0 ? &tm.g64 : &tm.u64;
                mbar_wait(bars + 8 * BD2, 0);
#pragma unroll 1
                for (int i = 0; i < 4; i++) {
                    mbar_expect_tx(bars + 8 * (B4F + i), 16384 + 32768);
                    const uint32_t dst = base + i * P4_STAGE;
                    tma_load_2d_mc(dst + 16384 + rank * 16384, t128, f0, i * 64, bars + 8 * (B4F + i), 3);
                    tma_load_2d_mc(dst + 16384 + rank * 16384 + 8192, t128, f0 + 64, i * 64, bars + 8 * (B4F + i), 3);
                }
                flag_wait(F_H2 + mt, (epoch + 1) * 8);
                fence_proxy_async_all();
#pragma unroll 1
                for (int i = 0; i < 4; i++) tma_load_2d(base + i * P4_STAGE, &tm.h2, i * 64, m0, bars + 8 * (B4F + i));
                uint32_t st = 0, ph = 0;
#pragma unroll 1
                for (int i = 4; i < 20; i++) {
                    const int kb = i < 10 ? i : i - 10;
                    mbar_wait(bars + 8 * (B4E + st), ph);
                    const uint32_t dst = base + st * P4_STAGE;
                    if (i < 10) {
                        mbar_expect_tx(bars + 8 * (B4F + st), 16384 + 32768);
                        tma_load_2d(dst, &tm.h2, kb * 64, m0, bars + 8 * (B4F + st));
                        tma_load_2d_mc(dst + 16384 + rank * 16384, t128, f0, kb * 64, bars + 8 * (B4F + st), 3);
                        tma_load_2d_mc(dst + 16384 + rank * 16384 + 8192, t128, f0 + 64, kb * 64, bars + 8 * (B4F + st), 3);
                    } else {
                        mbar_expect_tx(bars + 8 * (B4F + st), 16384 + 24576);
                        tma_load_2d(dst, &tm.h2, kb * 64, m0, bars + 8 * (B4F + st));
#pragma unroll 1
                        for (int c = 0; c < 3; c++)
                            tma_load_2d_mc(dst + 16384 + rank * 12288 + c * 4096, t64, f0 + 128 + c * 32, kb * 64, bars + 8 * (B4F + st), 3);
                    }
                    if (++st == 4) { st = 0; ph ^= 1; }
                }
            }
            {
                const int mt5 = p * 2 + (j >> 2), n0 = (j & 3) * 160;
                const int kb0 = rank == 0 ? 0 : 14, nkb = rank == 0 ? 14 : 13;
                mbar_wait(bars + 8 * BD4, 0);
#pragma unroll 1
                for (int i = 0; i < 5; i++) {
                    mbar_expect_tx(bars + 8 * (B5F + i), P5_STAGE);
                    const uint32_t dst = base + i * P5_STAGE + 16384;
                    tma_load_2d(dst, &tm.wd, n0, (kb0 + i) * 64, bars + 8 * (B5F + i));
                    tma_load_2d(dst + 8192, &tm.wd, n0 + 64, (kb0 + i) * 64, bars + 8 * (B5F + i));
                    tma_load_2d(dst + 16384, &tm.wd32, n0 + 128, (kb0 + i) * 64, bars + 8 * (B5F + i));
                }
                flag_wait(F_A + mt5, (epoch + 1) * 16);
                fence_proxy_async_all();
#pragma unroll 1
                for (int i = 0; i < 5; i++) tma_load_2d(base + i * P5_STAGE, &tm.act_a, (kb0 + i) * 64, mt5 * 128, bars + 8 * (B5F + i));
                uint32_t st = 0, ph = 0;
#pragma unroll 1
                for (int i = 5; i < nkb; i++) {
                    mbar_wait(bars + 8 * (B5E + st), ph);
                    mbar_expect_tx(bars + 8 * (B5F + st), P5_STAGE);
                    const uint32_t dst = base + st * P5_STAGE;
                    const int k0 = (kb0 + i) * 64;
                    tma_load_2d(dst, &tm.act_a, k0, mt5 * 128, bars + 8 * (B5F + st));
                    tma_load_2d(dst + 16384, &tm.wd, n0, k0, bars + 8 * (B5F + st));
                    tma_load_2d(dst + 16384 + 8192, &tm.wd, n0 + 64, k0, bars + 8 * (B5F + st));
                    tma_load_2d(dst + 16384 + 16384, &tm.wd32, n0 + 128, k0, bars + 8 * (B5F + st));
                    if (++st == 5) { st = 0; ph ^= 1; }
                }
            }
        }
        else if (threadIdx.x == 288) {
            mbar_wait(bars + 8 * B1F, 0);
            const char* pw[4] = {(const char*)wo_p, (const char*)wg_p, (const char*)wu_p, (const char*)wd_p};
#pragma unroll 1
            for (int t = 0; t < 4; t++) {
                const uint32_t bytes = t == 0 ? 40960u : 17280u;
                asm volatile("cp.async.bulk.prefetch.L2.global [%0], %1;" ::"l"(pw[t] + (size_t)blockIdx.x * bytes), "r"(bytes) : "memory");
            }
        }
        __syncwarp();
        asm volatile("barrier.cluster.arrive.relaxed.aligned; // producer\n barrier.cluster.wait.aligned;" ::: "memory");
    } else {
        reg_alloc<232>();
        const int tid = threadIdx.x & 127;
        const int warp = tid >> 5, lane = tid & 31;
        const int cw = threadIdx.x >> 5;
        const uint32_t mystage = base + SM_STAGING + wg * 16384;
        auto arrive_both = [&](uint32_t bar) {
            if (tid == 0) mbar_arrive_cluster(bar, 0);
            if (tid == 32) mbar_arrive_cluster(bar, 1);
        };
        TS(0, 0);
        {
            uint2 xr[2][5];
            uint4 w[10];
            unsigned short cr[10];
            const int mb = blockIdx.x < 120 ? blockIdx.x : 0;
#pragma unroll
            for (int i = 0; i < 10; i++) cr[i] = __ldg(reinterpret_cast<const unsigned short*>(cvec) + cw * 80 + i * 8 + (lane >> 2));
#pragma unroll
            for (int i = 0; i < 10; i++)
                w[i] = __ldg(reinterpret_cast<const uint4*>(w_mod + (size_t)(cw * 80 + i * 8 + (lane >> 2)) * (6 * D_MODEL) + mb * 32 + (lane & 3) * 8));
#pragma unroll
            for (int rr = 0; rr < 2; rr++)
#pragma unroll
                for (int i = 0; i < 5; i++)
                    xr[rr][i] = __ldg(reinterpret_cast<const uint2*>(x + (size_t)(m0 + j * 16 + cw * 2 + rr) * D_MODEL + (lane + 32 * i) * 4));
            if (blockIdx.x < 120) {
                float* red = reinterpret_cast<float*>(smem_raw + (base - smem_u32(smem_raw)) + SM_STAGING);
                float acc[8];
#pragma unroll
                for (int i = 0; i < 8; i++) acc[i] = 0.f;
#pragma unroll
                for (int i = 0; i < 10; i++) {
                    const float s = bf16_round(silu_mul(__uint_as_float((uint32_t)cr[i] << 16), 1.f));
                    acc[0] += s * bf16lo(w[i].x); acc[1] += s * bf16hi(w[i].x);
                    acc[2] += s * bf16lo(w[i].y); acc[3] += s * bf16hi(w[i].y);
                    acc[4] += s * bf16lo(w[i].z); acc[5] += s * bf16hi(w[i].z);
                    acc[6] += s * bf16lo(w[i].w); acc[7] += s * bf16hi(w[i].w);
                }
#pragma unroll
                for (int i = 0; i < 8; i++) {
                    acc[i] += __shfl_xor_sync(0xffffffffu, acc[i], 4);
                    acc[i] += __shfl_xor_sync(0xffffffffu, acc[i], 8);
                    acc[i] += __shfl_xor_sync(0xffffffffu, acc[i], 16);
                }
                if (lane < 4) {
#pragma unroll
                    for (int i = 0; i < 8; i++) red[cw * 32 + lane * 8 + i] = acc[i];
                }
                TS(6, 0);
                bar_sync(5, 256);
                TS(6, 1);
                if (threadIdx.x < 32) {
                    float t = 0.f;
#pragma unroll
                    for (int i = 0; i < 8; i++) t += red[i * 32 + threadIdx.x];
                    t = bf16_round(t);
                    const int chunk = blockIdx.x / 20;
                    if (chunk == 1 || chunk == 4) t = bf16_round(1.f + t);
                    g_mod[blockIdx.x * 32 + threadIdx.x] = t;
                    __syncwarp();
                    TS(6, 2);
                    if (threadIdx.x == 0) flag_signal(blockIdx.x < 40 ? F_MODAB : F_MODALL);
                    TS(6, 3);
                }
            }
            if (threadIdx.x == 0) flag_wait(F_MODAB, (epoch + 1) * 40);
            bar_sync(5, 256);
            TS(0, 1);
            ln_rows(xr, g_mod, g_mod + D_MODEL, g_h + (size_t)(m0 + j * 16 + cw * 2) * D_MODEL, lane);
            TS(6, 4);
            bar_sync(5, 256);
            TS(6, 5);
            if (threadIdx.x == 0) flag_signal(F_H + mt);
        }
        TS(0, 2);
        {
            const float cscale = 0.08838834764831845f * 1.4426950408889634f;
            uint32_t st = 0, ph = 0;
            auto wait_full = [&]() -> uint32_t {
                mbar_wait(bars + 8 * (B1F + st), ph);
                return base + st * P1_STAGE;
            };
            auto release = [&](uint32_t s) { arrive_both(bars + 8 * (B1E + s)); };
            auto advance = [&]() { if (++st == 6) { st = 0; ph ^= 1; } };
            auto turn_wait = [&]() { bar_sync(3 + wg, 256); };
            auto turn_pass = [&]() { bar_arrive(3 + (wg ^ 1), 256); };
            if (wg == 1) bar_arrive(3, 256);

            for (int hp = 0; hp < 2; hp++) {
                const int head0 = j * 4 + hp * 2;
                uint32_t q[8][4];
                {
                    float acc[128];
#pragma unroll
                    for (int i = 0; i < 128; i++) acc[i] = 0.f;
                    for (int kk2 = 0; kk2 < 5; kk2++) {
                        const uint32_t hbuf = wait_full();
                        if (kk2 == 0 && hp == 0) TS(0, 3);
                        const uint32_t sth = st;
                        advance();
#pragma unroll
                        for (int u = 0; u < 2; u++) {
                            const uint32_t wbuf = wait_full();
                            const uint32_t stw = st;
                            advance();
                            wgmma_fence();
#pragma unroll
                            for (int k = 0; k < 4; k++) {
                                uint64_t da = make_desc(hbuf + u * 16384 + wg * 8192 + k * 32, 16, 1024, 1);
                                uint64_t db = make_desc(wbuf + k * 2048, 8192, 1024, 1);
                                wgmma_ss_n256_t1(acc, da, db, 1);
                            }
                            wgmma_commit();
                            wgmma_wait<0>();
                            release(stw);
                        }
                        release(sth);
                    }
                    fence_regs(acc);
                    if (tid == 0) tma_store_wait_read<0>();
                    bar_sync(1 + wg, 128);
#pragma unroll
                    for (int i = 0; i < 8; i++) {
                        q[i][0] = pack_bf16(acc[8 * i + 0], acc[8 * i + 1]);
                        q[i][1] = pack_bf16(acc[8 * i + 2], acc[8 * i + 3]);
                        q[i][2] = pack_bf16(acc[8 * i + 4], acc[8 * i + 5]);
                        q[i][3] = pack_bf16(acc[8 * i + 6], acc[8 * i + 7]);
                        uint32_t b0 = pack_bf16(acc[64 + 8 * i + 0], acc[64 + 8 * i + 1]);
                        uint32_t b1 = pack_bf16(acc[64 + 8 * i + 2], acc[64 + 8 * i + 3]);
                        uint32_t b2 = pack_bf16(acc[64 + 8 * i + 4], acc[64 + 8 * i + 5]);
                        uint32_t b3 = pack_bf16(acc[64 + 8 * i + 6], acc[64 + 8 * i + 7]);
                        asm volatile("st.shared.v4.b32 [%0], {%1, %2, %3, %4};" ::"r"(mystage + (i * 128 + tid) * 16), "r"(b0), "r"(b1),
                                     "r"(b2), "r"(b3) : "memory");
                    }
                }
                float o[64], s[64], e[64];
                uint32_t pp[8][4];
                float mm0, mm1, l0, l1, a0, a1, lo0, lo1;
#pragma unroll
                for (int i = 0; i < 64; i++) { o[i] = 0.f; }

                auto issue_s = [&]() -> uint32_t {
                    const uint32_t kbuf = wait_full();
                    const uint32_t stk = st;
                    advance();
                    wgmma_fence();
#pragma unroll
                    for (int k = 0; k < 8; k++) {
                        uint64_t db = make_desc(kbuf + (k >> 2) * 16384 + (k & 3) * 32, 16, 1024, 1);
                        if (k == 0) wgmma_rs_n128_t0_z(s, q[k], db);
                        else wgmma_rs_n128_t0(s, q[k], db, 1);
                    }
                    wgmma_commit();
                    return stk;
                };
                auto issue_pv = [&](bool fresh) -> uint32_t {
                    const uint32_t vbuf = wait_full();
                    const uint32_t stv = st;
                    advance();
                    wgmma_fence();
#pragma unroll
                    for (int k = 0; k < 8; k++) {
                        uint64_t db = make_desc(vbuf + k * 2048, 16384, 1024, 1);
                        wgmma_rs_n128_t1(o, pp[k], db, (!fresh) || k != 0);
                    }
                    wgmma_commit();
                    return stv;
                };
                auto softmax = [&](bool first) {
                    float mx0 = fmaxf(s[0], s[1]), mx1 = fmaxf(s[2], s[3]);
#pragma unroll
                    for (int jj = 1; jj < 16; jj++) {
                        mx0 = fmaxf(mx0, fmaxf(s[4 * jj], s[4 * jj + 1]));
                        mx1 = fmaxf(mx1, fmaxf(s[4 * jj + 2], s[4 * jj + 3]));
                    }
                    mx0 = fmaxf(mx0, __shfl_xor_sync(0xffffffffu, mx0, 1));
                    mx0 = fmaxf(mx0, __shfl_xor_sync(0xffffffffu, mx0, 2));
                    mx1 = fmaxf(mx1, __shfl_xor_sync(0xffffffffu, mx1, 1));
                    mx1 = fmaxf(mx1, __shfl_xor_sync(0xffffffffu, mx1, 2));
                    if (first) {
                        lo0 = l0; lo1 = l1;
                        mm0 = mx0; mm1 = mx1; l0 = 0.f; l1 = 0.f; a0 = 0.f; a1 = 0.f;
                    } else {
                        float mn0 = fmaxf(mm0, mx0), mn1 = fmaxf(mm1, mx1);
                        a0 = ex2((mm0 - mn0) * cscale); a1 = ex2((mm1 - mn1) * cscale);
                        mm0 = mn0; mm1 = mn1;
                    }
                    const float mc0 = mm0 * cscale, mc1 = mm1 * cscale;
                    float r0 = 0.f, r1 = 0.f;
#pragma unroll
                    for (int jj = 0; jj < 16; jj++) {
                        e[4 * jj] = ex2(fmaf(s[4 * jj], cscale, -mc0));
                        e[4 * jj + 1] = ex2(fmaf(s[4 * jj + 1], cscale, -mc0));
                        e[4 * jj + 2] = ex2(fmaf(s[4 * jj + 2], cscale, -mc1));
                        e[4 * jj + 3] = ex2(fmaf(s[4 * jj + 3], cscale, -mc1));
                        r0 += e[4 * jj] + e[4 * jj + 1];
                        r1 += e[4 * jj + 2] + e[4 * jj + 3];
                    }
                    l0 = l0 * a0 + r0; l1 = l1 * a1 + r1;
                };
                auto convert_p = [&]() {
#pragma unroll
                    for (int i = 0; i < 8; i++) {
                        pp[i][0] = pack_bf16(e[8 * i + 0], e[8 * i + 1]);
                        pp[i][1] = pack_bf16(e[8 * i + 2], e[8 * i + 3]);
                        pp[i][2] = pack_bf16(e[8 * i + 4], e[8 * i + 5]);
                        pp[i][3] = pack_bf16(e[8 * i + 6], e[8 * i + 7]);
                    }
                };
                auto store_o = [&](float ls0, float ls1, int head, bool last) {
                    float s0 = ls0 + __shfl_xor_sync(0xffffffffu, ls0, 1); s0 += __shfl_xor_sync(0xffffffffu, s0, 2);
                    float s1 = ls1 + __shfl_xor_sync(0xffffffffu, ls1, 1); s1 += __shfl_xor_sync(0xffffffffu, s1, 2);
                    const float i0 = 1.f / s0, i1 = 1.f / s1;
                    if (tid == 0) {
                        tma_store_wait<0>();
                        if (last) {
                            mbar_arrive_cluster(bars + 8 * BD1A, 0);
                            mbar_arrive_cluster(bars + 8 * BD1A, 1);
                        }
                    }
                    bar_sync(1 + wg, 128);
#pragma unroll
                    for (int jj = 0; jj < 16; jj += 2) {
                        const int mi = lane >> 3;
                        const int row = warp * 16 + (mi & 1) * 8 + (lane & 7);
                        const int grp = jj + (mi >> 1);
                        const uint32_t addr = mystage + (grp >> 3) * 8192 + row * 128 + (((grp & 7) ^ (row & 7)) << 4);
                        stmatrix_x4(addr, pack_bf16(o[4 * jj] * i0, o[4 * jj + 1] * i0), pack_bf16(o[4 * jj + 2] * i1, o[4 * jj + 3] * i1),
                                    pack_bf16(o[4 * jj + 4] * i0, o[4 * jj + 5] * i0), pack_bf16(o[4 * jj + 6] * i1, o[4 * jj + 7] * i1));
                    }
                    fence_proxy_async();
                    bar_sync(1 + wg, 128);
                    if (tid == 0) {
                        tma_store_2d(&tm.o_st, mystage, head * 128, m0 + wg * 64);
                        tma_store_2d(&tm.o_st, mystage + 8192, head * 128 + 64, m0 + wg * 64);
                        tma_store_commit();
                        if (last) {
                            tma_store_wait<0>();
                            mbar_arrive_cluster(bars + 8 * BD1, 0);
                            mbar_arrive_cluster(bars + 8 * BD1, 1);
                            flag_signal_relaxed(F_O + mt * 4 + (j >> 1));
                        }
                    }
                };

                l0 = 0.f; l1 = 0.f;
                {
                    turn_wait();
                    uint32_t stk = issue_s();
                    turn_pass();
                    wgmma_wait<0>();
                    fence_regs(s);
                    release(stk);
                    softmax(true);
                    convert_p();
                }
#pragma unroll 1
                for (int t = 1; t < 8; t++) {
                    const bool first = (t == 4);
                    if (t == 4) {
#pragma unroll
                        for (int i = 0; i < 8; i++) {
                            asm volatile("ld.shared.v4.b32 {%0, %1, %2, %3}, [%4];" : "=r"(q[i][0]), "=r"(q[i][1]), "=r"(q[i][2]), "=r"(q[i][3])
                                         : "r"(mystage + (i * 128 + tid) * 16) : "memory");
                        }
                    }
                    turn_wait();
                    uint32_t stk = issue_s();
                    uint32_t stv = issue_pv(t == 1 || t == 5);
                    turn_pass();
                    wgmma_wait<1>();
                    fence_regs(s);
                    release(stk);
                    softmax(first);
                    asm volatile("{\n.reg .pred p;\nsetp.lt.f32 p, %0, 0fBF800000;\n@p st.shared.f32 [%1], %0;\n}\n" ::"f"(l0 + l1), "r"(mystage) : "memory");
                    wgmma_wait<0>();
                    fence_regs(o);
                    release(stv);
                    if (first) {
                        store_o(lo0, lo1, head0, false);
                    } else {
#pragma unroll
                        for (int jj = 0; jj < 16; jj++) {
                            o[4 * jj] *= a0; o[4 * jj + 1] *= a0; o[4 * jj + 2] *= a1; o[4 * jj + 3] *= a1;
                        }
                    }
                    convert_p();
                }
                {
                    turn_wait();
                    uint32_t stv = issue_pv(false);
                    turn_pass();
                    wgmma_wait<0>();
                    fence_regs(o);
                    release(stv);
                    store_o(l0, l1, head0 + 1, hp == 1);
                }
            }
        }
        TS(0, 4);
        {
            const int kq = j >> 1, n0 = (j & 1) * 320;
            float acc0[96], acc1[64];
#pragma unroll
            for (int i = 0; i < 96; i++) acc0[i] = 0.f;
#pragma unroll
            for (int i = 0; i < 64; i++) acc1[i] = 0.f;
            uint32_t st = 0, ph = 0, prev = 0;
            for (int i = 0; i < 16; i++) {
                mbar_wait(bars + 8 * (B2F + st), ph);
                if (i == 0) TS(0, 5);
                const uint32_t buf = base + st * P2_STAGE;
                wgmma_fence();
#pragma unroll
                for (int k = 0; k < 4; k++) {
                    uint64_t da = make_desc(buf + wg * 8192 + k * 32, 16, 1024, 1);
                    wgmma_ss_n192_t1(acc0, da, make_desc(buf + 16384 + k * 2048, 8192, 1024, 1), 1);
                    wgmma_ss_n128_t1(acc1, da, make_desc(buf + 16384 + 3 * 8192 + k * 2048, 8192, 1024, 1), 1);
                }
                wgmma_commit();
                if (i > 0) { wgmma_wait<1>(); arrive_both(bars + 8 * (B2E + prev)); }
                prev = st;
                if (++st == 4) { st = 0; ph ^= 1; }
            }
            wgmma_wait<0>();
            fence_regs(acc0); fence_regs(acc1);
            TS(0, 6);
            bar_sync(5, 256);
            TS(4, 0);
            const uint32_t stg = base + wg * 40960;
            const int mi = lane >> 3;
            const int row = warp * 16 + (mi & 1) * 8 + (lane & 7);
#pragma unroll
            for (int jj = 0; jj < 24; jj += 2) {
                const int grp = jj + (mi >> 1);
                stmatrix_x4(stg + (grp >> 3) * 8192 + row * 128 + (((grp & 7) ^ (row & 7)) << 4),
                            pack_bf16(acc0[4 * jj], acc0[4 * jj + 1]), pack_bf16(acc0[4 * jj + 2], acc0[4 * jj + 3]),
                            pack_bf16(acc0[4 * jj + 4], acc0[4 * jj + 5]), pack_bf16(acc0[4 * jj + 6], acc0[4 * jj + 7]));
            }
#pragma unroll
            for (int jj = 0; jj < 16; jj += 2) {
                const int grp = jj + (mi >> 1);
                stmatrix_x4(stg + (3 + (grp >> 3)) * 8192 + row * 128 + (((grp & 7) ^ (row & 7)) << 4),
                            pack_bf16(acc1[4 * jj], acc1[4 * jj + 1]), pack_bf16(acc1[4 * jj + 2], acc1[4 * jj + 3]),
                            pack_bf16(acc1[4 * jj + 4], acc1[4 * jj + 5]), pack_bf16(acc1[4 * jj + 6], acc1[4 * jj + 7]));
            }
            TS(4, 1);
            fence_proxy_async();
            bar_sync(1 + wg, 128);
            TS(4, 2);
            if (tid == 0) {
#pragma unroll
                for (int c = 0; c < 5; c++) tma_store_2d(&tm.part_st, stg + c * 8192, n0 + c * 64, kq * S_LEN + m0 + wg * 64);
                tma_store_commit();
                TS(4, 3);
                tma_store_wait<0>();
                TS(4, 4);
                mbar_arrive_cluster(bars + 8 * BD2, 0);
                mbar_arrive_cluster(bars + 8 * BD2, 1);
                flag_signal_relaxed(F_P + mt);
            }
        }
        TS(0, 7);
        {
            uint2 xr[2][5];
#pragma unroll
            for (int rr = 0; rr < 2; rr++)
#pragma unroll
                for (int i = 0; i < 5; i++)
                    xr[rr][i] = __ldg(reinterpret_cast<const uint2*>(x + (size_t)(m0 + j * 16 + cw * 2 + rr) * D_MODEL + (lane + 32 * i) * 4));
            if (threadIdx.x == 0) { flag_wait(F_MODALL, (epoch + 1) * 80); flag_wait(F_P + mt, (epoch + 1) * 16); }
            bar_sync(5, 256);
            TS(0, 8);
            uint2 pr[2][4][5];
            float4 gv[5];
#pragma unroll
            for (int rr = 0; rr < 2; rr++)
#pragma unroll
                for (int s = 0; s < 4; s++)
#pragma unroll
                    for (int i = 0; i < 5; i++)
                        pr[rr][s][i] = ldcg_u2(g_part + ((size_t)s * S_LEN + m0 + j * 16 + cw * 2 + rr) * D_MODEL + (lane + 32 * i) * 4);
#pragma unroll
            for (int i = 0; i < 5; i++) gv[i] = __ldcg(reinterpret_cast<const float4*>(g_mod + 2 * D_MODEL + (lane + 32 * i) * 4));
#pragma unroll
            for (int rr = 0; rr < 2; rr++) {
#pragma unroll
                for (int i = 0; i < 5; i++) {
                    float a0 = (bf16lo(pr[rr][0][i].x) + bf16lo(pr[rr][1][i].x)) + (bf16lo(pr[rr][2][i].x) + bf16lo(pr[rr][3][i].x));
                    float a1 = (bf16hi(pr[rr][0][i].x) + bf16hi(pr[rr][1][i].x)) + (bf16hi(pr[rr][2][i].x) + bf16hi(pr[rr][3][i].x));
                    float a2 = (bf16lo(pr[rr][0][i].y) + bf16lo(pr[rr][1][i].y)) + (bf16lo(pr[rr][2][i].y) + bf16lo(pr[rr][3][i].y));
                    float a3 = (bf16hi(pr[rr][0][i].y) + bf16hi(pr[rr][1][i].y)) + (bf16hi(pr[rr][2][i].y) + bf16hi(pr[rr][3][i].y));
                    xr[rr][i].x = pack_bf16(bf16lo(xr[rr][i].x) + gv[i].x * a0, bf16hi(xr[rr][i].x) + gv[i].y * a1);
                    xr[rr][i].y = pack_bf16(bf16lo(xr[rr][i].y) + gv[i].z * a2, bf16hi(xr[rr][i].y) + gv[i].w * a3);
                    *reinterpret_cast<uint2*>(g_x1 + (size_t)(m0 + j * 16 + cw * 2 + rr) * D_MODEL + (lane + 32 * i) * 4) = xr[rr][i];
                }
            }
            TS(5, 0);
            ln_rows(xr, g_mod + 3 * D_MODEL, g_mod + 4 * D_MODEL, g_h2 + (size_t)(m0 + j * 16 + cw * 2) * D_MODEL, lane);
            TS(5, 1);
            bar_sync(5, 256);
            TS(5, 2);
            if (threadIdx.x == 0) flag_signal(F_H2 + mt);
        }
        TS(0, 9);
        {
            const int f0 = j * 216;
            uint32_t st = 0, ph = 0, prev = 0;
            {
                float acc[128];
#pragma unroll
                for (int i = 0; i < 128; i++) acc[i] = 0.f;
                if (wg == 1) bar_sync(6, 256);
                for (int i = 0; i < 10; i++) {
                    mbar_wait(bars + 8 * (B4F + st), ph);
                    if (i == 0) TS(0, 10);
                    const uint32_t buf = base + st * P4_STAGE;
                    wgmma_fence();
#pragma unroll
                    for (int k = 0; k < 4; k++) {
                        uint64_t da = make_desc(buf + wg * 8192 + k * 32, 16, 1024, 1);
                        uint64_t db = make_desc(buf + 16384 + k * 2048, 8192, 1024, 1);
                        wgmma_ss_n256_t1(acc, da, db, 1);
                    }
                    wgmma_commit();
                    if (i == 1 && wg == 0) bar_arrive(6, 256);
                    if (i > 0) { wgmma_wait<1>(); arrive_both(bars + 8 * (B4E + prev)); }
                    prev = st;
                    if (++st == 4) { st = 0; ph ^= 1; }
                }
                wgmma_wait<0>();
                arrive_both(bars + 8 * (B4E + prev));
                fence_regs(acc);
                TS(2, 0);
#pragma unroll
                for (int jj = 0; jj < 16; jj += 2) {
                    const int mi = lane >> 3;
                    const int row = warp * 16 + (mi & 1) * 8 + (lane & 7);
                    const int grp = jj + (mi >> 1);
                    const uint32_t addr = mystage + (grp >> 3) * 8192 + row * 128 + (((grp & 7) ^ (row & 7)) << 4);
                    stmatrix_x4(addr, pack_bf16(silu_mul(acc[4 * jj], acc[64 + 4 * jj]), silu_mul(acc[4 * jj + 1], acc[64 + 4 * jj + 1])),
                                pack_bf16(silu_mul(acc[4 * jj + 2], acc[64 + 4 * jj + 2]), silu_mul(acc[4 * jj + 3], acc[64 + 4 * jj + 3])),
                                pack_bf16(silu_mul(acc[4 * jj + 4], acc[64 + 4 * jj + 4]), silu_mul(acc[4 * jj + 5], acc[64 + 4 * jj + 5])),
                                pack_bf16(silu_mul(acc[4 * jj + 6], acc[64 + 4 * jj + 6]), silu_mul(acc[4 * jj + 7], acc[64 + 4 * jj + 7])));
                }
                fence_proxy_async();
                bar_sync(1 + wg, 128);
                TS(2, 1);
                if (tid == 0) {
                    tma_store_2d(&tm.act_st64, mystage, f0, m0 + wg * 64);
                    tma_store_2d(&tm.act_st64, mystage + 8192, f0 + 64, m0 + wg * 64);
                    tma_store_commit();
                }
                TS(2, 2);
            }
            {
                float acc[92];
#pragma unroll
                for (int i = 0; i < 92; i++) acc[i] = 0.f;
                for (int i = 0; i < 10; i++) {
                    mbar_wait(bars + 8 * (B4F + st), ph);
                    const uint32_t buf = base + st * P4_STAGE;
                    wgmma_fence();
#pragma unroll
                    for (int k = 0; k < 4; k++) {
                        uint64_t da = make_desc(buf + wg * 8192 + k * 32, 16, 1024, 1);
                        uint64_t db = make_desc(buf + 16384 + k * 1024, 4096, 512, 2);
                        wgmma_ss_n184_t1(acc, da, db, 1);
                    }
                    wgmma_commit();
                    if (i > 0) { wgmma_wait<1>(); arrive_both(bars + 8 * (B4E + prev)); }
                    prev = st;
                    if (++st == 4) { st = 0; ph ^= 1; }
                }
                wgmma_wait<0>();
                fence_regs(acc);
                TS(0, 11);
                if (tid == 0) tma_store_wait_read<0>();
                bar_sync(1 + wg, 128);
                TS(2, 3);
#pragma unroll
                for (int jj = 0; jj < 8; jj += 2) {
                    const int mi = lane >> 3;
                    const int row = warp * 16 + (mi & 1) * 8 + (lane & 7);
                    const int grp = jj + (mi >> 1);
                    const uint32_t addr = mystage + row * 128 + ((grp ^ (row & 7)) << 4);
                    stmatrix_x4(addr, pack_bf16(silu_mul(acc[4 * jj], acc[48 + 4 * jj]), silu_mul(acc[4 * jj + 1], acc[48 + 4 * jj + 1])),
                                pack_bf16(silu_mul(acc[4 * jj + 2], acc[48 + 4 * jj + 2]), silu_mul(acc[4 * jj + 3], acc[48 + 4 * jj + 3])),
                                pack_bf16(silu_mul(acc[4 * jj + 4], acc[48 + 4 * jj + 4]), silu_mul(acc[4 * jj + 5], acc[48 + 4 * jj + 5])),
                                pack_bf16(silu_mul(acc[4 * jj + 6], acc[48 + 4 * jj + 6]), silu_mul(acc[4 * jj + 7], acc[48 + 4 * jj + 7])));
                }
                {
                    const int mi = lane >> 3;
                    const int row = warp * 16 + (mi & 1) * 8 + (lane & 7);
                    const uint32_t addr = mystage + 8192 + row * 48 + (mi >> 1) * 16;
                    stmatrix_x4(addr, pack_bf16(silu_mul(acc[32], acc[80]), silu_mul(acc[33], acc[81])),
                                pack_bf16(silu_mul(acc[34], acc[82]), silu_mul(acc[35], acc[83])),
                                pack_bf16(silu_mul(acc[36], acc[84]), silu_mul(acc[37], acc[85])),
                                pack_bf16(silu_mul(acc[38], acc[86]), silu_mul(acc[39], acc[87])));
                    const uint32_t addr2 = mystage + 8192 + (warp * 16 + ((lane >> 3) & 1) * 8 + (lane & 7)) * 48 + 32;
                    asm volatile("stmatrix.sync.aligned.m8n8.x2.shared.b16 [%0], {%1, %2};" ::"r"(addr2),
                                 "r"(pack_bf16(silu_mul(acc[40], acc[88]), silu_mul(acc[41], acc[89]))),
                                 "r"(pack_bf16(silu_mul(acc[42], acc[90]), silu_mul(acc[43], acc[91]))) : "memory");
                }
                fence_proxy_async();
                bar_sync(1 + wg, 128);
                TS(2, 4);
                if (tid == 0) {
                    tma_store_2d(&tm.act_st64, mystage, f0 + 128, m0 + wg * 64);
                    tma_store_2d(&tm.act_st24, mystage + 8192, f0 + 192, m0 + wg * 64);
                    tma_store_commit();
                    TS(2, 5);
                    tma_store_wait<0>();
                    TS(2, 6);
                    mbar_arrive_cluster(bars + 8 * BD4, 0);
                    mbar_arrive_cluster(bars + 8 * BD4, 1);
                    TS(2, 7);
                    flag_signal_relaxed(F_A + mt);
                    TS(2, 8);
                }
            }
        }
        TS(0, 12);
        {
            const int m5 = (p * 2 + (j >> 2)) * 128, n0 = (j & 3) * 160;
            const int nkb = rank == 0 ? 14 : 13;
            float accA[64], accB[16];
#pragma unroll
            for (int i = 0; i < 64; i++) accA[i] = 0.f;
#pragma unroll
            for (int i = 0; i < 16; i++) accB[i] = 0.f;
            uint32_t st = 0, ph = 0, prev = 0;
            const int cbase = n0 + (int)rank * 80;
            for (int i = 0; i < nkb; i++) {
                mbar_wait(bars + 8 * (B5F + st), ph);
                if (i == 0) TS(0, 13);
                const uint32_t buf = base + st * P5_STAGE;
                wgmma_fence();
#pragma unroll
                for (int k = 0; k < 4; k++) {
                    uint64_t da = make_desc(buf + wg * 8192 + k * 32, 16, 1024, 1);
                    wgmma_ss_n128_t1(accA, da, make_desc(buf + 16384 + k * 2048, 8192, 1024, 1), 1);
                    wgmma_ss_n32_t1(accB, da, make_desc(buf + 32768 + k * 1024, 4096, 512, 2), 1);
                }
                wgmma_commit();
                if (i > 0) {
                    wgmma_wait<1>();
                    if (tid == 0) mbar_arrive(bars + 8 * (B5E + prev));
                }
                prev = st;
                if (++st == 5) { st = 0; ph ^= 1; }
            }
            uint4 xv[5];
            float2 gbv[10];
#pragma unroll
            for (int it = 0; it < 5; it++) {
                const int idx = it * 256 + (int)threadIdx.x;
                const int row = idx / 10, ch = idx - row * 10;
                xv[it] = __ldcg(reinterpret_cast<const uint4*>(g_x1 + (size_t)(m5 + row) * D_MODEL + cbase + ch * 8));
            }
#pragma unroll
            for (int jj = 0; jj < 10; jj++) gbv[jj] = __ldcg(reinterpret_cast<const float2*>(g_mod + 5 * D_MODEL + cbase + jj * 8 + (lane & 3) * 2));
            wgmma_wait<0>();
            fence_regs(accA); fence_regs(accB);
            float acc[80];
#pragma unroll
            for (int i = 0; i < 64; i++) acc[i] = accA[i];
#pragma unroll
            for (int i = 0; i < 16; i++) acc[64 + i] = accB[i];
            TS(0, 14);
            constexpr uint32_t XBUF = 5 * P5_STAGE;
            {
                const uint32_t dst = mapa(base + XBUF, rank ^ 1) + wg * 20480 + tid * 16;
                const uint32_t rbar = mapa(bars + 8 * BX, rank ^ 1);
                if (rank == 0) {
#pragma unroll
                    for (int i = 0; i < 10; i++)
                        asm volatile("st.async.shared::cluster.mbarrier::complete_tx::bytes.v4.f32 [%0], {%1, %2, %3, %4}, [%5];" ::"r"(dst + i * 2048),
                                     "f"(acc[40 + 4 * i]), "f"(acc[40 + 4 * i + 1]), "f"(acc[40 + 4 * i + 2]), "f"(acc[40 + 4 * i + 3]), "r"(rbar) : "memory");
                } else {
#pragma unroll
                    for (int i = 0; i < 10; i++)
                        asm volatile("st.async.shared::cluster.mbarrier::complete_tx::bytes.v4.f32 [%0], {%1, %2, %3, %4}, [%5];" ::"r"(dst + i * 2048),
                                     "f"(acc[4 * i]), "f"(acc[4 * i + 1]), "f"(acc[4 * i + 2]), "f"(acc[4 * i + 3]), "r"(rbar) : "memory");
                }
            }
            mbar_wait(bars + 8 * BX, 0);
            {
                bar_sync(5, 256);
                const uint32_t tile = base;
#pragma unroll
                for (int jj = 0; jj < 10; jj += 2) {
                    float4 o0, o1;
                    asm volatile("ld.shared.v4.f32 {%0, %1, %2, %3}, [%4];" : "=f"(o0.x), "=f"(o0.y), "=f"(o0.z), "=f"(o0.w) : "r"(base + XBUF + wg * 20480 + tid * 16 + jj * 2048));
                    asm volatile("ld.shared.v4.f32 {%0, %1, %2, %3}, [%4];" : "=f"(o1.x), "=f"(o1.y), "=f"(o1.z), "=f"(o1.w) : "r"(base + XBUF + wg * 20480 + tid * 16 + (jj + 1) * 2048));
                    const float2 g0 = gbv[jj], g1 = gbv[jj + 1];
                    float a[8];
#pragma unroll
                    for (int ee = 0; ee < 8; ee++) a[ee] = rank == 0 ? acc[4 * jj + ee] : acc[40 + 4 * jj + ee];
                    const int mi = lane >> 3;
                    const int row = wg * 64 + warp * 16 + (mi & 1) * 8 + (lane & 7);
                    const uint32_t addr = tile + row * 176 + (jj + (mi >> 1)) * 16;
                    stmatrix_x4(addr, pack_bf16(g0.x * bf16_round(a[0] + o0.x), g0.y * bf16_round(a[1] + o0.y)),
                                pack_bf16(g0.x * bf16_round(a[2] + o0.z), g0.y * bf16_round(a[3] + o0.w)),
                                pack_bf16(g1.x * bf16_round(a[4] + o1.x), g1.y * bf16_round(a[5] + o1.y)),
                                pack_bf16(g1.x * bf16_round(a[6] + o1.z), g1.y * bf16_round(a[7] + o1.w)));
                }
                bar_sync(5, 256);
#pragma unroll
                for (int it = 0; it < 5; it++) {
                    const int idx = it * 256 + (int)threadIdx.x;
                    const int row = idx / 10, ch = idx - row * 10;
                    uint4 tv;
                    asm volatile("ld.shared.v4.b32 {%0, %1, %2, %3}, [%4];" : "=r"(tv.x), "=r"(tv.y), "=r"(tv.z), "=r"(tv.w) : "r"(tile + row * 176 + ch * 16));
                    uint4 r;
                    r.x = pack_bf16(bf16lo(xv[it].x) + bf16lo(tv.x), bf16hi(xv[it].x) + bf16hi(tv.x));
                    r.y = pack_bf16(bf16lo(xv[it].y) + bf16lo(tv.y), bf16hi(xv[it].y) + bf16hi(tv.y));
                    r.z = pack_bf16(bf16lo(xv[it].z) + bf16lo(tv.z), bf16hi(xv[it].z) + bf16hi(tv.z));
                    r.w = pack_bf16(bf16lo(xv[it].w) + bf16lo(tv.w), bf16hi(xv[it].w) + bf16hi(tv.w));
                    *reinterpret_cast<uint4*>(out + (size_t)(m5 + row) * D_MODEL + cbase + ch * 8) = r;
                }
            }
            TS(0, 15);
            if (threadIdx.x == 0) {
                const unsigned old = atomicAdd(&g_exit, 1u);
                if (old == (epoch + 1) * 128u - 1u) {
                    asm volatile("st.volatile.global.u32 [%0], %1;" ::"l"(&g_epoch), "r"(epoch + 1) : "memory");
                }
            }
            asm volatile("barrier.cluster.arrive.relaxed.aligned;\n barrier.cluster.wait.aligned;" ::: "memory");
        }
    }
}

typedef CUresult (*PFN_encodeTiled)(CUtensorMap*, CUtensorMapDataType, cuuint32_t, void*, const cuuint64_t*, const cuuint64_t*,
                                    const cuuint32_t*, const cuuint32_t*, CUtensorMapInterleave, CUtensorMapSwizzle,
                                    CUtensorMapL2promotion, CUtensorMapFloatOOBfill);

static PFN_encodeTiled get_encode() {
    static PFN_encodeTiled fn = nullptr;
    if (!fn) {
        void* p = nullptr;
        cudaDriverEntryPointQueryResult qr;
        cudaGetDriverEntryPoint("cuTensorMapEncodeTiled", &p, cudaEnableDefault, &qr);
        fn = (PFN_encodeTiled)p;
    }
    return fn;
}

static CUtensorMap make_map(const void* ptr, uint64_t rows, uint64_t cols, uint32_t box_rows, uint32_t box_cols, CUtensorMapSwizzle swz) {
    CUtensorMap m;
    cuuint64_t dims[2] = {cols, rows};
    cuuint64_t strides[1] = {cols * 2};
    cuuint32_t box[2] = {box_cols, box_rows};
    cuuint32_t es[2] = {1, 1};
    get_encode()(&m, CU_TENSOR_MAP_DATA_TYPE_BFLOAT16, 2, const_cast<void*>(ptr), dims, strides, box, es, CU_TENSOR_MAP_INTERLEAVE_NONE,
                 swz, CU_TENSOR_MAP_L2_PROMOTION_L2_256B, CU_TENSOR_MAP_FLOAT_OOB_FILL_NONE);
    return m;
}

extern "C" void kernel_launch(void* const* d_in, const int* in_sizes, int n_in, void* d_out, int out_size) {
    (void)in_sizes; (void)n_in; (void)out_size;
    const __nv_bfloat16* x = (const __nv_bfloat16*)d_in[0];
    const __nv_bfloat16* kc = (const __nv_bfloat16*)d_in[1];
    const __nv_bfloat16* vc = (const __nv_bfloat16*)d_in[2];
    const __nv_bfloat16* wq = (const __nv_bfloat16*)d_in[3];
    const __nv_bfloat16* wo = (const __nv_bfloat16*)d_in[4];
    const __nv_bfloat16* wg = (const __nv_bfloat16*)d_in[6];
    const __nv_bfloat16* wu = (const __nv_bfloat16*)d_in[7];
    const __nv_bfloat16* wd = (const __nv_bfloat16*)d_in[8];
    const __nv_bfloat16* c = (const __nv_bfloat16*)d_in[9];
    const __nv_bfloat16* wmod = (const __nv_bfloat16*)d_in[10];
    __nv_bfloat16* out = (__nv_bfloat16*)d_out;

    static bool init = false;
    static void *p_h, *p_o, *p_x1, *p_h2, *p_act, *p_part;
    if (!init) {
        cudaFuncSetAttribute(mega_kernel, cudaFuncAttributeMaxDynamicSharedMemorySize, SM_TOTAL);
        cudaGetSymbolAddress(&p_h, g_h);
        cudaGetSymbolAddress(&p_o, g_o);
        cudaGetSymbolAddress(&p_x1, g_x1);
        cudaGetSymbolAddress(&p_h2, g_h2);
        cudaGetSymbolAddress(&p_act, g_act);
        cudaGetSymbolAddress(&p_part, g_part);
        init = true;
    }
    const CUtensorMapSwizzle S128 = CU_TENSOR_MAP_SWIZZLE_128B, S64 = CU_TENSOR_MAP_SWIZZLE_64B;
    Maps tm;
    tm.h = make_map(p_h, S_LEN, D_MODEL, 128, 64, S128);
    tm.wq = make_map(wq, D_MODEL, N_HEADS * D_HEAD, 64, 64, S128);
    tm.k = make_map(kc, N_HEADS * S_KV, D_HEAD, 128, 64, S128);
    tm.v = make_map(vc, N_HEADS * S_KV, D_HEAD, 128, 64, S128);
    tm.o_st = make_map(p_o, S_LEN, N_HEADS * D_HEAD, 64, 64, S128);
    tm.o_a = make_map(p_o, S_LEN, N_HEADS * D_HEAD, 128, 64, S128);
    tm.wo = make_map(wo, N_HEADS * D_HEAD, D_MODEL, 64, 64, S128);
    tm.part_st = make_map(p_part, 4 * S_LEN, D_MODEL, 64, 64, S128);
    tm.h2 = make_map(p_h2, S_LEN, D_MODEL, 128, 64, S128);
    tm.g128 = make_map(wg, D_MODEL, D_FF, 64, 64, S128);
    tm.u128 = make_map(wu, D_MODEL, D_FF, 64, 64, S128);
    tm.g64 = make_map(wg, D_MODEL, D_FF, 64, 32, S64);
    tm.u64 = make_map(wu, D_MODEL, D_FF, 64, 32, S64);
    tm.act_st64 = make_map(p_act, S_LEN, D_FF, 64, 64, S128);
    tm.act_st24 = make_map(p_act, S_LEN, D_FF, 64, 24, CU_TENSOR_MAP_SWIZZLE_NONE);
    tm.act_a = make_map(p_act, S_LEN, D_FF, 128, 64, S128);
    tm.wd = make_map(wd, D_FF, D_MODEL, 64, 64, S128);
    tm.wd32 = make_map(wd, D_FF, D_MODEL, 64, 32, S64);

    cudaLaunchConfig_t cfg = {};
    cfg.gridDim = dim3(128);
    cfg.blockDim = dim3(384);
    cfg.dynamicSmemBytes = SM_TOTAL;
    cfg.stream = cudaStreamPerThread;
    cfg.attrs = nullptr;
    cfg.numAttrs = 0;
    cudaLaunchKernelEx(&cfg, mega_kernel, tm, x, c, wmod, out, (const void*)wo, (const void*)wg, (const void*)wu, (const void*)wd);
}
```

```cpp
#include <cuda_runtime.h>
#include <cuda_bf16.h>
#include <cuda.h>
#include <stdint.h>

__device__ __forceinline__ uint32_t smem_u32(const void* p) { return (uint32_t)__cvta_generic_to_shared(p); }

__device__ __forceinline__ void mbar_init(uint32_t bar, uint32_t count) {
    asm volatile("mbarrier.init.shared::cta.b64 [%0], %1;" ::"r"(bar), "r"(count) : "memory");
}
__device__ __forceinline__ void mbar_expect_tx(uint32_t bar, uint32_t bytes) {
    asm volatile("mbarrier.arrive.expect_tx.shared::cta.b64 _, [%0], %1;" ::"r"(bar), "r"(bytes) : "memory");
}
__device__ __forceinline__ void mbar_arrive(uint32_t bar) {
    asm volatile("mbarrier.arrive.shared::cta.b64 _, [%0];" ::"r"(bar) : "memory");
}
__device__ __forceinline__ void mbar_arrive_cluster(uint32_t bar, uint32_t cta) {
    asm volatile(
        "{\n.reg .b32 ra;\n"
        "mapa.shared::cluster.u32 ra, %0, %1;\n"
        "mbarrier.arrive.shared::cluster.b64 _, [ra];\n}\n" ::"r"(bar), "r"(cta)
        : "memory");
}
__device__ __forceinline__ bool mbar_try_wait(uint32_t bar, uint32_t parity) {
    uint32_t ok;
    asm volatile(
        "{\n.reg .pred p;\n"
        "mbarrier.try_wait.parity.shared::cta.b64 p, [%1], %2;\n"
        "selp.u32 %0, 1, 0, p;\n}\n"
        : "=r"(ok)
        : "r"(bar), "r"(parity)
        : "memory");
    return ok != 0;
}
__device__ __forceinline__ bool mbar_try_wait_cluster(uint32_t bar, uint32_t parity) {
    uint32_t ok;
    asm volatile(
        "{\n.reg .pred p;\n"
        "mbarrier.try_wait.parity.shared::cta.b64 p, [%1], %2;\n"
        "selp.u32 %0, 1, 0, p;\n}\n"
        : "=r"(ok)
        : "r"(bar), "r"(parity)
        : "memory");
    return ok != 0;
}
__device__ volatile int g_abort = 0;
__device__ __forceinline__ void mbar_wait(uint32_t bar, uint32_t parity) {
    uint32_t n = 0;
    while (!mbar_try_wait(bar, parity)) {
        if ((++n & 0x3fffu) == 0) {
            if (n > (1u << 26)) g_abort = 1;
            if (g_abort) break;
        }
    }
}
__device__ __forceinline__ void mbar_wait_cluster(uint32_t bar, uint32_t parity) { mbar_wait(bar, parity); }
__device__ __forceinline__ void fence_mbar_init() { asm volatile("fence.mbarrier_init.release.cluster;" ::: "memory"); }
__device__ __forceinline__ void fence_proxy_async() { asm volatile("fence.proxy.async.shared::cta;" ::: "memory"); }
__device__ __forceinline__ void fence_proxy_async_all() { asm volatile("fence.proxy.async;" ::: "memory"); }
__device__ __forceinline__ void cluster_arrive() { asm volatile("barrier.cluster.arrive.release.aligned;" ::: "memory"); }
__device__ __forceinline__ void cluster_wait() { asm volatile("barrier.cluster.wait.acquire.aligned;" ::: "memory"); }
__device__ __forceinline__ void cluster_sync() { cluster_arrive(); cluster_wait(); }
__device__ __forceinline__ uint32_t cluster_ctarank() {
    uint32_t r;
    asm volatile("mov.u32 %0, %%cluster_ctarank;" : "=r"(r));
    return r;
}
__device__ __forceinline__ void bar_sync(int id, int n) { asm volatile("bar.sync %0, %1;" ::"r"(id), "r"(n) : "memory"); }
__device__ __forceinline__ void bar_arrive(int id, int n) { asm volatile("bar.arrive %0, %1;" ::"r"(id), "r"(n) : "memory"); }
__device__ __forceinline__ void pdl_wait() { asm volatile("griddepcontrol.wait;" ::: "memory"); }
__device__ __forceinline__ void pdl_launch() { asm volatile("griddepcontrol.launch_dependents;" ::: "memory"); }

__device__ __forceinline__ void tma_prefetch_desc(const CUtensorMap* m) {
    asm volatile("prefetch.tensormap [%0];" ::"l"(m) : "memory");
}
__device__ __forceinline__ void tma_load_2d(uint32_t dst, const CUtensorMap* m, int c0, int c1, uint32_t bar) {
    asm volatile(
        "cp.async.bulk.tensor.2d.shared::cluster.global.mbarrier::complete_tx::bytes [%0], [%1, {%3, %4}], [%2];"
        ::"r"(dst), "l"(m), "r"(bar), "r"(c0), "r"(c1)
        : "memory");
}
__device__ __forceinline__ void tma_load_2d_mc(uint32_t dst, const CUtensorMap* m, int c0, int c1, uint32_t bar, uint16_t mask) {
    asm volatile(
        "cp.async.bulk.tensor.2d.shared::cluster.global.mbarrier::complete_tx::bytes.multicast::cluster [%0], [%1, {%3, %4}], [%2], %5;"
        ::"r"(dst), "l"(m), "r"(bar), "r"(c0), "r"(c1), "h"(mask)
        : "memory");
}
__device__ __forceinline__ void tma_store_2d(const CUtensorMap* m, uint32_t src, int c0, int c1) {
    asm volatile("cp.async.bulk.tensor.2d.global.shared::cta.bulk_group [%0, {%2, %3}], [%1];"
                 ::"l"(m), "r"(src), "r"(c0), "r"(c1)
                 : "memory");
}
__device__ __forceinline__ void tma_store_commit() { asm volatile("cp.async.bulk.commit_group;" ::: "memory"); }
template <int N> __device__ __forceinline__ void tma_store_wait_read() {
    asm volatile("cp.async.bulk.wait_group.read %0;" ::"n"(N) : "memory");
}
template <int N> __device__ __forceinline__ void tma_store_wait() {
    asm volatile("cp.async.bulk.wait_group %0;" ::"n"(N) : "memory");
}

__device__ __forceinline__ void wgmma_fence() { asm volatile("wgmma.fence.sync.aligned;" ::: "memory"); }
__device__ __forceinline__ void wgmma_commit() { asm volatile("wgmma.commit_group.sync.aligned;" ::: "memory"); }
template <int N> __device__ __forceinline__ void wgmma_wait() {
    asm volatile("wgmma.wait_group.sync.aligned %0;" ::"n"(N) : "memory");
}
template <int R> __device__ __forceinline__ void reg_alloc() { asm volatile("setmaxnreg.inc.sync.aligned.u32 %0;" ::"n"(R)); }
template <int R> __device__ __forceinline__ void reg_dealloc() { asm volatile("setmaxnreg.dec.sync.aligned.u32 %0;" ::"n"(R)); }

template <int N> __device__ __forceinline__ void fence_regs(float (&r)[N]) {
#pragma unroll
    for (int i = 0; i < N; i++) asm volatile("" : "+f"(r[i])::"memory");
}
template <int N> __device__ __forceinline__ void fence_regs_u(uint32_t (&r)[N][4]) {
#pragma unroll
    for (int i = 0; i < N; i++) {
#pragma unroll
        for (int j = 0; j < 4; j++) asm volatile("" : "+r"(r[i][j])::"memory");
    }
}

__device__ __forceinline__ uint64_t make_desc(uint32_t addr, uint32_t lbo_bytes, uint32_t sbo_bytes, uint32_t swz) {
    return (uint64_t)((addr & 0x3FFFF) >> 4) | ((uint64_t)(lbo_bytes >> 4) << 16) | ((uint64_t)(sbo_bytes >> 4) << 32) |
           ((uint64_t)swz << 62);
}

__device__ __forceinline__ uint32_t pack_bf16(float lo, float hi) {
    uint32_t r;
    asm("cvt.rn.bf16x2.f32 %0, %1, %2;" : "=r"(r) : "f"(hi), "f"(lo));
    return r;
}
__device__ __forceinline__ float bf16_round(float x) { return __bfloat162float(__float2bfloat16_rn(x)); }
__device__ __forceinline__ float bf16lo(uint32_t v) { return __uint_as_float(v << 16); }
__device__ __forceinline__ float bf16hi(uint32_t v) { return __uint_as_float(v & 0xffff0000u); }
__device__ __forceinline__ float ex2(float x) {
    float y;
    asm("ex2.approx.ftz.f32 %0, %1;" : "=f"(y) : "f"(x));
    return y;
}
__device__ __forceinline__ void stmatrix_x4(uint32_t addr, uint32_t r0, uint32_t r1, uint32_t r2, uint32_t r3) {
    asm volatile("stmatrix.sync.aligned.m8n8.x4.shared.b16 [%0], {%1, %2, %3, %4};" ::"r"(addr), "r"(r0), "r"(r1), "r"(r2), "r"(r3)
                 : "memory");
}
__device__ __forceinline__ uint32_t mapa(uint32_t addr, uint32_t cta) {
    uint32_t r;
    asm volatile("mapa.shared::cluster.u32 %0, %1, %2;" : "=r"(r) : "r"(addr), "r"(cta));
    return r;
}
__device__ __forceinline__ void st_cluster_v2(uint32_t addr, float a, float b) {
    asm volatile("st.shared::cluster.v2.f32 [%0], {%1, %2};" ::"r"(addr), "f"(a), "f"(b) : "memory");
}
__device__ __forceinline__ void wgmma_ss_n256_t1(float (&d)[128], uint64_t descA, uint64_t descB, int scaleD) {
    asm volatile("{\n.reg .pred p;\n"
        "setp.ne.b32 p, %130, 0;\n"
        "wgmma.mma_async.sync.aligned.m64n256k16.f32.bf16.bf16 "
        "{%0, %1, %2, %3, %4, %5, %6, %7, %8, %9, %10, %11, %12, %13, %14, %15, "
        "%16, %17, %18, %19, %20, %21, %22, %23, %24, %25, %26, %27, %28, %29, %30, %31, "
        "%32, %33, %34, %35, %36, %37, %38, %39, %40, %41, %42, %43, %44, %45, %46, %47, "
        "%48, %49, %50, %51, %52, %53, %54, %55, %56, %57, %58, %59, %60, %61, %62, %63, "
        "%64, %65, %66, %67, %68, %69, %70, %71, %72, %73, %74, %75, %76, %77, %78, %79, "
        "%80, %81, %82, %83, %84, %85, %86, %87, %88, %89, %90, %91, %92, %93, %94, %95, "
        "%96, %97, %98, %99, %100, %101, %102, %103, %104, %105, %106, %107, %108, %109, %110, %111, "
        "%112, %113, %114, %115, %116, %117, %118, %119, %120, %121, %122, %123, %124, %125, %126, %127}, "
        "%128, %129, p, 1, 1, 0, 1;\n}\n"
        :
          "+f"(d[0]), "+f"(d[1]), "+f"(d[2]), "+f"(d[3]), "+f"(d[4]), "+f"(d[5]), "+f"(d[6]), "+f"(d[7]),
          "+f"(d[8]), "+f"(d[9]), "+f"(d[10]), "+f"(d[11]), "+f"(d[12]), "+f"(d[13]), "+f"(d[14]), "+f"(d[15]),
          "+f"(d[16]), "+f"(d[17]), "+f"(d[18]), "+f"(d[19]), "+f"(d[20]), "+f"(d[21]), "+f"(d[22]), "+f"(d[23]),
          "+f"(d[24]), "+f"(d[25]), "+f"(d[26]), "+f"(d[27]), "+f"(d[28]), "+f"(d[29]), "+f"(d[30]), "+f"(d[31]),
          "+f"(d[32]), "+f"(d[33]), "+f"(d[34]), "+f"(d[35]), "+f"(d[36]), "+f"(d[37]), "+f"(d[38]), "+f"(d[39]),
          "+f"(d[40]), "+f"(d[41]), "+f"(d[42]), "+f"(d[43]), "+f"(d[44]), "+f"(d[45]), "+f"(d[46]), "+f"(d[47]),
          "+f"(d[48]), "+f"(d[49]), "+f"(d[50]), "+f"(d[51]), "+f"(d[52]), "+f"(d[53]), "+f"(d[54]), "+f"(d[55]),
          "+f"(d[56]), "+f"(d[57]), "+f"(d[58]), "+f"(d[59]), "+f"(d[60]), "+f"(d[61]), "+f"(d[62]), "+f"(d[63]),
          "+f"(d[64]), "+f"(d[65]), "+f"(d[66]), "+f"(d[67]), "+f"(d[68]), "+f"(d[69]), "+f"(d[70]), "+f"(d[71]),
          "+f"(d[72]), "+f"(d[73]), "+f"(d[74]), "+f"(d[75]), "+f"(d[76]), "+f"(d[77]), "+f"(d[78]), "+f"(d[79]),
          "+f"(d[80]), "+f"(d[81]), "+f"(d[82]), "+f"(d[83]), "+f"(d[84]), "+f"(d[85]), "+f"(d[86]), "+f"(d[87]),
          "+f"(d[88]), "+f"(d[89]), "+f"(d[90]), "+f"(d[91]), "+f"(d[92]), "+f"(d[93]), "+f"(d[94]), "+f"(d[95]),
          "+f"(d[96]), "+f"(d[97]), "+f"(d[98]), "+f"(d[99]), "+f"(d[100]), "+f"(d[101]), "+f"(d[102]), "+f"(d[103]),
          "+f"(d[104]), "+f"(d[105]), "+f"(d[106]), "+f"(d[107]), "+f"(d[108]), "+f"(d[109]), "+f"(d[110]), "+f"(d[111]),
          "+f"(d[112]), "+f"(d[113]), "+f"(d[114]), "+f"(d[115]), "+f"(d[116]), "+f"(d[117]), "+f"(d[118]), "+f"(d[119]),
          "+f"(d[120]), "+f"(d[121]), "+f"(d[122]), "+f"(d[123]), "+f"(d[124]), "+f"(d[125]), "+f"(d[126]), "+f"(d[127])
        : "l"(descA), "l"(descB), "r"(scaleD));
}

__device__ __forceinline__ void wgmma_rs_n128_t0(float (&d)[64], const uint32_t (&a)[4], uint64_t descB, int scaleD) {
    asm volatile("{\n.reg .pred p;\n"
        "setp.ne.b32 p, %69, 0;\n"
        "wgmma.mma_async.sync.aligned.m64n128k16.f32.bf16.bf16 "
        "{%0, %1, %2, %3, %4, %5, %6, %7, %8, %9, %10, %11, %12, %13, %14, %15, "
        "%16, %17, %18, %19, %20, %21, %22, %23, %24, %25, %26, %27, %28, %29, %30, %31, "
        "%32, %33, %34, %35, %36, %37, %38, %39, %40, %41, %42, %43, %44, %45, %46, %47, "
        "%48, %49, %50, %51, %52, %53, %54, %55, %56, %57, %58, %59, %60, %61, %62, %63}, "
        "{%64, %65, %66, %67}, %68, p, 1, 1, 0;\n}\n"
        :
          "+f"(d[0]), "+f"(d[1]), "+f"(d[2]), "+f"(d[3]), "+f"(d[4]), "+f"(d[5]), "+f"(d[6]), "+f"(d[7]),
          "+f"(d[8]), "+f"(d[9]), "+f"(d[10]), "+f"(d[11]), "+f"(d[12]), "+f"(d[13]), "+f"(d[14]), "+f"(d[15]),
          "+f"(d[16]), "+f"(d[17]), "+f"(d[18]), "+f"(d[19]), "+f"(d[20]), "+f"(d[21]), "+f"(d[22]), "+f"(d[23]),
          "+f"(d[24]), "+f"(d[25]), "+f"(d[26]), "+f"(d[27]), "+f"(d[28]), "+f"(d[29]), "+f"(d[30]), "+f"(d[31]),
          "+f"(d[32]), "+f"(d[33]), "+f"(d[34]), "+f"(d[35]), "+f"(d[36]), "+f"(d[37]), "+f"(d[38]), "+f"(d[39]),
          "+f"(d[40]), "+f"(d[41]), "+f"(d[42]), "+f"(d[43]), "+f"(d[44]), "+f"(d[45]), "+f"(d[46]), "+f"(d[47]),
          "+f"(d[48]), "+f"(d[49]), "+f"(d[50]), "+f"(d[51]), "+f"(d[52]), "+f"(d[53]), "+f"(d[54]), "+f"(d[55]),
          "+f"(d[56]), "+f"(d[57]), "+f"(d[58]), "+f"(d[59]), "+f"(d[60]), "+f"(d[61]), "+f"(d[62]), "+f"(d[63])
        : "r"(a[0]), "r"(a[1]), "r"(a[2]), "r"(a[3]), "l"(descB), "r"(scaleD));
}

__device__ __forceinline__ void wgmma_rs_n128_t0_z(float (&d)[64], const uint32_t (&a)[4], uint64_t descB) {
    asm volatile("{\n.reg .pred p;\n"
        "setp.ne.b32 p, 0, 0;\n"
        "wgmma.mma_async.sync.aligned.m64n128k16.f32.bf16.bf16 "
        "{%0, %1, %2, %3, %4, %5, %6, %7, %8, %9, %10, %11, %12, %13, %14, %15, "
        "%16, %17, %18, %19, %20, %21, %22, %23, %24, %25, %26, %27, %28, %29, %30, %31, "
        "%32, %33, %34, %35, %36, %37, %38, %39, %40, %41, %42, %43, %44, %45, %46, %47, "
        "%48, %49, %50, %51, %52, %53, %54, %55, %56, %57, %58, %59, %60, %61, %62, %63}, "
        "{%64, %65, %66, %67}, %68, p, 1, 1, 0;\n}\n"
        :
          "=f"(d[0]), "=f"(d[1]), "=f"(d[2]), "=f"(d[3]), "=f"(d[4]), "=f"(d[5]), "=f"(d[6]), "=f"(d[7]),
          "=f"(d[8]), "=f"(d[9]), "=f"(d[10]), "=f"(d[11]), "=f"(d[12]), "=f"(d[13]), "=f"(d[14]), "=f"(d[15]),
          "=f"(d[16]), "=f"(d[17]), "=f"(d[18]), "=f"(d[19]), "=f"(d[20]), "=f"(d[21]), "=f"(d[22]), "=f"(d[23]),
          "=f"(d[24]), "=f"(d[25]), "=f"(d[26]), "=f"(d[27]), "=f"(d[28]), "=f"(d[29]), "=f"(d[30]), "=f"(d[31]),
          "=f"(d[32]), "=f"(d[33]), "=f"(d[34]), "=f"(d[35]), "=f"(d[36]), "=f"(d[37]), "=f"(d[38]), "=f"(d[39]),
          "=f"(d[40]), "=f"(d[41]), "=f"(d[42]), "=f"(d[43]), "=f"(d[44]), "=f"(d[45]), "=f"(d[46]), "=f"(d[47]),
          "=f"(d[48]), "=f"(d[49]), "=f"(d[50]), "=f"(d[51]), "=f"(d[52]), "=f"(d[53]), "=f"(d[54]), "=f"(d[55]),
          "=f"(d[56]), "=f"(d[57]), "=f"(d[58]), "=f"(d[59]), "=f"(d[60]), "=f"(d[61]), "=f"(d[62]), "=f"(d[63])
        : "r"(a[0]), "r"(a[1]), "r"(a[2]), "r"(a[3]), "l"(descB));
}

__device__ __forceinline__ void wgmma_rs_n128_t1(float (&d)[64], const uint32_t (&a)[4], uint64_t descB, int scaleD) {
    asm volatile("{\n.reg .pred p;\n"
        "setp.ne.b32 p, %69, 0;\n"
        "wgmma.mma_async.sync.aligned.m64n128k16.f32.bf16.bf16 "
        "{%0, %1, %2, %3, %4, %5, %6, %7, %8, %9, %10, %11, %12, %13, %14, %15, "
        "%16, %17, %18, %19, %20, %21, %22, %23, %24, %25, %26, %27, %28, %29, %30, %31, "
        "%32, %33, %34, %35, %36, %37, %38, %39, %40, %41, %42, %43, %44, %45, %46, %47, "
        "%48, %49, %50, %51, %52, %53, %54, %55, %56, %57, %58, %59, %60, %61, %62, %63}, "
        "{%64, %65, %66, %67}, %68, p, 1, 1, 1;\n}\n"
        :
          "+f"(d[0]), "+f"(d[1]), "+f"(d[2]), "+f"(d[3]), "+f"(d[4]), "+f"(d[5]), "+f"(d[6]), "+f"(d[7]),
          "+f"(d[8]), "+f"(d[9]), "+f"(d[10]), "+f"(d[11]), "+f"(d[12]), "+f"(d[13]), "+f"(d[14]), "+f"(d[15]),
          "+f"(d[16]), "+f"(d[17]), "+f"(d[18]), "+f"(d[19]), "+f"(d[20]), "+f"(d[21]), "+f"(d[22]), "+f"(d[23]),
          "+f"(d[24]), "+f"(d[25]), "+f"(d[26]), "+f"(d[27]), "+f"(d[28]), "+f"(d[29]), "+f"(d[30]), "+f"(d[31]),
          "+f"(d[32]), "+f"(d[33]), "+f"(d[34]), "+f"(d[35]), "+f"(d[36]), "+f"(d[37]), "+f"(d[38]), "+f"(d[39]),
          "+f"(d[40]), "+f"(d[41]), "+f"(d[42]), "+f"(d[43]), "+f"(d[44]), "+f"(d[45]), "+f"(d[46]), "+f"(d[47]),
          "+f"(d[48]), "+f"(d[49]), "+f"(d[50]), "+f"(d[51]), "+f"(d[52]), "+f"(d[53]), "+f"(d[54]), "+f"(d[55]),
          "+f"(d[56]), "+f"(d[57]), "+f"(d[58]), "+f"(d[59]), "+f"(d[60]), "+f"(d[61]), "+f"(d[62]), "+f"(d[63])
        : "r"(a[0]), "r"(a[1]), "r"(a[2]), "r"(a[3]), "l"(descB), "r"(scaleD));
}

__device__ __forceinline__ void wgmma_ss_n184_t1(float (&d)[92], uint64_t descA, uint64_t descB, int scaleD) {
    asm volatile("{\n.reg .pred p;\n"
        "setp.ne.b32 p, %94, 0;\n"
        "wgmma.mma_async.sync.aligned.m64n184k16.f32.bf16.bf16 "
        "{%0, %1, %2, %3, %4, %5, %6, %7, %8, %9, %10, %11, %12, %13, %14, %15, "
        "%16, %17, %18, %19, %20, %21, %22, %23, %24, %25, %26, %27, %28, %29, %30, %31, "
        "%32, %33, %34, %35, %36, %37, %38, %39, %40, %41, %42, %43, %44, %45, %46, %47, "
        "%48, %49, %50, %51, %52, %53, %54, %55, %56, %57, %58, %59, %60, %61, %62, %63, "
        "%64, %65, %66, %67, %68, %69, %70, %71, %72, %73, %74, %75, %76, %77, %78, %79, "
        "%80, %81, %82, %83, %84, %85, %86, %87, %88, %89, %90, %91}, "
        "%92, %93, p, 1, 1, 0, 1;\n}\n"
        :
          "+f"(d[0]), "+f"(d[1]), "+f"(d[2]), "+f"(d[3]), "+f"(d[4]), "+f"(d[5]), "+f"(d[6]), "+f"(d[7]),
          "+f"(d[8]), "+f"(d[9]), "+f"(d[10]), "+f"(d[11]), "+f"(d[12]), "+f"(d[13]), "+f"(d[14]), "+f"(d[15]),
          "+f"(d[16]), "+f"(d[17]), "+f"(d[18]), "+f"(d[19]), "+f"(d[20]), "+f"(d[21]), "+f"(d[22]), "+f"(d[23]),
          "+f"(d[24]), "+f"(d[25]), "+f"(d[26]), "+f"(d[27]), "+f"(d[28]), "+f"(d[29]), "+f"(d[30]), "+f"(d[31]),
          "+f"(d[32]), "+f"(d[33]), "+f"(d[34]), "+f"(d[35]), "+f"(d[36]), "+f"(d[37]), "+f"(d[38]), "+f"(d[39]),
          "+f"(d[40]), "+f"(d[41]), "+f"(d[42]), "+f"(d[43]), "+f"(d[44]), "+f"(d[45]), "+f"(d[46]), "+f"(d[47]),
          "+f"(d[48]), "+f"(d[49]), "+f"(d[50]), "+f"(d[51]), "+f"(d[52]), "+f"(d[53]), "+f"(d[54]), "+f"(d[55]),
          "+f"(d[56]), "+f"(d[57]), "+f"(d[58]), "+f"(d[59]), "+f"(d[60]), "+f"(d[61]), "+f"(d[62]), "+f"(d[63]),
          "+f"(d[64]), "+f"(d[65]), "+f"(d[66]), "+f"(d[67]), "+f"(d[68]), "+f"(d[69]), "+f"(d[70]), "+f"(d[71]),
          "+f"(d[72]), "+f"(d[73]), "+f"(d[74]), "+f"(d[75]), "+f"(d[76]), "+f"(d[77]), "+f"(d[78]), "+f"(d[79]),
          "+f"(d[80]), "+f"(d[81]), "+f"(d[82]), "+f"(d[83]), "+f"(d[84]), "+f"(d[85]), "+f"(d[86]), "+f"(d[87]),
          "+f"(d[88]), "+f"(d[89]), "+f"(d[90]), "+f"(d[91])
        : "l"(descA), "l"(descB), "r"(scaleD));
}

__device__ __forceinline__ void wgmma_ss_n192_t1(float (&d)[96], uint64_t descA, uint64_t descB, int scaleD) {
    asm volatile("{\n.reg .pred p;\n"
        "setp.ne.b32 p, %98, 0;\n"
        "wgmma.mma_async.sync.aligned.m64n192k16.f32.bf16.bf16 "
        "{%0, %1, %2, %3, %4, %5, %6, %7, %8, %9, %10, %11, %12, %13, %14, %15, "
        "%16, %17, %18, %19, %20, %21, %22, %23, %24, %25, %26, %27, %28, %29, %30, %31, "
        "%32, %33, %34, %35, %36, %37, %38, %39, %40, %41, %42, %43, %44, %45, %46, %47, "
        "%48, %49, %50, %51, %52, %53, %54, %55, %56, %57, %58, %59, %60, %61, %62, %63, "
        "%64, %65, %66, %67, %68, %69, %70, %71, %72, %73, %74, %75, %76, %77, %78, %79, "
        "%80, %81, %82, %83, %84, %85, %86, %87, %88, %89, %90, %91, %92, %93, %94, %95}, "
        "%96, %97, p, 1, 1, 0, 1;\n}\n"
        :
          "+f"(d[0]), "+f"(d[1]), "+f"(d[2]), "+f"(d[3]), "+f"(d[4]), "+f"(d[5]), "+f"(d[6]), "+f"(d[7]),
          "+f"(d[8]), "+f"(d[9]), "+f"(d[10]), "+f"(d[11]), "+f"(d[12]), "+f"(d[13]), "+f"(d[14]), "+f"(d[15]),
          "+f"(d[16]), "+f"(d[17]), "+f"(d[18]), "+f"(d[19]), "+f"(d[20]), "+f"(d[21]), "+f"(d[22]), "+f"(d[23]),
          "+f"(d[24]), "+f"(d[25]), "+f"(d[26]), "+f"(d[27]), "+f"(d[28]), "+f"(d[29]), "+f"(d[30]), "+f"(d[31]),
          "+f"(d[32]), "+f"(d[33]), "+f"(d[34]), "+f"(d[35]), "+f"(d[36]), "+f"(d[37]), "+f"(d[38]), "+f"(d[39]),
          "+f"(d[40]), "+f"(d[41]), "+f"(d[42]), "+f"(d[43]), "+f"(d[44]), "+f"(d[45]), "+f"(d[46]), "+f"(d[47]),
          "+f"(d[48]), "+f"(d[49]), "+f"(d[50]), "+f"(d[51]), "+f"(d[52]), "+f"(d[53]), "+f"(d[54]), "+f"(d[55]),
          "+f"(d[56]), "+f"(d[57]), "+f"(d[58]), "+f"(d[59]), "+f"(d[60]), "+f"(d[61]), "+f"(d[62]), "+f"(d[63]),
          "+f"(d[64]), "+f"(d[65]), "+f"(d[66]), "+f"(d[67]), "+f"(d[68]), "+f"(d[69]), "+f"(d[70]), "+f"(d[71]),
          "+f"(d[72]), "+f"(d[73]), "+f"(d[74]), "+f"(d[75]), "+f"(d[76]), "+f"(d[77]), "+f"(d[78]), "+f"(d[79]),
          "+f"(d[80]), "+f"(d[81]), "+f"(d[82]), "+f"(d[83]), "+f"(d[84]), "+f"(d[85]), "+f"(d[86]), "+f"(d[87]),
          "+f"(d[88]), "+f"(d[89]), "+f"(d[90]), "+f"(d[91]), "+f"(d[92]), "+f"(d[93]), "+f"(d[94]), "+f"(d[95])
        : "l"(descA), "l"(descB), "r"(scaleD));
}

__device__ __forceinline__ void wgmma_ss_n128_t1(float (&d)[64], uint64_t descA, uint64_t descB, int scaleD) {
    asm volatile("{\n.reg .pred p;\n"
        "setp.ne.b32 p, %66, 0;\n"
        "wgmma.mma_async.sync.aligned.m64n128k16.f32.bf16.bf16 "
        "{%0, %1, %2, %3, %4, %5, %6, %7, %8, %9, %10, %11, %12, %13, %14, %15, "
        "%16, %17, %18, %19, %20, %21, %22, %23, %24, %25, %26, %27, %28, %29, %30, %31, "
        "%32, %33, %34, %35, %36, %37, %38, %39, %40, %41, %42, %43, %44, %45, %46, %47, "
        "%48, %49, %50, %51, %52, %53, %54, %55, %56, %57, %58, %59, %60, %61, %62, %63}, "
        "%64, %65, p, 1, 1, 0, 1;\n}\n"
        :
          "+f"(d[0]), "+f"(d[1]), "+f"(d[2]), "+f"(d[3]), "+f"(d[4]), "+f"(d[5]), "+f"(d[6]), "+f"(d[7]),
          "+f"(d[8]), "+f"(d[9]), "+f"(d[10]), "+f"(d[11]), "+f"(d[12]), "+f"(d[13]), "+f"(d[14]), "+f"(d[15]),
          "+f"(d[16]), "+f"(d[17]), "+f"(d[18]), "+f"(d[19]), "+f"(d[20]), "+f"(d[21]), "+f"(d[22]), "+f"(d[23]),
          "+f"(d[24]), "+f"(d[25]), "+f"(d[26]), "+f"(d[27]), "+f"(d[28]), "+f"(d[29]), "+f"(d[30]), "+f"(d[31]),
          "+f"(d[32]), "+f"(d[33]), "+f"(d[34]), "+f"(d[35]), "+f"(d[36]), "+f"(d[37]), "+f"(d[38]), "+f"(d[39]),
          "+f"(d[40]), "+f"(d[41]), "+f"(d[42]), "+f"(d[43]), "+f"(d[44]), "+f"(d[45]), "+f"(d[46]), "+f"(d[47]),
          "+f"(d[48]), "+f"(d[49]), "+f"(d[50]), "+f"(d[51]), "+f"(d[52]), "+f"(d[53]), "+f"(d[54]), "+f"(d[55]),
          "+f"(d[56]), "+f"(d[57]), "+f"(d[58]), "+f"(d[59]), "+f"(d[60]), "+f"(d[61]), "+f"(d[62]), "+f"(d[63])
        : "l"(descA), "l"(descB), "r"(scaleD));
}

__device__ __forceinline__ void wgmma_ss_n32_t1(float (&d)[16], uint64_t descA, uint64_t descB, int scaleD) {
    asm volatile("{\n.reg .pred p;\n"
        "setp.ne.b32 p, %18, 0;\n"
        "wgmma.mma_async.sync.aligned.m64n32k16.f32.bf16.bf16 "
        "{%0, %1, %2, %3, %4, %5, %6, %7, %8, %9, %10, %11, %12, %13, %14, %15}, "
        "%16, %17, p, 1, 1, 0, 1;\n}\n"
        :
          "+f"(d[0]), "+f"(d[1]), "+f"(d[2]), "+f"(d[3]), "+f"(d[4]), "+f"(d[5]), "+f"(d[6]), "+f"(d[7]),
          "+f"(d[8]), "+f"(d[9]), "+f"(d[10]), "+f"(d[11]), "+f"(d[12]), "+f"(d[13]), "+f"(d[14]), "+f"(d[15])
        : "l"(descA), "l"(descB), "r"(scaleD));
}

constexpr int S_LEN = 2048;
constexpr int D_MODEL = 640;
constexpr int N_HEADS = 32;
constexpr int D_HEAD = 128;
constexpr int S_KV = 2048;
constexpr int WIN = 512;
constexpr int D_FF = 1728;
constexpr float LN_EPS = 1e-5f;

#define TS(kid, slot)

__device__ float g_mod[6 * D_MODEL];
__device__ __align__(1024) __nv_bfloat16 g_h[S_LEN * D_MODEL];
__device__ __align__(1024) __nv_bfloat16 g_o[S_LEN * N_HEADS * D_HEAD];
__device__ __align__(1024) __nv_bfloat16 g_part[4 * S_LEN * D_MODEL];
__device__ __align__(1024) __nv_bfloat16 g_x1[S_LEN * D_MODEL];
__device__ __align__(1024) __nv_bfloat16 g_h2[S_LEN * D_MODEL];
__device__ __align__(1024) __nv_bfloat16 g_act[S_LEN * D_FF];

constexpr int F_MODAB = 0, F_MODALL = 1, F_H = 2, F_P = 18, F_H2 = 34, F_A = 50, F_O = 66, F_A1 = 130, F_COUNT = 146;
__device__ unsigned g_flags[F_COUNT * 32];
__device__ unsigned g_epoch;
__device__ unsigned g_exit;

__device__ __forceinline__ void flag_signal(int f) {
    asm volatile("red.release.gpu.global.add.u32 [%0], 1;" ::"l"(g_flags + f * 32) : "memory");
}
__device__ __forceinline__ void flag_signal_relaxed(int f) {
    asm volatile("red.relaxed.gpu.global.add.u32 [%0], 1;" ::"l"(g_flags + f * 32) : "memory");
}
__device__ __forceinline__ void flag_wait(int f, unsigned target) {
    unsigned n = 0;
    while (true) {
        unsigned v;
        asm volatile("ld.acquire.gpu.global.u32 %0, [%1];" : "=r"(v) : "l"(g_flags + f * 32) : "memory");
        if ((int)(v - target) >= 0) break;
        if ((++n & 0xfffu) == 0) {
            if (n > (1u << 24)) g_abort = 1;
            if (g_abort) break;
        }
    }
}

struct Maps {
    CUtensorMap h, wq, k, v, o_st, o_a, wo, part_st, h2, g128, u128, g64, u64, act_st64, act_st24, act_a, wd, wd32;
};

constexpr int SM_DATA = 229376;
constexpr int SM_STAGING = 196608;
constexpr int SM_TOTAL = SM_DATA + 1024 + 512;
constexpr int B1F = 0, B1E = 6, B2F = 12, B2E = 16, B4F = 20, B4E = 24, B5F = 28, B5E = 33, BD1 = 38, BD2 = 39, BD4 = 40, BD1A = 41, BX = 42, BD4B = 43;
constexpr int P1_STAGE = 32768, P2_STAGE = 57344, P4_STAGE = 49152, P5_STAGE = 36864;

__device__ __forceinline__ float rcp_approx(float x) { float y; asm("rcp.approx.ftz.f32 %0, %1;" : "=f"(y) : "f"(x)); return y; }
__device__ __forceinline__ float silu_mul(float g, float u) { return g * rcp_approx(1.f + ex2(-1.4426950408889634f * g)) * u; }
__device__ __forceinline__ uint2 ldcg_u2(const void* p) { return __ldcg(reinterpret_cast<const uint2*>(p)); }

__device__ __forceinline__ void ln_rows(const uint2 (&xr)[2][5], const float* __restrict__ shift, const float* __restrict__ scale1p,
                                     __nv_bfloat16* __restrict__ dst, int lane) {
    float4 sh[5], sc[5];
#pragma unroll
    for (int i = 0; i < 5; i++) {
        sh[i] = __ldcg(reinterpret_cast<const float4*>(shift + (lane + 32 * i) * 4));
        sc[i] = __ldcg(reinterpret_cast<const float4*>(scale1p + (lane + 32 * i) * 4));
    }
    float mean[2], rstd[2];
#pragma unroll
    for (int rr = 0; rr < 2; rr++) {
        float s = 0.f;
#pragma unroll
        for (int i = 0; i < 5; i++) s += (bf16lo(xr[rr][i].x) + bf16hi(xr[rr][i].x)) + (bf16lo(xr[rr][i].y) + bf16hi(xr[rr][i].y));
#pragma unroll
        for (int o = 16; o > 0; o >>= 1) s += __shfl_xor_sync(0xffffffffu, s, o);
        mean[rr] = s * (1.f / D_MODEL);
    }
#pragma unroll
    for (int rr = 0; rr < 2; rr++) {
        float q = 0.f;
#pragma unroll
        for (int i = 0; i < 5; i++) {
            const float d0 = bf16lo(xr[rr][i].x) - mean[rr], d1 = bf16hi(xr[rr][i].x) - mean[rr];
            const float d2 = bf16lo(xr[rr][i].y) - mean[rr], d3 = bf16hi(xr[rr][i].y) - mean[rr];
            q += (d0 * d0 + d1 * d1) + (d2 * d2 + d3 * d3);
        }
#pragma unroll
        for (int o = 16; o > 0; o >>= 1) q += __shfl_xor_sync(0xffffffffu, q, o);
        rstd[rr] = rsqrtf(q * (1.f / D_MODEL) + LN_EPS);
    }
#pragma unroll
    for (int rr = 0; rr < 2; rr++) {
#pragma unroll
        for (int i = 0; i < 5; i++) {
            uint2 u;
            u.x = pack_bf16((bf16lo(xr[rr][i].x) - mean[rr]) * rstd[rr] * sc[i].x + sh[i].x, (bf16hi(xr[rr][i].x) - mean[rr]) * rstd[rr] * sc[i].y + sh[i].y);
            u.y = pack_bf16((bf16lo(xr[rr][i].y) - mean[rr]) * rstd[rr] * sc[i].z + sh[i].z, (bf16hi(xr[rr][i].y) - mean[rr]) * rstd[rr] * sc[i].w + sh[i].w);
            *reinterpret_cast<uint2*>(dst + (size_t)rr * D_MODEL + (lane + 32 * i) * 4) = u;
        }
    }
}

__global__ void __cluster_dims__(2, 1, 1) __launch_bounds__(384, 1)
mega_kernel(const __grid_constant__ Maps tm, const __nv_bfloat16* __restrict__ x, const __nv_bfloat16* __restrict__ cvec,
            const __nv_bfloat16* __restrict__ w_mod, __nv_bfloat16* __restrict__ out, const void* wo_p, const void* wg_p,
            const void* wu_p, const void* wd_p) {
    extern __shared__ uint8_t smem_raw[];
    const uint32_t base = (smem_u32(smem_raw) + 1023u) & ~1023u;
    const uint32_t bars = base + SM_DATA;
    const uint32_t rank = cluster_ctarank();
    const int cid = blockIdx.x >> 1;
    const int p = cid & 7, j = cid >> 3;
    const int mt = p * 2 + (int)rank;
    const int m0 = mt * 128;
    const int wg = threadIdx.x >> 7;
    unsigned epoch;
    asm volatile("ld.volatile.global.u32 %0, [%1];" : "=r"(epoch) : "l"(&g_epoch));

    if (threadIdx.x == 0) {
        for (int i = 0; i < 6; i++) { mbar_init(bars + 8 * (B1F + i), 1); mbar_init(bars + 8 * (B1E + i), 4); }
        for (int i = 0; i < 4; i++) { mbar_init(bars + 8 * (B2F + i), 1); mbar_init(bars + 8 * (B2E + i), 4); }
        for (int i = 0; i < 4; i++) { mbar_init(bars + 8 * (B4F + i), 1); mbar_init(bars + 8 * (B4E + i), 4); }
        for (int i = 0; i < 5; i++) { mbar_init(bars + 8 * (B5F + i), 1); mbar_init(bars + 8 * (B5E + i), 2); }
        mbar_init(bars + 8 * BD1, 4); mbar_init(bars + 8 * BD2, 4); mbar_init(bars + 8 * BD4, 4); mbar_init(bars + 8 * BD1A, 4);
        mbar_init(bars + 8 * BX, 1); mbar_init(bars + 8 * BD4B, 4);
        mbar_expect_tx(bars + 8 * BX, 40960);
        fence_mbar_init();
    }
    __syncthreads();
    cluster_sync();

    if (wg == 2) {
        reg_dealloc<40>();
        if (threadIdx.x == 256) {
            {
                uint32_t st = 0, ph = 1;
                bool first = true;
#pragma unroll 1
                for (int hp = 0; hp < 2; hp++) {
                    const int head0 = j * 4 + hp * 2;
                    if (first) {
#pragma unroll 1
                        for (int s = 1; s < 6; s++) {
                            if (s == 3) continue;
                            const int kb = s < 3 ? s - 1 : s - 2;
                            mbar_expect_tx(bars + 8 * (B1F + s), P1_STAGE);
#pragma unroll 1
                            for (int c = 0; c < 2; c++) {
                                const int chunk = 2 * (int)rank + c;
                                tma_load_2d_mc(base + s * P1_STAGE + chunk * 8192, &tm.wq, head0 * 128 + chunk * 64, kb * 64, bars + 8 * (B1F + s), 3);
                            }
                        }
                        flag_wait(F_H + mt, (epoch + 1) * 8);
                        fence_proxy_async_all();
#pragma unroll 1
                        for (int s = 0; s < 6; s += 3) {
                            mbar_expect_tx(bars + 8 * (B1F + s), P1_STAGE);
                            tma_load_2d(base + s * P1_STAGE, &tm.h, (s / 3 * 2) * 64, m0, bars + 8 * (B1F + s));
                            tma_load_2d(base + s * P1_STAGE + 16384, &tm.h, (s / 3 * 2 + 1) * 64, m0, bars + 8 * (B1F + s));
                        }
                        ph = 0;
                    }
#pragma unroll 1
                    for (int kk2 = first ? 2 : 0; kk2 < 5; kk2++) {
                        mbar_wait(bars + 8 * (B1E + st), ph);
                        mbar_expect_tx(bars + 8 * (B1F + st), P1_STAGE);
                        tma_load_2d(base + st * P1_STAGE, &tm.h, (2 * kk2) * 64, m0, bars + 8 * (B1F + st));
                        tma_load_2d(base + st * P1_STAGE + 16384, &tm.h, (2 * kk2 + 1) * 64, m0, bars + 8 * (B1F + st));
                        if (++st == 6) { st = 0; ph ^= 1; }
#pragma unroll 1
                        for (int u = 0; u < 2; u++) {
                            mbar_wait(bars + 8 * (B1E + st), ph);
                            mbar_expect_tx(bars + 8 * (B1F + st), P1_STAGE);
                            const int kb = 2 * kk2 + u;
#pragma unroll 1
                            for (int c = 0; c < 2; c++) {
                                const int chunk = 2 * (int)rank + c;
                                tma_load_2d_mc(base + st * P1_STAGE + chunk * 8192, &tm.wq, head0 * 128 + chunk * 64, kb * 64, bars + 8 * (B1F + st), 3);
                            }
                            if (++st == 6) { st = 0; ph ^= 1; }
                        }
                    }
                    first = false;
#pragma unroll 1
                    for (int t = 0; t <= 8; t++) {
                        if (t < 8) {
                            mbar_wait(bars + 8 * (B1E + st), ph);
                            mbar_expect_tx(bars + 8 * (B1F + st), P1_STAGE);
                            const int row = (head0 + (t >> 2)) * S_KV + (S_KV - WIN) + (t & 3) * 128;
                            tma_load_2d_mc(base + st * P1_STAGE + rank * 16384, &tm.k, rank * 64, row, bars + 8 * (B1F + st), 3);
                            if (++st == 6) { st = 0; ph ^= 1; }
                        }
                        if (t > 0) {
                            mbar_wait(bars + 8 * (B1E + st), ph);
                            mbar_expect_tx(bars + 8 * (B1F + st), P1_STAGE);
                            const int tv = t - 1;
                            const int row = (head0 + (tv >> 2)) * S_KV + (S_KV - WIN) + (tv & 3) * 128;
                            tma_load_2d_mc(base + st * P1_STAGE + rank * 16384, &tm.v, rank * 64, row, bars + 8 * (B1F + st), 3);
                            if (++st == 6) { st = 0; ph ^= 1; }
                        }
                    }
                }
            }
            {
                const int kq = j >> 1, n0 = (j & 1) * 320;
                uint32_t st = 0, ph = 1;
#pragma unroll 1
                for (int i = 0; i < 16; i++) {
                    if (i == 0) mbar_wait(bars + 8 * BD1A, 0);
                    if (i == 3) mbar_wait(bars + 8 * BD1, 0);
                    if (i == 8) { flag_wait(F_O + mt * 4 + kq, (epoch + 1) * 4); fence_proxy_async_all(); }
                    mbar_wait(bars + 8 * (B2E + st), ph);
                    mbar_expect_tx(bars + 8 * (B2F + st), P2_STAGE);
                    const uint32_t dst = base + st * P2_STAGE;
                    const int k0 = kq * 1024 + ((i + (j & 1) * 8) & 15) * 64;
                    tma_load_2d(dst, &tm.o_a, k0, m0, bars + 8 * (B2F + st));
#pragma unroll 1
                    for (int c = 0; c < 5; c++)
                        if (((c + i) & 1) == (int)rank) tma_load_2d_mc(dst + 16384 + c * 8192, &tm.wo, n0 + c * 64, k0, bars + 8 * (B2F + st), 3);
                    if (++st == 4) { st = 0; ph ^= 1; }
                }
            }
            {
                const int f0 = j * 216;
                const CUtensorMap* t128 = rank == 0 ? &tm.g128 : &tm.u128;
                const CUtensorMap* t64 = rank == 0 ? &tm.g64 : &tm.u64;
                mbar_wait(bars + 8 * BD2, 0);
#pragma unroll 1
                for (int i = 0; i < 4; i++) {
                    mbar_expect_tx(bars + 8 * (B4F + i), 16384 + 32768);
                    const uint32_t dst = base + i * P4_STAGE;
                    tma_load_2d_mc(dst + 16384 + rank * 16384, t128, f0, i * 64, bars + 8 * (B4F + i), 3);
                    tma_load_2d_mc(dst + 16384 + rank * 16384 + 8192, t128, f0 + 64, i * 64, bars + 8 * (B4F + i), 3);
                }
                flag_wait(F_H2 + mt, (epoch + 1) * 8);
                fence_proxy_async_all();
#pragma unroll 1
                for (int i = 0; i < 4; i++) tma_load_2d(base + i * P4_STAGE, &tm.h2, i * 64, m0, bars + 8 * (B4F + i));
                uint32_t st = 0, ph = 0;
#pragma unroll 1
                for (int i = 4; i < 20; i++) {
                    const int kb = i < 10 ? i : i - 10;
                    mbar_wait(bars + 8 * (B4E + st), ph);
                    const uint32_t dst = base + st * P4_STAGE;
                    if (i < 10) {
                        mbar_expect_tx(bars + 8 * (B4F + st), 16384 + 32768);
                        tma_load_2d(dst, &tm.h2, kb * 64, m0, bars + 8 * (B4F + st));
                        tma_load_2d_mc(dst + 16384 + rank * 16384, t128, f0, kb * 64, bars + 8 * (B4F + st), 3);
                        tma_load_2d_mc(dst + 16384 + rank * 16384 + 8192, t128, f0 + 64, kb * 64, bars + 8 * (B4F + st), 3);
                    } else {
                        mbar_expect_tx(bars + 8 * (B4F + st), 16384 + 24576);
                        tma_load_2d(dst, &tm.h2, kb * 64, m0, bars + 8 * (B4F + st));
#pragma unroll 1
                        for (int c = 0; c < 3; c++)
                            tma_load_2d_mc(dst + 16384 + rank * 12288 + c * 4096, t64, f0 + 128 + c * 32, kb * 64, bars + 8 * (B4F + st), 3);
                    }
                    if (++st == 4) { st = 0; ph ^= 1; }
                }
            }
            {
                const int mt5 = p * 2 + (j >> 2), n0 = (j & 3) * 160;
                const int nkb = rank == 0 ? 14 : 13;
                const unsigned long long ord = rank == 0
                    ? (0ull | 1ull << 5 | 4ull << 10 | 7ull << 15 | 11ull << 20 | 2ull << 25 | 3ull << 30 | 5ull << 35 | 6ull << 40 | 8ull << 45 | 9ull << 50 | 10ull << 55)
                    : (14ull | 17ull << 5 | 21ull << 10 | 24ull << 15 | 15ull << 20 | 16ull << 25 | 18ull << 30 | 19ull << 35 | 20ull << 40 | 22ull << 45 | 23ull << 50 | 25ull << 55);
                const int nearly = rank == 0 ? 5 : 4;
                mbar_wait(bars + 8 * BD4, 0);
                uint32_t st = 0, ph = 1;
#pragma unroll 1
                for (int i = 0; i < nkb; i++) {
                    const int kb = i < 12 ? (int)((ord >> (5 * i)) & 31) : (rank == 0 ? i : 26);
                    if (i == 0) { flag_wait(F_A1 + mt5, (epoch + 1) * 16); fence_proxy_async_all(); }
                    if (i == nearly) { flag_wait(F_A + mt5, (epoch + 1) * 16); fence_proxy_async_all(); }
                    mbar_wait(bars + 8 * (B5E + st), ph);
                    mbar_expect_tx(bars + 8 * (B5F + st), P5_STAGE);
                    const uint32_t dst = base + st * P5_STAGE;
                    const int k0 = kb * 64;
                    tma_load_2d(dst + 16384, &tm.wd, n0, k0, bars + 8 * (B5F + st));
                    tma_load_2d(dst + 16384 + 8192, &tm.wd, n0 + 64, k0, bars + 8 * (B5F + st));
                    tma_load_2d(dst + 16384 + 16384, &tm.wd32, n0 + 128, k0, bars + 8 * (B5F + st));
                    tma_load_2d(dst, &tm.act_a, k0, mt5 * 128, bars + 8 * (B5F + st));
                    if (++st == 5) { st = 0; ph ^= 1; }
                }
            }
        }
        else if (threadIdx.x == 288) {
            mbar_wait(bars + 8 * B1F, 0);
            const char* pw[4] = {(const char*)wo_p, (const char*)wg_p, (const char*)wu_p, (const char*)wd_p};
#pragma unroll 1
            for (int t = 0; t < 4; t++) {
                const uint32_t bytes = t == 0 ? 40960u : 17280u;
                asm volatile("cp.async.bulk.prefetch.L2.global [%0], %1;" ::"l"(pw[t] + (size_t)blockIdx.x * bytes), "r"(bytes) : "memory");
            }
        }
        __syncwarp();
        asm volatile("barrier.cluster.arrive.relaxed.aligned; // producer\n barrier.cluster.wait.aligned;" ::: "memory");
    } else {
        reg_alloc<232>();
        const int tid = threadIdx.x & 127;
        const int warp = tid >> 5, lane = tid & 31;
        const int cw = threadIdx.x >> 5;
        const uint32_t mystage = base + SM_STAGING + wg * 16384;
        auto arrive_both = [&](uint32_t bar) {
            if (tid == 0) mbar_arrive_cluster(bar, 0);
            if (tid == 32) mbar_arrive_cluster(bar, 1);
        };
        TS(0, 0);
        {
            uint2 xr[2][5];
            uint4 w[10];
            unsigned short cr[10];
            const int mb = blockIdx.x < 120 ? blockIdx.x : 0;
#pragma unroll
            for (int i = 0; i < 10; i++) cr[i] = __ldg(reinterpret_cast<const unsigned short*>(cvec) + cw * 80 + i * 8 + (lane >> 2));
#pragma unroll
            for (int i = 0; i < 10; i++)
                w[i] = __ldg(reinterpret_cast<const uint4*>(w_mod + (size_t)(cw * 80 + i * 8 + (lane >> 2)) * (6 * D_MODEL) + mb * 32 + (lane & 3) * 8));
#pragma unroll
            for (int rr = 0; rr < 2; rr++)
#pragma unroll
                for (int i = 0; i < 5; i++)
                    xr[rr][i] = __ldg(reinterpret_cast<const uint2*>(x + (size_t)(m0 + j * 16 + cw * 2 + rr) * D_MODEL + (lane + 32 * i) * 4));
            if (blockIdx.x < 120) {
                float* red = reinterpret_cast<float*>(smem_raw + (base - smem_u32(smem_raw)) + SM_STAGING);
                float acc[8];
#pragma unroll
                for (int i = 0; i < 8; i++) acc[i] = 0.f;
#pragma unroll
                for (int i = 0; i < 10; i++) {
                    const float s = bf16_round(silu_mul(__uint_as_float((uint32_t)cr[i] << 16), 1.f));
                    acc[0] += s * bf16lo(w[i].x); acc[1] += s * bf16hi(w[i].x);
                    acc[2] += s * bf16lo(w[i].y); acc[3] += s * bf16hi(w[i].y);
                    acc[4] += s * bf16lo(w[i].z); acc[5] += s * bf16hi(w[i].z);
                    acc[6] += s * bf16lo(w[i].w); acc[7] += s * bf16hi(w[i].w);
                }
#pragma unroll
                for (int i = 0; i < 8; i++) {
                    acc[i] += __shfl_xor_sync(0xffffffffu, acc[i], 4);
                    acc[i] += __shfl_xor_sync(0xffffffffu, acc[i], 8);
                    acc[i] += __shfl_xor_sync(0xffffffffu, acc[i], 16);
                }
                if (lane < 4) {
#pragma unroll
                    for (int i = 0; i < 8; i++) red[cw * 32 + lane * 8 + i] = acc[i];
                }
                TS(6, 0);
                bar_sync(5, 256);
                TS(6, 1);
                if (threadIdx.x < 32) {
                    float t = 0.f;
#pragma unroll
                    for (int i = 0; i < 8; i++) t += red[i * 32 + threadIdx.x];
                    t = bf16_round(t);
                    const int chunk = blockIdx.x / 20;
                    if (chunk == 1 || chunk == 4) t = bf16_round(1.f + t);
                    g_mod[blockIdx.x * 32 + threadIdx.x] = t;
                    __syncwarp();
                    TS(6, 2);
                    if (threadIdx.x == 0) flag_signal(blockIdx.x < 40 ? F_MODAB : F_MODALL);
                    TS(6, 3);
                }
            }
            if (threadIdx.x == 0) flag_wait(F_MODAB, (epoch + 1) * 40);
            bar_sync(5, 256);
            TS(0, 1);
            ln_rows(xr, g_mod, g_mod + D_MODEL, g_h + (size_t)(m0 + j * 16 + cw * 2) * D_MODEL, lane);
            TS(6, 4);
            bar_sync(5, 256);
            TS(6, 5);
            if (threadIdx.x == 0) flag_signal(F_H + mt);
        }
        TS(0, 2);
        {
            const float cscale = 0.08838834764831845f * 1.4426950408889634f;
            uint32_t st = 0, ph = 0;
            auto wait_full = [&]() -> uint32_t {
                mbar_wait(bars + 8 * (B1F + st), ph);
                return base + st * P1_STAGE;
            };
            auto release = [&](uint32_t s) { arrive_both(bars + 8 * (B1E + s)); };
            auto advance = [&]() { if (++st == 6) { st = 0; ph ^= 1; } };
            auto turn_wait = [&]() { bar_sync(3 + wg, 256); };
            auto turn_pass = [&]() { bar_arrive(3 + (wg ^ 1), 256); };
            if (wg == 1) bar_arrive(3, 256);

            for (int hp = 0; hp < 2; hp++) {
                const int head0 = j * 4 + hp * 2;
                uint32_t q[8][4];
                {
                    float acc[128];
#pragma unroll
                    for (int i = 0; i < 128; i++) acc[i] = 0.f;
                    for (int kk2 = 0; kk2 < 5; kk2++) {
                        const uint32_t hbuf = wait_full();
                        if (kk2 == 0 && hp == 0) TS(0, 3);
                        const uint32_t sth = st;
                        advance();
#pragma unroll
                        for (int u = 0; u < 2; u++) {
                            const uint32_t wbuf = wait_full();
                            const uint32_t stw = st;
                            advance();
                            wgmma_fence();
#pragma unroll
                            for (int k = 0; k < 4; k++) {
                                uint64_t da = make_desc(hbuf + u * 16384 + wg * 8192 + k * 32, 16, 1024, 1);
                                uint64_t db = make_desc(wbuf + k * 2048, 8192, 1024, 1);
                                wgmma_ss_n256_t1(acc, da, db, 1);
                            }
                            wgmma_commit();
                            wgmma_wait<0>();
                            release(stw);
                        }
                        release(sth);
                    }
                    fence_regs(acc);
                    if (tid == 0) tma_store_wait_read<0>();
                    bar_sync(1 + wg, 128);
#pragma unroll
                    for (int i = 0; i < 8; i++) {
                        q[i][0] = pack_bf16(acc[8 * i + 0], acc[8 * i + 1]);
                        q[i][1] = pack_bf16(acc[8 * i + 2], acc[8 * i + 3]);
                        q[i][2] = pack_bf16(acc[8 * i + 4], acc[8 * i + 5]);
                        q[i][3] = pack_bf16(acc[8 * i + 6], acc[8 * i + 7]);
                        uint32_t b0 = pack_bf16(acc[64 + 8 * i + 0], acc[64 + 8 * i + 1]);
                        uint32_t b1 = pack_bf16(acc[64 + 8 * i + 2], acc[64 + 8 * i + 3]);
                        uint32_t b2 = pack_bf16(acc[64 + 8 * i + 4], acc[64 + 8 * i + 5]);
                        uint32_t b3 = pack_bf16(acc[64 + 8 * i + 6], acc[64 + 8 * i + 7]);
                        asm volatile("st.shared.v4.b32 [%0], {%1, %2, %3, %4};" ::"r"(mystage + (i * 128 + tid) * 16), "r"(b0), "r"(b1),
                                     "r"(b2), "r"(b3) : "memory");
                    }
                }
                float o[64], s[64], e[64];
                uint32_t pp[8][4];
                float mm0, mm1, l0, l1, a0, a1, lo0, lo1;
#pragma unroll
                for (int i = 0; i < 64; i++) { o[i] = 0.f; }

                auto issue_s = [&]() -> uint32_t {
                    const uint32_t kbuf = wait_full();
                    const uint32_t stk = st;
                    advance();
                    wgmma_fence();
#pragma unroll
                    for (int k = 0; k < 8; k++) {
                        uint64_t db = make_desc(kbuf + (k >> 2) * 16384 + (k & 3) * 32, 16, 1024, 1);
                        if (k == 0) wgmma_rs_n128_t0_z(s, q[k], db);
                        else wgmma_rs_n128_t0(s, q[k], db, 1);
                    }
                    wgmma_commit();
                    return stk;
                };
                auto issue_pv = [&](bool fresh) -> uint32_t {
                    const uint32_t vbuf = wait_full();
                    const uint32_t stv = st;
                    advance();
                    wgmma_fence();
#pragma unroll
                    for (int k = 0; k < 8; k++) {
                        uint64_t db = make_desc(vbuf + k * 2048, 16384, 1024, 1);
                        wgmma_rs_n128_t1(o, pp[k], db, (!fresh) || k != 0);
                    }
                    wgmma_commit();
                    return stv;
                };
                auto softmax = [&](bool first) {
                    float mx0 = fmaxf(s[0], s[1]), mx1 = fmaxf(s[2], s[3]);
#pragma unroll
                    for (int jj = 1; jj < 16; jj++) {
                        mx0 = fmaxf(mx0, fmaxf(s[4 * jj], s[4 * jj + 1]));
                        mx1 = fmaxf(mx1, fmaxf(s[4 * jj + 2], s[4 * jj + 3]));
                    }
                    mx0 = fmaxf(mx0, __shfl_xor_sync(0xffffffffu, mx0, 1));
                    mx0 = fmaxf(mx0, __shfl_xor_sync(0xffffffffu, mx0, 2));
                    mx1 = fmaxf(mx1, __shfl_xor_sync(0xffffffffu, mx1, 1));
                    mx1 = fmaxf(mx1, __shfl_xor_sync(0xffffffffu, mx1, 2));
                    if (first) {
                        lo0 = l0; lo1 = l1;
                        mm0 = mx0; mm1 = mx1; l0 = 0.f; l1 = 0.f; a0 = 0.f; a1 = 0.f;
                    } else {
                        float mn0 = fmaxf(mm0, mx0), mn1 = fmaxf(mm1, mx1);
                        a0 = ex2((mm0 - mn0) * cscale); a1 = ex2((mm1 - mn1) * cscale);
                        mm0 = mn0; mm1 = mn1;
                    }
                    const float mc0 = mm0 * cscale, mc1 = mm1 * cscale;
                    float r0 = 0.f, r1 = 0.f;
#pragma unroll
                    for (int jj = 0; jj < 16; jj++) {
                        e[4 * jj] = ex2(fmaf(s[4 * jj], cscale, -mc0));
                        e[4 * jj + 1] = ex2(fmaf(s[4 * jj + 1], cscale, -mc0));
                        e[4 * jj + 2] = ex2(fmaf(s[4 * jj + 2], cscale, -mc1));
                        e[4 * jj + 3] = ex2(fmaf(s[4 * jj + 3], cscale, -mc1));
                        r0 += e[4 * jj] + e[4 * jj + 1];
                        r1 += e[4 * jj + 2] + e[4 * jj + 3];
                    }
                    l0 = l0 * a0 + r0; l1 = l1 * a1 + r1;
                };
                auto convert_p = [&]() {
#pragma unroll
                    for (int i = 0; i < 8; i++) {
                        pp[i][0] = pack_bf16(e[8 * i + 0], e[8 * i + 1]);
                        pp[i][1] = pack_bf16(e[8 * i + 2], e[8 * i + 3]);
                        pp[i][2] = pack_bf16(e[8 * i + 4], e[8 * i + 5]);
                        pp[i][3] = pack_bf16(e[8 * i + 6], e[8 * i + 7]);
                    }
                };
                auto store_o = [&](float ls0, float ls1, int head, bool last) {
                    float s0 = ls0 + __shfl_xor_sync(0xffffffffu, ls0, 1); s0 += __shfl_xor_sync(0xffffffffu, s0, 2);
                    float s1 = ls1 + __shfl_xor_sync(0xffffffffu, ls1, 1); s1 += __shfl_xor_sync(0xffffffffu, s1, 2);
                    const float i0 = 1.f / s0, i1 = 1.f / s1;
                    if (tid == 0) {
                        tma_store_wait<0>();
                        if (last) {
                            mbar_arrive_cluster(bars + 8 * BD1A, 0);
                            mbar_arrive_cluster(bars + 8 * BD1A, 1);
                        }
                    }
                    bar_sync(1 + wg, 128);
#pragma unroll
                    for (int jj = 0; jj < 16; jj += 2) {
                        const int mi = lane >> 3;
                        const int row = warp * 16 + (mi & 1) * 8 + (lane & 7);
                        const int grp = jj + (mi >> 1);
                        const uint32_t addr = mystage + (grp >> 3) * 8192 + row * 128 + (((grp & 7) ^ (row & 7)) << 4);
                        stmatrix_x4(addr, pack_bf16(o[4 * jj] * i0, o[4 * jj + 1] * i0), pack_bf16(o[4 * jj + 2] * i1, o[4 * jj + 3] * i1),
                                    pack_bf16(o[4 * jj + 4] * i0, o[4 * jj + 5] * i0), pack_bf16(o[4 * jj + 6] * i1, o[4 * jj + 7] * i1));
                    }
                    fence_proxy_async();
                    bar_sync(1 + wg, 128);
                    if (tid == 0) {
                        tma_store_2d(&tm.o_st, mystage, head * 128, m0 + wg * 64);
                        tma_store_2d(&tm.o_st, mystage + 8192, head * 128 + 64, m0 + wg * 64);
                        tma_store_commit();
                        if (last) {
                            tma_store_wait<0>();
                            mbar_arrive_cluster(bars + 8 * BD1, 0);
                            mbar_arrive_cluster(bars + 8 * BD1, 1);
                            flag_signal_relaxed(F_O + mt * 4 + (j >> 1));
                        }
                    }
                };

                l0 = 0.f; l1 = 0.f;
                {
                    turn_wait();
                    uint32_t stk = issue_s();
                    turn_pass();
                    wgmma_wait<0>();
                    fence_regs(s);
                    release(stk);
                    softmax(true);
                    convert_p();
                }
#pragma unroll 1
                for (int t = 1; t < 8; t++) {
                    const bool first = (t == 4);
                    if (t == 4) {
#pragma unroll
                        for (int i = 0; i < 8; i++) {
                            asm volatile("ld.shared.v4.b32 {%0, %1, %2, %3}, [%4];" : "=r"(q[i][0]), "=r"(q[i][1]), "=r"(q[i][2]), "=r"(q[i][3])
                                         : "r"(mystage + (i * 128 + tid) * 16) : "memory");
                        }
                    }
                    turn_wait();
                    uint32_t stk = issue_s();
                    uint32_t stv = issue_pv(t == 1 || t == 5);
                    turn_pass();
                    wgmma_wait<1>();
                    fence_regs(s);
                    release(stk);
                    softmax(first);
                    asm volatile("{\n.reg .pred p;\nsetp.lt.f32 p, %0, 0fBF800000;\n@p st.shared.f32 [%1], %0;\n}\n" ::"f"(l0 + l1), "r"(mystage) : "memory");
                    wgmma_wait<0>();
                    fence_regs(o);
                    release(stv);
                    if (first) {
                        store_o(lo0, lo1, head0, false);
                    } else {
#pragma unroll
                        for (int jj = 0; jj < 16; jj++) {
                            o[4 * jj] *= a0; o[4 * jj + 1] *= a0; o[4 * jj + 2] *= a1; o[4 * jj + 3] *= a1;
                        }
                    }
                    convert_p();
                }
                {
                    turn_wait();
                    uint32_t stv = issue_pv(false);
                    turn_pass();
                    wgmma_wait<0>();
                    fence_regs(o);
                    release(stv);
                    store_o(l0, l1, head0 + 1, hp == 1);
                }
            }
        }
        TS(0, 4);
        {
            const int kq = j >> 1, n0 = (j & 1) * 320;
            float acc0[96], acc1[64];
#pragma unroll
            for (int i = 0; i < 96; i++) acc0[i] = 0.f;
#pragma unroll
            for (int i = 0; i < 64; i++) acc1[i] = 0.f;
            uint32_t st = 0, ph = 0, prev = 0;
            for (int i = 0; i < 16; i++) {
                mbar_wait(bars + 8 * (B2F + st), ph);
                if (i == 0) TS(0, 5);
                const uint32_t buf = base + st * P2_STAGE;
                wgmma_fence();
#pragma unroll
                for (int k = 0; k < 4; k++) {
                    uint64_t da = make_desc(buf + wg * 8192 + k * 32, 16, 1024, 1);
                    wgmma_ss_n192_t1(acc0, da, make_desc(buf + 16384 + k * 2048, 8192, 1024, 1), 1);
                    wgmma_ss_n128_t1(acc1, da, make_desc(buf + 16384 + 3 * 8192 + k * 2048, 8192, 1024, 1), 1);
                }
                wgmma_commit();
                if (i > 0) { wgmma_wait<1>(); arrive_both(bars + 8 * (B2E + prev)); }
                prev = st;
                if (++st == 4) { st = 0; ph ^= 1; }
            }
            wgmma_wait<0>();
            fence_regs(acc0); fence_regs(acc1);
            TS(0, 6);
            bar_sync(5, 256);
            TS(4, 0);
            const uint32_t stg = base + wg * 40960;
            const int mi = lane >> 3;
            const int row = warp * 16 + (mi & 1) * 8 + (lane & 7);
#pragma unroll
            for (int jj = 0; jj < 24; jj += 2) {
                const int grp = jj + (mi >> 1);
                stmatrix_x4(stg + (grp >> 3) * 8192 + row * 128 + (((grp & 7) ^ (row & 7)) << 4),
                            pack_bf16(acc0[4 * jj], acc0[4 * jj + 1]), pack_bf16(acc0[4 * jj + 2], acc0[4 * jj + 3]),
                            pack_bf16(acc0[4 * jj + 4], acc0[4 * jj + 5]), pack_bf16(acc0[4 * jj + 6], acc0[4 * jj + 7]));
            }
#pragma unroll
            for (int jj = 0; jj < 16; jj += 2) {
                const int grp = jj + (mi >> 1);
                stmatrix_x4(stg + (3 + (grp >> 3)) * 8192 + row * 128 + (((grp & 7) ^ (row & 7)) << 4),
                            pack_bf16(acc1[4 * jj], acc1[4 * jj + 1]), pack_bf16(acc1[4 * jj + 2], acc1[4 * jj + 3]),
                            pack_bf16(acc1[4 * jj + 4], acc1[4 * jj + 5]), pack_bf16(acc1[4 * jj + 6], acc1[4 * jj + 7]));
            }
            TS(4, 1);
            fence_proxy_async();
            bar_sync(1 + wg, 128);
            TS(4, 2);
            if (tid == 0) {
#pragma unroll
                for (int c = 0; c < 5; c++) tma_store_2d(&tm.part_st, stg + c * 8192, n0 + c * 64, kq * S_LEN + m0 + wg * 64);
                tma_store_commit();
                TS(4, 3);
                tma_store_wait<0>();
                TS(4, 4);
                mbar_arrive_cluster(bars + 8 * BD2, 0);
                mbar_arrive_cluster(bars + 8 * BD2, 1);
                flag_signal_relaxed(F_P + mt);
            }
        }
        TS(0, 7);
        {
            uint2 xr[2][5];
#pragma unroll
            for (int rr = 0; rr < 2; rr++)
#pragma unroll
                for (int i = 0; i < 5; i++)
                    xr[rr][i] = __ldg(reinterpret_cast<const uint2*>(x + (size_t)(m0 + j * 16 + cw * 2 + rr) * D_MODEL + (lane + 32 * i) * 4));
            if (threadIdx.x == 0) { flag_wait(F_MODALL, (epoch + 1) * 80); flag_wait(F_P + mt, (epoch + 1) * 16); }
            bar_sync(5, 256);
            TS(0, 8);
            uint2 pr[2][4][5];
            float4 gv[5];
#pragma unroll
            for (int rr = 0; rr < 2; rr++)
#pragma unroll
                for (int s = 0; s < 4; s++)
#pragma unroll
                    for (int i = 0; i < 5; i++)
                        pr[rr][s][i] = ldcg_u2(g_part + ((size_t)s * S_LEN + m0 + j * 16 + cw * 2 + rr) * D_MODEL + (lane + 32 * i) * 4);
#pragma unroll
            for (int i = 0; i < 5; i++) gv[i] = __ldcg(reinterpret_cast<const float4*>(g_mod + 2 * D_MODEL + (lane + 32 * i) * 4));
#pragma unroll
            for (int rr = 0; rr < 2; rr++) {
#pragma unroll
                for (int i = 0; i < 5; i++) {
                    float a0 = (bf16lo(pr[rr][0][i].x) + bf16lo(pr[rr][1][i].x)) + (bf16lo(pr[rr][2][i].x) + bf16lo(pr[rr][3][i].x));
                    float a1 = (bf16hi(pr[rr][0][i].x) + bf16hi(pr[rr][1][i].x)) + (bf16hi(pr[rr][2][i].x) + bf16hi(pr[rr][3][i].x));
                    float a2 = (bf16lo(pr[rr][0][i].y) + bf16lo(pr[rr][1][i].y)) + (bf16lo(pr[rr][2][i].y) + bf16lo(pr[rr][3][i].y));
                    float a3 = (bf16hi(pr[rr][0][i].y) + bf16hi(pr[rr][1][i].y)) + (bf16hi(pr[rr][2][i].y) + bf16hi(pr[rr][3][i].y));
                    xr[rr][i].x = pack_bf16(bf16lo(xr[rr][i].x) + gv[i].x * a0, bf16hi(xr[rr][i].x) + gv[i].y * a1);
                    xr[rr][i].y = pack_bf16(bf16lo(xr[rr][i].y) + gv[i].z * a2, bf16hi(xr[rr][i].y) + gv[i].w * a3);
                    *reinterpret_cast<uint2*>(g_x1 + (size_t)(m0 + j * 16 + cw * 2 + rr) * D_MODEL + (lane + 32 * i) * 4) = xr[rr][i];
                }
            }
            TS(5, 0);
            ln_rows(xr, g_mod + 3 * D_MODEL, g_mod + 4 * D_MODEL, g_h2 + (size_t)(m0 + j * 16 + cw * 2) * D_MODEL, lane);
            TS(5, 1);
            bar_sync(5, 256);
            TS(5, 2);
            if (threadIdx.x == 0) flag_signal(F_H2 + mt);
        }
        TS(0, 9);
        {
            const int f0 = j * 216;
            uint32_t st = 0, ph = 0, prev = 0;
            {
                float acc[128];
#pragma unroll
                for (int i = 0; i < 128; i++) acc[i] = 0.f;
                if (wg == 1) bar_sync(6, 256);
                for (int i = 0; i < 10; i++) {
                    mbar_wait(bars + 8 * (B4F + st), ph);
                    if (i == 0) TS(0, 10);
                    const uint32_t buf = base + st * P4_STAGE;
                    wgmma_fence();
#pragma unroll
                    for (int k = 0; k < 4; k++) {
                        uint64_t da = make_desc(buf + wg * 8192 + k * 32, 16, 1024, 1);
                        uint64_t db = make_desc(buf + 16384 + k * 2048, 8192, 1024, 1);
                        wgmma_ss_n256_t1(acc, da, db, 1);
                    }
                    wgmma_commit();
                    if (i == 1 && wg == 0) bar_arrive(6, 256);
                    if (i > 0) { wgmma_wait<1>(); arrive_both(bars + 8 * (B4E + prev)); }
                    prev = st;
                    if (++st == 4) { st = 0; ph ^= 1; }
                }
                wgmma_wait<0>();
                arrive_both(bars + 8 * (B4E + prev));
                fence_regs(acc);
                TS(2, 0);
#pragma unroll
                for (int jj = 0; jj < 16; jj += 2) {
                    const int mi = lane >> 3;
                    const int row = warp * 16 + (mi & 1) * 8 + (lane & 7);
                    const int grp = jj + (mi >> 1);
                    const uint32_t addr = mystage + (grp >> 3) * 8192 + row * 128 + (((grp & 7) ^ (row & 7)) << 4);
                    stmatrix_x4(addr, pack_bf16(silu_mul(acc[4 * jj], acc[64 + 4 * jj]), silu_mul(acc[4 * jj + 1], acc[64 + 4 * jj + 1])),
                                pack_bf16(silu_mul(acc[4 * jj + 2], acc[64 + 4 * jj + 2]), silu_mul(acc[4 * jj + 3], acc[64 + 4 * jj + 3])),
                                pack_bf16(silu_mul(acc[4 * jj + 4], acc[64 + 4 * jj + 4]), silu_mul(acc[4 * jj + 5], acc[64 + 4 * jj + 5])),
                                pack_bf16(silu_mul(acc[4 * jj + 6], acc[64 + 4 * jj + 6]), silu_mul(acc[4 * jj + 7], acc[64 + 4 * jj + 7])));
                }
                fence_proxy_async();
                bar_sync(1 + wg, 128);
                TS(2, 1);
                if (tid == 0) {
                    tma_store_2d(&tm.act_st64, mystage, f0, m0 + wg * 64);
                    tma_store_2d(&tm.act_st64, mystage + 8192, f0 + 64, m0 + wg * 64);
                    tma_store_commit();
                }
                TS(2, 2);
            }
            {
                float acc[92];
#pragma unroll
                for (int i = 0; i < 92; i++) acc[i] = 0.f;
                for (int i = 0; i < 10; i++) {
                    mbar_wait(bars + 8 * (B4F + st), ph);
                    const uint32_t buf = base + st * P4_STAGE;
                    wgmma_fence();
#pragma unroll
                    for (int k = 0; k < 4; k++) {
                        uint64_t da = make_desc(buf + wg * 8192 + k * 32, 16, 1024, 1);
                        uint64_t db = make_desc(buf + 16384 + k * 1024, 4096, 512, 2);
                        wgmma_ss_n184_t1(acc, da, db, 1);
                    }
                    wgmma_commit();
                    if (i == 3 && tid == 0) { tma_store_wait<0>(); flag_signal_relaxed(F_A1 + mt); }
                    if (i > 0) { wgmma_wait<1>(); arrive_both(bars + 8 * (B4E + prev)); }
                    prev = st;
                    if (++st == 4) { st = 0; ph ^= 1; }
                }
                wgmma_wait<0>();
                arrive_both(bars + 8 * BD4);
                fence_regs(acc);
                TS(0, 11);
                bar_sync(1 + wg, 128);
                TS(2, 3);
#pragma unroll
                for (int jj = 0; jj < 8; jj += 2) {
                    const int mi = lane >> 3;
                    const int row = warp * 16 + (mi & 1) * 8 + (lane & 7);
                    const int grp = jj + (mi >> 1);
                    const uint32_t addr = mystage + row * 128 + ((grp ^ (row & 7)) << 4);
                    stmatrix_x4(addr, pack_bf16(silu_mul(acc[4 * jj], acc[48 + 4 * jj]), silu_mul(acc[4 * jj + 1], acc[48 + 4 * jj + 1])),
                                pack_bf16(silu_mul(acc[4 * jj + 2], acc[48 + 4 * jj + 2]), silu_mul(acc[4 * jj + 3], acc[48 + 4 * jj + 3])),
                                pack_bf16(silu_mul(acc[4 * jj + 4], acc[48 + 4 * jj + 4]), silu_mul(acc[4 * jj + 5], acc[48 + 4 * jj + 5])),
                                pack_bf16(silu_mul(acc[4 * jj + 6], acc[48 + 4 * jj + 6]), silu_mul(acc[4 * jj + 7], acc[48 + 4 * jj + 7])));
                }
                {
                    const int mi = lane >> 3;
                    const int row = warp * 16 + (mi & 1) * 8 + (lane & 7);
                    const uint32_t addr = mystage + 8192 + row * 48 + (mi >> 1) * 16;
                    stmatrix_x4(addr, pack_bf16(silu_mul(acc[32], acc[80]), silu_mul(acc[33], acc[81])),
                                pack_bf16(silu_mul(acc[34], acc[82]), silu_mul(acc[35], acc[83])),
                                pack_bf16(silu_mul(acc[36], acc[84]), silu_mul(acc[37], acc[85])),
                                pack_bf16(silu_mul(acc[38], acc[86]), silu_mul(acc[39], acc[87])));
                    const uint32_t addr2 = mystage + 8192 + (warp * 16 + ((lane >> 3) & 1) * 8 + (lane & 7)) * 48 + 32;
                    asm volatile("stmatrix.sync.aligned.m8n8.x2.shared.b16 [%0], {%1, %2};" ::"r"(addr2),
                                 "r"(pack_bf16(silu_mul(acc[40], acc[88]), silu_mul(acc[41], acc[89]))),
                                 "r"(pack_bf16(silu_mul(acc[42], acc[90]), silu_mul(acc[43], acc[91]))) : "memory");
                }
                fence_proxy_async();
                bar_sync(1 + wg, 128);
                TS(2, 4);
                if (tid == 0) {
                    tma_store_2d(&tm.act_st64, mystage, f0 + 128, m0 + wg * 64);
                    tma_store_2d(&tm.act_st24, mystage + 8192, f0 + 192, m0 + wg * 64);
                    tma_store_commit();
                    TS(2, 5);
                    tma_store_wait<0>();
                    TS(2, 6);
                    mbar_arrive_cluster(bars + 8 * BD4B, 0);
                    mbar_arrive_cluster(bars + 8 * BD4B, 1);
                    TS(2, 7);
                    flag_signal_relaxed(F_A + mt);
                    TS(2, 8);
                }
            }
        }
        TS(0, 12);
        {
            const int m5 = (p * 2 + (j >> 2)) * 128, n0 = (j & 3) * 160;
            const int nkb = rank == 0 ? 14 : 13;
            float accA[64], accB[16];
#pragma unroll
            for (int i = 0; i < 64; i++) accA[i] = 0.f;
#pragma unroll
            for (int i = 0; i < 16; i++) accB[i] = 0.f;
            uint32_t st = 0, ph = 0, prev = 0;
            const int cbase = n0 + (int)rank * 80;
            for (int i = 0; i < nkb; i++) {
                mbar_wait(bars + 8 * (B5F + st), ph);
                if (i == 0) TS(0, 13);
                const uint32_t buf = base + st * P5_STAGE;
                wgmma_fence();
#pragma unroll
                for (int k = 0; k < 4; k++) {
                    uint64_t da = make_desc(buf + wg * 8192 + k * 32, 16, 1024, 1);
                    wgmma_ss_n128_t1(accA, da, make_desc(buf + 16384 + k * 2048, 8192, 1024, 1), 1);
                    wgmma_ss_n32_t1(accB, da, make_desc(buf + 32768 + k * 1024, 4096, 512, 2), 1);
                }
                wgmma_commit();
                if (i > 0) {
                    wgmma_wait<1>();
                    if (tid == 0) mbar_arrive(bars + 8 * (B5E + prev));
                }
                prev = st;
                if (++st == 5) { st = 0; ph ^= 1; }
            }
            uint4 xv[5];
            float2 gbv[10];
#pragma unroll
            for (int it = 0; it < 5; it++) {
                const int idx = it * 256 + (int)threadIdx.x;
                const int row = idx / 10, ch = idx - row * 10;
                xv[it] = __ldcg(reinterpret_cast<const uint4*>(g_x1 + (size_t)(m5 + row) * D_MODEL + cbase + ch * 8));
            }
#pragma unroll
            for (int jj = 0; jj < 10; jj++) gbv[jj] = __ldcg(reinterpret_cast<const float2*>(g_mod + 5 * D_MODEL + cbase + jj * 8 + (lane & 3) * 2));
            wgmma_wait<0>();
            fence_regs(accA); fence_regs(accB);
            float acc[80];
#pragma unroll
            for (int i = 0; i < 64; i++) acc[i] = accA[i];
#pragma unroll
            for (int i = 0; i < 16; i++) acc[64 + i] = accB[i];
            TS(0, 14);
            constexpr uint32_t XBUF = 5 * P5_STAGE;
            mbar_wait(bars + 8 * BD4B, 0);
            {
                const uint32_t dst = mapa(base + XBUF, rank ^ 1) + wg * 20480 + tid * 16;
                const uint32_t rbar = mapa(bars + 8 * BX, rank ^ 1);
                if (rank == 0) {
#pragma unroll
                    for (int i = 0; i < 10; i++)
                        asm volatile("st.async.shared::cluster.mbarrier::complete_tx::bytes.v4.f32 [%0], {%1, %2, %3, %4}, [%5];" ::"r"(dst + i * 2048),
                                     "f"(acc[40 + 4 * i]), "f"(acc[40 + 4 * i + 1]), "f"(acc[40 + 4 * i + 2]), "f"(acc[40 + 4 * i + 3]), "r"(rbar) : "memory");
                } else {
#pragma unroll
                    for (int i = 0; i < 10; i++)
                        asm volatile("st.async.shared::cluster.mbarrier::complete_tx::bytes.v4.f32 [%0], {%1, %2, %3, %4}, [%5];" ::"r"(dst + i * 2048),
                                     "f"(acc[4 * i]), "f"(acc[4 * i + 1]), "f"(acc[4 * i + 2]), "f"(acc[4 * i + 3]), "r"(rbar) : "memory");
                }
            }
            mbar_wait(bars + 8 * BX, 0);
            {
                bar_sync(5, 256);
                const uint32_t tile = base;
#pragma unroll
                for (int jj = 0; jj < 10; jj += 2) {
                    float4 o0, o1;
                    asm volatile("ld.shared.v4.f32 {%0, %1, %2, %3}, [%4];" : "=f"(o0.x), "=f"(o0.y), "=f"(o0.z), "=f"(o0.w) : "r"(base + XBUF + wg * 20480 + tid * 16 + jj * 2048));
                    asm volatile("ld.shared.v4.f32 {%0, %1, %2, %3}, [%4];" : "=f"(o1.x), "=f"(o1.y), "=f"(o1.z), "=f"(o1.w) : "r"(base + XBUF + wg * 20480 + tid * 16 + (jj + 1) * 2048));
                    const float2 g0 = gbv[jj], g1 = gbv[jj + 1];
                    float a[8];
#pragma unroll
                    for (int ee = 0; ee < 8; ee++) a[ee] = rank == 0 ? acc[4 * jj + ee] : acc[40 + 4 * jj + ee];
                    const int mi = lane >> 3;
                    const int row = wg * 64 + warp * 16 + (mi & 1) * 8 + (lane & 7);
                    const uint32_t addr = tile + row * 176 + (jj + (mi >> 1)) * 16;
                    stmatrix_x4(addr, pack_bf16(g0.x * bf16_round(a[0] + o0.x), g0.y * bf16_round(a[1] + o0.y)),
                                pack_bf16(g0.x * bf16_round(a[2] + o0.z), g0.y * bf16_round(a[3] + o0.w)),
                                pack_bf16(g1.x * bf16_round(a[4] + o1.x), g1.y * bf16_round(a[5] + o1.y)),
                                pack_bf16(g1.x * bf16_round(a[6] + o1.z), g1.y * bf16_round(a[7] + o1.w)));
                }
                bar_sync(5, 256);
#pragma unroll
                for (int it = 0; it < 5; it++) {
                    const int idx = it * 256 + (int)threadIdx.x;
                    const int row = idx / 10, ch = idx - row * 10;
                    uint4 tv;
                    asm volatile("ld.shared.v4.b32 {%0, %1, %2, %3}, [%4];" : "=r"(tv.x), "=r"(tv.y), "=r"(tv.z), "=r"(tv.w) : "r"(tile + row * 176 + ch * 16));
                    uint4 r;
                    r.x = pack_bf16(bf16lo(xv[it].x) + bf16lo(tv.x), bf16hi(xv[it].x) + bf16hi(tv.x));
                    r.y = pack_bf16(bf16lo(xv[it].y) + bf16lo(tv.y), bf16hi(xv[it].y) + bf16hi(tv.y));
                    r.z = pack_bf16(bf16lo(xv[it].z) + bf16lo(tv.z), bf16hi(xv[it].z) + bf16hi(tv.z));
                    r.w = pack_bf16(bf16lo(xv[it].w) + bf16lo(tv.w), bf16hi(xv[it].w) + bf16hi(tv.w));
                    *reinterpret_cast<uint4*>(out + (size_t)(m5 + row) * D_MODEL + cbase + ch * 8) = r;
                }
            }
            TS(0, 15);
            if (threadIdx.x == 0) {
                const unsigned old = atomicAdd(&g_exit, 1u);
                if (old == (epoch + 1) * 128u - 1u) {
                    asm volatile("st.volatile.global.u32 [%0], %1;" ::"l"(&g_epoch), "r"(epoch + 1) : "memory");
                }
            }
            asm volatile("barrier.cluster.arrive.relaxed.aligned;\n barrier.cluster.wait.aligned;" ::: "memory");
        }
    }
}

typedef CUresult (*PFN_encodeTiled)(CUtensorMap*, CUtensorMapDataType, cuuint32_t, void*, const cuuint64_t*, const cuuint64_t*,
                                    const cuuint32_t*, const cuuint32_t*, CUtensorMapInterleave, CUtensorMapSwizzle,
                                    CUtensorMapL2promotion, CUtensorMapFloatOOBfill);

static PFN_encodeTiled get_encode() {
    static PFN_encodeTiled fn = nullptr;
    if (!fn) {
        void* p = nullptr;
        cudaDriverEntryPointQueryResult qr;
        cudaGetDriverEntryPoint("cuTensorMapEncodeTiled", &p, cudaEnableDefault, &qr);
        fn = (PFN_encodeTiled)p;
    }
    return fn;
}

static CUtensorMap make_map(const void* ptr, uint64_t rows, uint64_t cols, uint32_t box_rows, uint32_t box_cols, CUtensorMapSwizzle swz) {
    CUtensorMap m;
    cuuint64_t dims[2] = {cols, rows};
    cuuint64_t strides[1] = {cols * 2};
    cuuint32_t box[2] = {box_cols, box_rows};
    cuuint32_t es[2] = {1, 1};
    get_encode()(&m, CU_TENSOR_MAP_DATA_TYPE_BFLOAT16, 2, const_cast<void*>(ptr), dims, strides, box, es, CU_TENSOR_MAP_INTERLEAVE_NONE,
                 swz, CU_TENSOR_MAP_L2_PROMOTION_L2_256B, CU_TENSOR_MAP_FLOAT_OOB_FILL_NONE);
    return m;
}

extern "C" void kernel_launch(void* const* d_in, const int* in_sizes, int n_in, void* d_out, int out_size) {
    (void)in_sizes; (void)n_in; (void)out_size;
    const __nv_bfloat16* x = (const __nv_bfloat16*)d_in[0];
    const __nv_bfloat16* kc = (const __nv_bfloat16*)d_in[1];
    const __nv_bfloat16* vc = (const __nv_bfloat16*)d_in[2];
    const __nv_bfloat16* wq = (const __nv_bfloat16*)d_in[3];
    const __nv_bfloat16* wo = (const __nv_bfloat16*)d_in[4];
    const __nv_bfloat16* wg = (const __nv_bfloat16*)d_in[6];
    const __nv_bfloat16* wu = (const __nv_bfloat16*)d_in[7];
    const __nv_bfloat16* wd = (const __nv_bfloat16*)d_in[8];
    const __nv_bfloat16* c = (const __nv_bfloat16*)d_in[9];
    const __nv_bfloat16* wmod = (const __nv_bfloat16*)d_in[10];
    __nv_bfloat16* out = (__nv_bfloat16*)d_out;

    static bool init = false;
    static void *p_h, *p_o, *p_x1, *p_h2, *p_act, *p_part;
    if (!init) {
        cudaFuncSetAttribute(mega_kernel, cudaFuncAttributeMaxDynamicSharedMemorySize, SM_TOTAL);
        cudaGetSymbolAddress(&p_h, g_h);
        cudaGetSymbolAddress(&p_o, g_o);
        cudaGetSymbolAddress(&p_x1, g_x1);
        cudaGetSymbolAddress(&p_h2, g_h2);
        cudaGetSymbolAddress(&p_act, g_act);
        cudaGetSymbolAddress(&p_part, g_part);
        init = true;
    }
    const CUtensorMapSwizzle S128 = CU_TENSOR_MAP_SWIZZLE_128B, S64 = CU_TENSOR_MAP_SWIZZLE_64B;
    Maps tm;
    tm.h = make_map(p_h, S_LEN, D_MODEL, 128, 64, S128);
    tm.wq = make_map(wq, D_MODEL, N_HEADS * D_HEAD, 64, 64, S128);
    tm.k = make_map(kc, N_HEADS * S_KV, D_HEAD, 128, 64, S128);
    tm.v = make_map(vc, N_HEADS * S_KV, D_HEAD, 128, 64, S128);
    tm.o_st = make_map(p_o, S_LEN, N_HEADS * D_HEAD, 64, 64, S128);
    tm.o_a = make_map(p_o, S_LEN, N_HEADS * D_HEAD, 128, 64, S128);
    tm.wo = make_map(wo, N_HEADS * D_HEAD, D_MODEL, 64, 64, S128);
    tm.part_st = make_map(p_part, 4 * S_LEN, D_MODEL, 64, 64, S128);
    tm.h2 = make_map(p_h2, S_LEN, D_MODEL, 128, 64, S128);
    tm.g128 = make_map(wg, D_MODEL, D_FF, 64, 64, S128);
    tm.u128 = make_map(wu, D_MODEL, D_FF, 64, 64, S128);
    tm.g64 = make_map(wg, D_MODEL, D_FF, 64, 32, S64);
    tm.u64 = make_map(wu, D_MODEL, D_FF, 64, 32, S64);
    tm.act_st64 = make_map(p_act, S_LEN, D_FF, 64, 64, S128);
    tm.act_st24 = make_map(p_act, S_LEN, D_FF, 64, 24, CU_TENSOR_MAP_SWIZZLE_NONE);
    tm.act_a = make_map(p_act, S_LEN, D_FF, 128, 64, S128);
    tm.wd = make_map(wd, D_FF, D_MODEL, 64, 64, S128);
    tm.wd32 = make_map(wd, D_FF, D_MODEL, 64, 32, S64);

    cudaLaunchConfig_t cfg = {};
    cfg.gridDim = dim3(128);
    cfg.blockDim = dim3(384);
    cfg.dynamicSmemBytes = SM_TOTAL;
    cfg.stream = cudaStreamPerThread;
    cfg.attrs = nullptr;
    cfg.numAttrs = 0;
    cudaLaunchKernelEx(&cfg, mega_kernel, tm, x, c, wmod, out, (const void*)wo, (const void*)wg, (const void*)wu, (const void*)wd);
}
```

```cpp
#include <cuda_runtime.h>
#include <cuda_bf16.h>
#include <cuda.h>
#include <stdint.h>

__device__ __forceinline__ uint32_t smem_u32(const void* p) { return (uint32_t)__cvta_generic_to_shared(p); }

__device__ __forceinline__ void mbar_init(uint32_t bar, uint32_t count) {
    asm volatile("mbarrier.init.shared::cta.b64 [%0], %1;" ::"r"(bar), "r"(count) : "memory");
}
__device__ __forceinline__ void mbar_expect_tx(uint32_t bar, uint32_t bytes) {
    asm volatile("mbarrier.arrive.expect_tx.shared::cta.b64 _, [%0], %1;" ::"r"(bar), "r"(bytes) : "memory");
}
__device__ __forceinline__ void mbar_arrive(uint32_t bar) {
    asm volatile("mbarrier.arrive.shared::cta.b64 _, [%0];" ::"r"(bar) : "memory");
}
__device__ __forceinline__ void mbar_arrive_cluster(uint32_t bar, uint32_t cta) {
    asm volatile(
        "{\n.reg .b32 ra;\n"
        "mapa.shared::cluster.u32 ra, %0, %1;\n"
        "mbarrier.arrive.shared::cluster.b64 _, [ra];\n}\n" ::"r"(bar), "r"(cta)
        : "memory");
}
__device__ __forceinline__ bool mbar_try_wait(uint32_t bar, uint32_t parity) {
    uint32_t ok;
    asm volatile(
        "{\n.reg .pred p;\n"
        "mbarrier.try_wait.parity.shared::cta.b64 p, [%1], %2;\n"
        "selp.u32 %0, 1, 0, p;\n}\n"
        : "=r"(ok)
        : "r"(bar), "r"(parity)
        : "memory");
    return ok != 0;
}
__device__ __forceinline__ bool mbar_try_wait_cluster(uint32_t bar, uint32_t parity) {
    uint32_t ok;
    asm volatile(
        "{\n.reg .pred p;\n"
        "mbarrier.try_wait.parity.shared::cta.b64 p, [%1], %2;\n"
        "selp.u32 %0, 1, 0, p;\n}\n"
        : "=r"(ok)
        : "r"(bar), "r"(parity)
        : "memory");
    return ok != 0;
}
__device__ volatile int g_abort = 0;
__device__ __forceinline__ void mbar_wait(uint32_t bar, uint32_t parity) {
    asm volatile(
        "{\n.reg .pred p;\n.reg .u32 n;\n"
        "mov.u32 n, 0;\n"
        "WAIT_LOOP:\n"
        "mbarrier.try_wait.parity.shared::cta.b64 p, [%0], %1;\n"
        "@p bra WAIT_DONE;\n"
        "add.u32 n, n, 1;\n"
        "setp.lt.u32 p, n, 16777216;\n"
        "@p bra WAIT_LOOP;\n"
        "WAIT_DONE:\n}\n" ::"r"(bar), "r"(parity) : "memory");
}
__device__ __forceinline__ void mbar_wait_cluster(uint32_t bar, uint32_t parity) { mbar_wait(bar, parity); }
__device__ __forceinline__ void fence_mbar_init() { asm volatile("fence.mbarrier_init.release.cluster;" ::: "memory"); }
__device__ __forceinline__ void fence_proxy_async() { asm volatile("fence.proxy.async.shared::cta;" ::: "memory"); }
__device__ __forceinline__ void fence_proxy_async_all() { asm volatile("fence.proxy.async;" ::: "memory"); }
__device__ __forceinline__ void cluster_arrive() { asm volatile("barrier.cluster.arrive.release.aligned;" ::: "memory"); }
__device__ __forceinline__ void cluster_wait() { asm volatile("barrier.cluster.wait.acquire.aligned;" ::: "memory"); }
__device__ __forceinline__ void cluster_sync() { cluster_arrive(); cluster_wait(); }
__device__ __forceinline__ uint32_t cluster_ctarank() {
    uint32_t r;
    asm volatile("mov.u32 %0, %%cluster_ctarank;" : "=r"(r));
    return r;
}
__device__ __forceinline__ void bar_sync(int id, int n) { asm volatile("bar.sync %0, %1;" ::"r"(id), "r"(n) : "memory"); }
__device__ __forceinline__ void bar_arrive(int id, int n) { asm volatile("bar.arrive %0, %1;" ::"r"(id), "r"(n) : "memory"); }
__device__ __forceinline__ void pdl_wait() { asm volatile("griddepcontrol.wait;" ::: "memory"); }
__device__ __forceinline__ void pdl_launch() { asm volatile("griddepcontrol.launch_dependents;" ::: "memory"); }

__device__ __forceinline__ void tma_prefetch_desc(const CUtensorMap* m) {
    asm volatile("prefetch.tensormap [%0];" ::"l"(m) : "memory");
}
__device__ __forceinline__ void tma_load_2d(uint32_t dst, const CUtensorMap* m, int c0, int c1, uint32_t bar) {
    asm volatile(
        "cp.async.bulk.tensor.2d.shared::cluster.global.mbarrier::complete_tx::bytes [%0], [%1, {%3, %4}], [%2];"
        ::"r"(dst), "l"(m), "r"(bar), "r"(c0), "r"(c1)
        : "memory");
}
__device__ __forceinline__ void tma_load_2d_mc(uint32_t dst, const CUtensorMap* m, int c0, int c1, uint32_t bar, uint16_t mask) {
    asm volatile(
        "cp.async.bulk.tensor.2d.shared::cluster.global.mbarrier::complete_tx::bytes.multicast::cluster [%0], [%1, {%3, %4}], [%2], %5;"
        ::"r"(dst), "l"(m), "r"(bar), "r"(c0), "r"(c1), "h"(mask)
        : "memory");
}
__device__ __forceinline__ void tma_store_2d(const CUtensorMap* m, uint32_t src, int c0, int c1) {
    asm volatile("cp.async.bulk.tensor.2d.global.shared::cta.bulk_group [%0, {%2, %3}], [%1];"
                 ::"l"(m), "r"(src), "r"(c0), "r"(c1)
                 : "memory");
}
__device__ __forceinline__ void tma_store_commit() { asm volatile("cp.async.bulk.commit_group;" ::: "memory"); }
template <int N> __device__ __forceinline__ void tma_store_wait_read() {
    asm volatile("cp.async.bulk.wait_group.read %0;" ::"n"(N) : "memory");
}
template <int N> __device__ __forceinline__ void tma_store_wait() {
    asm volatile("cp.async.bulk.wait_group %0;" ::"n"(N) : "memory");
}

__device__ __forceinline__ void wgmma_fence() { asm volatile("wgmma.fence.sync.aligned;" ::: "memory"); }
__device__ __forceinline__ void wgmma_commit() { asm volatile("wgmma.commit_group.sync.aligned;" ::: "memory"); }
template <int N> __device__ __forceinline__ void wgmma_wait() {
    asm volatile("wgmma.wait_group.sync.aligned %0;" ::"n"(N) : "memory");
}
template <int R> __device__ __forceinline__ void reg_alloc() { asm volatile("setmaxnreg.inc.sync.aligned.u32 %0;" ::"n"(R)); }
template <int R> __device__ __forceinline__ void reg_dealloc() { asm volatile("setmaxnreg.dec.sync.aligned.u32 %0;" ::"n"(R)); }

template <int N> __device__ __forceinline__ void fence_regs(float (&r)[N]) {
#pragma unroll
    for (int i = 0; i < N; i++) asm volatile("" : "+f"(r[i])::"memory");
}
template <int N> __device__ __forceinline__ void fence_regs_u(uint32_t (&r)[N][4]) {
#pragma unroll
    for (int i = 0; i < N; i++) {
#pragma unroll
        for (int j = 0; j < 4; j++) asm volatile("" : "+r"(r[i][j])::"memory");
    }
}

__device__ __forceinline__ uint64_t make_desc(uint32_t addr, uint32_t lbo_bytes, uint32_t sbo_bytes, uint32_t swz) {
    return (uint64_t)((addr & 0x3FFFF) >> 4) | ((uint64_t)(lbo_bytes >> 4) << 16) | ((uint64_t)(sbo_bytes >> 4) << 32) |
           ((uint64_t)swz << 62);
}

__device__ __forceinline__ uint32_t pack_bf16(float lo, float hi) {
    uint32_t r;
    asm("cvt.rn.bf16x2.f32 %0, %1, %2;" : "=r"(r) : "f"(hi), "f"(lo));
    return r;
}
__device__ __forceinline__ float bf16_round(float x) { return __bfloat162float(__float2bfloat16_rn(x)); }
__device__ __forceinline__ float bf16lo(uint32_t v) { return __uint_as_float(v << 16); }
__device__ __forceinline__ float bf16hi(uint32_t v) { return __uint_as_float(v & 0xffff0000u); }
__device__ __forceinline__ float ex2(float x) {
    float y;
    asm("ex2.approx.ftz.f32 %0, %1;" : "=f"(y) : "f"(x));
    return y;
}
__device__ __forceinline__ void stmatrix_x4(uint32_t addr, uint32_t r0, uint32_t r1, uint32_t r2, uint32_t r3) {
    asm volatile("stmatrix.sync.aligned.m8n8.x4.shared.b16 [%0], {%1, %2, %3, %4};" ::"r"(addr), "r"(r0), "r"(r1), "r"(r2), "r"(r3)
                 : "memory");
}
__device__ __forceinline__ uint32_t mapa(uint32_t addr, uint32_t cta) {
    uint32_t r;
    asm volatile("mapa.shared::cluster.u32 %0, %1, %2;" : "=r"(r) : "r"(addr), "r"(cta));
    return r;
}
__device__ __forceinline__ void st_cluster_v2(uint32_t addr, float a, float b) {
    asm volatile("st.shared::cluster.v2.f32 [%0], {%1, %2};" ::"r"(addr), "f"(a), "f"(b) : "memory");
}
__device__ __forceinline__ void wgmma_ss_n256_t1(float (&d)[128], uint64_t descA, uint64_t descB, int scaleD) {
    asm volatile("{\n.reg .pred p;\n"
        "setp.ne.b32 p, %130, 0;\n"
        "wgmma.mma_async.sync.aligned.m64n256k16.f32.bf16.bf16 "
        "{%0, %1, %2, %3, %4, %5, %6, %7, %8, %9, %10, %11, %12, %13, %14, %15, "
        "%16, %17, %18, %19, %20, %21, %22, %23, %24, %25, %26, %27, %28, %29, %30, %31, "
        "%32, %33, %34, %35, %36, %37, %38, %39, %40, %41, %42, %43, %44, %45, %46, %47, "
        "%48, %49, %50, %51, %52, %53, %54, %55, %56, %57, %58, %59, %60, %61, %62, %63, "
        "%64, %65, %66, %67, %68, %69, %70, %71, %72, %73, %74, %75, %76, %77, %78, %79, "
        "%80, %81, %82, %83, %84, %85, %86, %87, %88, %89, %90, %91, %92, %93, %94, %95, "
        "%96, %97, %98, %99, %100, %101, %102, %103, %104, %105, %106, %107, %108, %109, %110, %111, "
        "%112, %113, %114, %115, %116, %117, %118, %119, %120, %121, %122, %123, %124, %125, %126, %127}, "
        "%128, %129, p, 1, 1, 0, 1;\n}\n"
        :
          "+f"(d[0]), "+f"(d[1]), "+f"(d[2]), "+f"(d[3]), "+f"(d[4]), "+f"(d[5]), "+f"(d[6]), "+f"(d[7]),
          "+f"(d[8]), "+f"(d[9]), "+f"(d[10]), "+f"(d[11]), "+f"(d[12]), "+f"(d[13]), "+f"(d[14]), "+f"(d[15]),
          "+f"(d[16]), "+f"(d[17]), "+f"(d[18]), "+f"(d[19]), "+f"(d[20]), "+f"(d[21]), "+f"(d[22]), "+f"(d[23]),
          "+f"(d[24]), "+f"(d[25]), "+f"(d[26]), "+f"(d[27]), "+f"(d[28]), "+f"(d[29]), "+f"(d[30]), "+f"(d[31]),
          "+f"(d[32]), "+f"(d[33]), "+f"(d[34]), "+f"(d[35]), "+f"(d[36]), "+f"(d[37]), "+f"(d[38]), "+f"(d[39]),
          "+f"(d[40]), "+f"(d[41]), "+f"(d[42]), "+f"(d[43]), "+f"(d[44]), "+f"(d[45]), "+f"(d[46]), "+f"(d[47]),
          "+f"(d[48]), "+f"(d[49]), "+f"(d[50]), "+f"(d[51]), "+f"(d[52]), "+f"(d[53]), "+f"(d[54]), "+f"(d[55]),
          "+f"(d[56]), "+f"(d[57]), "+f"(d[58]), "+f"(d[59]), "+f"(d[60]), "+f"(d[61]), "+f"(d[62]), "+f"(d[63]),
          "+f"(d[64]), "+f"(d[65]), "+f"(d[66]), "+f"(d[67]), "+f"(d[68]), "+f"(d[69]), "+f"(d[70]), "+f"(d[71]),
          "+f"(d[72]), "+f"(d[73]), "+f"(d[74]), "+f"(d[75]), "+f"(d[76]), "+f"(d[77]), "+f"(d[78]), "+f"(d[79]),
          "+f"(d[80]), "+f"(d[81]), "+f"(d[82]), "+f"(d[83]), "+f"(d[84]), "+f"(d[85]), "+f"(d[86]), "+f"(d[87]),
          "+f"(d[88]), "+f"(d[89]), "+f"(d[90]), "+f"(d[91]), "+f"(d[92]), "+f"(d[93]), "+f"(d[94]), "+f"(d[95]),
          "+f"(d[96]), "+f"(d[97]), "+f"(d[98]), "+f"(d[99]), "+f"(d[100]), "+f"(d[101]), "+f"(d[102]), "+f"(d[103]),
          "+f"(d[104]), "+f"(d[105]), "+f"(d[106]), "+f"(d[107]), "+f"(d[108]), "+f"(d[109]), "+f"(d[110]), "+f"(d[111]),
          "+f"(d[112]), "+f"(d[113]), "+f"(d[114]), "+f"(d[115]), "+f"(d[116]), "+f"(d[117]), "+f"(d[118]), "+f"(d[119]),
          "+f"(d[120]), "+f"(d[121]), "+f"(d[122]), "+f"(d[123]), "+f"(d[124]), "+f"(d[125]), "+f"(d[126]), "+f"(d[127])
        : "l"(descA), "l"(descB), "r"(scaleD));
}

__device__ __forceinline__ void wgmma_rs_n128_t0(float (&d)[64], const uint32_t (&a)[4], uint64_t descB, int scaleD) {
    asm volatile("{\n.reg .pred p;\n"
        "setp.ne.b32 p, %69, 0;\n"
        "wgmma.mma_async.sync.aligned.m64n128k16.f32.bf16.bf16 "
        "{%0, %1, %2, %3, %4, %5, %6, %7, %8, %9, %10, %11, %12, %13, %14, %15, "
        "%16, %17, %18, %19, %20, %21, %22, %23, %24, %25, %26, %27, %28, %29, %30, %31, "
        "%32, %33, %34, %35, %36, %37, %38, %39, %40, %41, %42, %43, %44, %45, %46, %47, "
        "%48, %49, %50, %51, %52, %53, %54, %55, %56, %57, %58, %59, %60, %61, %62, %63}, "
        "{%64, %65, %66, %67}, %68, p, 1, 1, 0;\n}\n"
        :
          "+f"(d[0]), "+f"(d[1]), "+f"(d[2]), "+f"(d[3]), "+f"(d[4]), "+f"(d[5]), "+f"(d[6]), "+f"(d[7]),
          "+f"(d[8]), "+f"(d[9]), "+f"(d[10]), "+f"(d[11]), "+f"(d[12]), "+f"(d[13]), "+f"(d[14]), "+f"(d[15]),
          "+f"(d[16]), "+f"(d[17]), "+f"(d[18]), "+f"(d[19]), "+f"(d[20]), "+f"(d[21]), "+f"(d[22]), "+f"(d[23]),
          "+f"(d[24]), "+f"(d[25]), "+f"(d[26]), "+f"(d[27]), "+f"(d[28]), "+f"(d[29]), "+f"(d[30]), "+f"(d[31]),
          "+f"(d[32]), "+f"(d[33]), "+f"(d[34]), "+f"(d[35]), "+f"(d[36]), "+f"(d[37]), "+f"(d[38]), "+f"(d[39]),
          "+f"(d[40]), "+f"(d[41]), "+f"(d[42]), "+f"(d[43]), "+f"(d[44]), "+f"(d[45]), "+f"(d[46]), "+f"(d[47]),
          "+f"(d[48]), "+f"(d[49]), "+f"(d[50]), "+f"(d[51]), "+f"(d[52]), "+f"(d[53]), "+f"(d[54]), "+f"(d[55]),
          "+f"(d[56]), "+f"(d[57]), "+f"(d[58]), "+f"(d[59]), "+f"(d[60]), "+f"(d[61]), "+f"(d[62]), "+f"(d[63])
        : "r"(a[0]), "r"(a[1]), "r"(a[2]), "r"(a[3]), "l"(descB), "r"(scaleD));
}

__device__ __forceinline__ void wgmma_rs_n128_t0_z(float (&d)[64], const uint32_t (&a)[4], uint64_t descB) {
    asm volatile("{\n.reg .pred p;\n"
        "setp.ne.b32 p, 0, 0;\n"
        "wgmma.mma_async.sync.aligned.m64n128k16.f32.bf16.bf16 "
        "{%0, %1, %2, %3, %4, %5, %6, %7, %8, %9, %10, %11, %12, %13, %14, %15, "
        "%16, %17, %18, %19, %20, %21, %22, %23, %24, %25, %26, %27, %28, %29, %30, %31, "
        "%32, %33, %34, %35, %36, %37, %38, %39, %40, %41, %42, %43, %44, %45, %46, %47, "
        "%48, %49, %50, %51, %52, %53, %54, %55, %56, %57, %58, %59, %60, %61, %62, %63}, "
        "{%64, %65, %66, %67}, %68, p, 1, 1, 0;\n}\n"
        :
          "=f"(d[0]), "=f"(d[1]), "=f"(d[2]), "=f"(d[3]), "=f"(d[4]), "=f"(d[5]), "=f"(d[6]), "=f"(d[7]),
          "=f"(d[8]), "=f"(d[9]), "=f"(d[10]), "=f"(d[11]), "=f"(d[12]), "=f"(d[13]), "=f"(d[14]), "=f"(d[15]),
          "=f"(d[16]), "=f"(d[17]), "=f"(d[18]), "=f"(d[19]), "=f"(d[20]), "=f"(d[21]), "=f"(d[22]), "=f"(d[23]),
          "=f"(d[24]), "=f"(d[25]), "=f"(d[26]), "=f"(d[27]), "=f"(d[28]), "=f"(d[29]), "=f"(d[30]), "=f"(d[31]),
          "=f"(d[32]), "=f"(d[33]), "=f"(d[34]), "=f"(d[35]), "=f"(d[36]), "=f"(d[37]), "=f"(d[38]), "=f"(d[39]),
          "=f"(d[40]), "=f"(d[41]), "=f"(d[42]), "=f"(d[43]), "=f"(d[44]), "=f"(d[45]), "=f"(d[46]), "=f"(d[47]),
          "=f"(d[48]), "=f"(d[49]), "=f"(d[50]), "=f"(d[51]), "=f"(d[52]), "=f"(d[53]), "=f"(d[54]), "=f"(d[55]),
          "=f"(d[56]), "=f"(d[57]), "=f"(d[58]), "=f"(d[59]), "=f"(d[60]), "=f"(d[61]), "=f"(d[62]), "=f"(d[63])
        : "r"(a[0]), "r"(a[1]), "r"(a[2]), "r"(a[3]), "l"(descB));
}

__device__ __forceinline__ void wgmma_rs_n128_t1(float (&d)[64], const uint32_t (&a)[4], uint64_t descB, int scaleD) {
    asm volatile("{\n.reg .pred p;\n"
        "setp.ne.b32 p, %69, 0;\n"
        "wgmma.mma_async.sync.aligned.m64n128k16.f32.bf16.bf16 "
        "{%0, %1, %2, %3, %4, %5, %6, %7, %8, %9, %10, %11, %12, %13, %14, %15, "
        "%16, %17, %18, %19, %20, %21, %22, %23, %24, %25, %26, %27, %28, %29, %30, %31, "
        "%32, %33, %34, %35, %36, %37, %38, %39, %40, %41, %42, %43, %44, %45, %46, %47, "
        "%48, %49, %50, %51, %52, %53, %54, %55, %56, %57, %58, %59, %60, %61, %62, %63}, "
        "{%64, %65, %66, %67}, %68, p, 1, 1, 1;\n}\n"
        :
          "+f"(d[0]), "+f"(d[1]), "+f"(d[2]), "+f"(d[3]), "+f"(d[4]), "+f"(d[5]), "+f"(d[6]), "+f"(d[7]),
          "+f"(d[8]), "+f"(d[9]), "+f"(d[10]), "+f"(d[11]), "+f"(d[12]), "+f"(d[13]), "+f"(d[14]), "+f"(d[15]),
          "+f"(d[16]), "+f"(d[17]), "+f"(d[18]), "+f"(d[19]), "+f"(d[20]), "+f"(d[21]), "+f"(d[22]), "+f"(d[23]),
          "+f"(d[24]), "+f"(d[25]), "+f"(d[26]), "+f"(d[27]), "+f"(d[28]), "+f"(d[29]), "+f"(d[30]), "+f"(d[31]),
          "+f"(d[32]), "+f"(d[33]), "+f"(d[34]), "+f"(d[35]), "+f"(d[36]), "+f"(d[37]), "+f"(d[38]), "+f"(d[39]),
          "+f"(d[40]), "+f"(d[41]), "+f"(d[42]), "+f"(d[43]), "+f"(d[44]), "+f"(d[45]), "+f"(d[46]), "+f"(d[47]),
          "+f"(d[48]), "+f"(d[49]), "+f"(d[50]), "+f"(d[51]), "+f"(d[52]), "+f"(d[53]), "+f"(d[54]), "+f"(d[55]),
          "+f"(d[56]), "+f"(d[57]), "+f"(d[58]), "+f"(d[59]), "+f"(d[60]), "+f"(d[61]), "+f"(d[62]), "+f"(d[63])
        : "r"(a[0]), "r"(a[1]), "r"(a[2]), "r"(a[3]), "l"(descB), "r"(scaleD));
}

__device__ __forceinline__ void wgmma_ss_n184_t1(float (&d)[92], uint64_t descA, uint64_t descB, int scaleD) {
    asm volatile("{\n.reg .pred p;\n"
        "setp.ne.b32 p, %94, 0;\n"
        "wgmma.mma_async.sync.aligned.m64n184k16.f32.bf16.bf16 "
        "{%0, %1, %2, %3, %4, %5, %6, %7, %8, %9, %10, %11, %12, %13, %14, %15, "
        "%16, %17, %18, %19, %20, %21, %22, %23, %24, %25, %26, %27, %28, %29, %30, %31, "
        "%32, %33, %34, %35, %36, %37, %38, %39, %40, %41, %42, %43, %44, %45, %46, %47, "
        "%48, %49, %50, %51, %52, %53, %54, %55, %56, %57, %58, %59, %60, %61, %62, %63, "
        "%64, %65, %66, %67, %68, %69, %70, %71, %72, %73, %74, %75, %76, %77, %78, %79, "
        "%80, %81, %82, %83, %84, %85, %86, %87, %88, %89, %90, %91}, "
        "%92, %93, p, 1, 1, 0, 1;\n}\n"
        :
          "+f"(d[0]), "+f"(d[1]), "+f"(d[2]), "+f"(d[3]), "+f"(d[4]), "+f"(d[5]), "+f"(d[6]), "+f"(d[7]),
          "+f"(d[8]), "+f"(d[9]), "+f"(d[10]), "+f"(d[11]), "+f"(d[12]), "+f"(d[13]), "+f"(d[14]), "+f"(d[15]),
          "+f"(d[16]), "+f"(d[17]), "+f"(d[18]), "+f"(d[19]), "+f"(d[20]), "+f"(d[21]), "+f"(d[22]), "+f"(d[23]),
          "+f"(d[24]), "+f"(d[25]), "+f"(d[26]), "+f"(d[27]), "+f"(d[28]), "+f"(d[29]), "+f"(d[30]), "+f"(d[31]),
          "+f"(d[32]), "+f"(d[33]), "+f"(d[34]), "+f"(d[35]), "+f"(d[36]), "+f"(d[37]), "+f"(d[38]), "+f"(d[39]),
          "+f"(d[40]), "+f"(d[41]), "+f"(d[42]), "+f"(d[43]), "+f"(d[44]), "+f"(d[45]), "+f"(d[46]), "+f"(d[47]),
          "+f"(d[48]), "+f"(d[49]), "+f"(d[50]), "+f"(d[51]), "+f"(d[52]), "+f"(d[53]), "+f"(d[54]), "+f"(d[55]),
          "+f"(d[56]), "+f"(d[57]), "+f"(d[58]), "+f"(d[59]), "+f"(d[60]), "+f"(d[61]), "+f"(d[62]), "+f"(d[63]),
          "+f"(d[64]), "+f"(d[65]), "+f"(d[66]), "+f"(d[67]), "+f"(d[68]), "+f"(d[69]), "+f"(d[70]), "+f"(d[71]),
          "+f"(d[72]), "+f"(d[73]), "+f"(d[74]), "+f"(d[75]), "+f"(d[76]), "+f"(d[77]), "+f"(d[78]), "+f"(d[79]),
          "+f"(d[80]), "+f"(d[81]), "+f"(d[82]), "+f"(d[83]), "+f"(d[84]), "+f"(d[85]), "+f"(d[86]), "+f"(d[87]),
          "+f"(d[88]), "+f"(d[89]), "+f"(d[90]), "+f"(d[91])
        : "l"(descA), "l"(descB), "r"(scaleD));
}

__device__ __forceinline__ void wgmma_ss_n192_t1(float (&d)[96], uint64_t descA, uint64_t descB, int scaleD) {
    asm volatile("{\n.reg .pred p;\n"
        "setp.ne.b32 p, %98, 0;\n"
        "wgmma.mma_async.sync.aligned.m64n192k16.f32.bf16.bf16 "
        "{%0, %1, %2, %3, %4, %5, %6, %7, %8, %9, %10, %11, %12, %13, %14, %15, "
        "%16, %17, %18, %19, %20, %21, %22, %23, %24, %25, %26, %27, %28, %29, %30, %31, "
        "%32, %33, %34, %35, %36, %37, %38, %39, %40, %41, %42, %43, %44, %45, %46, %47, "
        "%48, %49, %50, %51, %52, %53, %54, %55, %56, %57, %58, %59, %60, %61, %62, %63, "
        "%64, %65, %66, %67, %68, %69, %70, %71, %72, %73, %74, %75, %76, %77, %78, %79, "
        "%80, %81, %82, %83, %84, %85, %86, %87, %88, %89, %90, %91, %92, %93, %94, %95}, "
        "%96, %97, p, 1, 1, 0, 1;\n}\n"
        :
          "+f"(d[0]), "+f"(d[1]), "+f"(d[2]), "+f"(d[3]), "+f"(d[4]), "+f"(d[5]), "+f"(d[6]), "+f"(d[7]),
          "+f"(d[8]), "+f"(d[9]), "+f"(d[10]), "+f"(d[11]), "+f"(d[12]), "+f"(d[13]), "+f"(d[14]), "+f"(d[15]),
          "+f"(d[16]), "+f"(d[17]), "+f"(d[18]), "+f"(d[19]), "+f"(d[20]), "+f"(d[21]), "+f"(d[22]), "+f"(d[23]),
          "+f"(d[24]), "+f"(d[25]), "+f"(d[26]), "+f"(d[27]), "+f"(d[28]), "+f"(d[29]), "+f"(d[30]), "+f"(d[31]),
          "+f"(d[32]), "+f"(d[33]), "+f"(d[34]), "+f"(d[35]), "+f"(d[36]), "+f"(d[37]), "+f"(d[38]), "+f"(d[39]),
          "+f"(d[40]), "+f"(d[41]), "+f"(d[42]), "+f"(d[43]), "+f"(d[44]), "+f"(d[45]), "+f"(d[46]), "+f"(d[47]),
          "+f"(d[48]), "+f"(d[49]), "+f"(d[50]), "+f"(d[51]), "+f"(d[52]), "+f"(d[53]), "+f"(d[54]), "+f"(d[55]),
          "+f"(d[56]), "+f"(d[57]), "+f"(d[58]), "+f"(d[59]), "+f"(d[60]), "+f"(d[61]), "+f"(d[62]), "+f"(d[63]),
          "+f"(d[64]), "+f"(d[65]), "+f"(d[66]), "+f"(d[67]), "+f"(d[68]), "+f"(d[69]), "+f"(d[70]), "+f"(d[71]),
          "+f"(d[72]), "+f"(d[73]), "+f"(d[74]), "+f"(d[75]), "+f"(d[76]), "+f"(d[77]), "+f"(d[78]), "+f"(d[79]),
          "+f"(d[80]), "+f"(d[81]), "+f"(d[82]), "+f"(d[83]), "+f"(d[84]), "+f"(d[85]), "+f"(d[86]), "+f"(d[87]),
          "+f"(d[88]), "+f"(d[89]), "+f"(d[90]), "+f"(d[91]), "+f"(d[92]), "+f"(d[93]), "+f"(d[94]), "+f"(d[95])
        : "l"(descA), "l"(descB), "r"(scaleD));
}

__device__ __forceinline__ void wgmma_ss_n128_t1(float (&d)[64], uint64_t descA, uint64_t descB, int scaleD) {
    asm volatile("{\n.reg .pred p;\n"
        "setp.ne.b32 p, %66, 0;\n"
        "wgmma.mma_async.sync.aligned.m64n128k16.f32.bf16.bf16 "
        "{%0, %1, %2, %3, %4, %5, %6, %7, %8, %9, %10, %11, %12, %13, %14, %15, "
        "%16, %17, %18, %19, %20, %21, %22, %23, %24, %25, %26, %27, %28, %29, %30, %31, "
        "%32, %33, %34, %35, %36, %37, %38, %39, %40, %41, %42, %43, %44, %45, %46, %47, "
        "%48, %49, %50, %51, %52, %53, %54, %55, %56, %57, %58, %59, %60, %61, %62, %63}, "
        "%64, %65, p, 1, 1, 0, 1;\n}\n"
        :
          "+f"(d[0]), "+f"(d[1]), "+f"(d[2]), "+f"(d[3]), "+f"(d[4]), "+f"(d[5]), "+f"(d[6]), "+f"(d[7]),
          "+f"(d[8]), "+f"(d[9]), "+f"(d[10]), "+f"(d[11]), "+f"(d[12]), "+f"(d[13]), "+f"(d[14]), "+f"(d[15]),
          "+f"(d[16]), "+f"(d[17]), "+f"(d[18]), "+f"(d[19]), "+f"(d[20]), "+f"(d[21]), "+f"(d[22]), "+f"(d[23]),
          "+f"(d[24]), "+f"(d[25]), "+f"(d[26]), "+f"(d[27]), "+f"(d[28]), "+f"(d[29]), "+f"(d[30]), "+f"(d[31]),
          "+f"(d[32]), "+f"(d[33]), "+f"(d[34]), "+f"(d[35]), "+f"(d[36]), "+f"(d[37]), "+f"(d[38]), "+f"(d[39]),
          "+f"(d[40]), "+f"(d[41]), "+f"(d[42]), "+f"(d[43]), "+f"(d[44]), "+f"(d[45]), "+f"(d[46]), "+f"(d[47]),
          "+f"(d[48]), "+f"(d[49]), "+f"(d[50]), "+f"(d[51]), "+f"(d[52]), "+f"(d[53]), "+f"(d[54]), "+f"(d[55]),
          "+f"(d[56]), "+f"(d[57]), "+f"(d[58]), "+f"(d[59]), "+f"(d[60]), "+f"(d[61]), "+f"(d[62]), "+f"(d[63])
        : "l"(descA), "l"(descB), "r"(scaleD));
}

__device__ __forceinline__ void wgmma_ss_n32_t1(float (&d)[16], uint64_t descA, uint64_t descB, int scaleD) {
    asm volatile("{\n.reg .pred p;\n"
        "setp.ne.b32 p, %18, 0;\n"
        "wgmma.mma_async.sync.aligned.m64n32k16.f32.bf16.bf16 "
        "{%0, %1, %2, %3, %4, %5, %6, %7, %8, %9, %10, %11, %12, %13, %14, %15}, "
        "%16, %17, p, 1, 1, 0, 1;\n}\n"
        :
          "+f"(d[0]), "+f"(d[1]), "+f"(d[2]), "+f"(d[3]), "+f"(d[4]), "+f"(d[5]), "+f"(d[6]), "+f"(d[7]),
          "+f"(d[8]), "+f"(d[9]), "+f"(d[10]), "+f"(d[11]), "+f"(d[12]), "+f"(d[13]), "+f"(d[14]), "+f"(d[15])
        : "l"(descA), "l"(descB), "r"(scaleD));
}

constexpr int S_LEN = 2048;
constexpr int D_MODEL = 640;
constexpr int N_HEADS = 32;
constexpr int D_HEAD = 128;
constexpr int S_KV = 2048;
constexpr int WIN = 512;
constexpr int D_FF = 1728;
constexpr float LN_EPS = 1e-5f;

#define TS(kid, slot)

__device__ float g_mod[6 * D_MODEL];
__device__ __align__(1024) __nv_bfloat16 g_h[S_LEN * D_MODEL];
__device__ __align__(1024) __nv_bfloat16 g_o[S_LEN * N_HEADS * D_HEAD];
__device__ __align__(1024) __nv_bfloat16 g_part[4 * S_LEN * D_MODEL];
__device__ __align__(1024) __nv_bfloat16 g_x1[S_LEN * D_MODEL];
__device__ __align__(1024) __nv_bfloat16 g_h2[S_LEN * D_MODEL];
__device__ __align__(1024) __nv_bfloat16 g_act[S_LEN * D_FF];

constexpr int F_MODAB = 0, F_MODALL = 1, F_H = 2, F_P = 18, F_H2 = 34, F_A = 50, F_O = 66, F_A1 = 130, F_COUNT = 146;
__device__ unsigned g_flags[F_COUNT * 32];
__device__ unsigned g_epoch;
__device__ unsigned g_exit;

__device__ __forceinline__ void flag_signal(int f) {
    asm volatile("red.release.gpu.global.add.u32 [%0], 1;" ::"l"(g_flags + f * 32) : "memory");
}
__device__ __forceinline__ void flag_signal_relaxed(int f) {
    asm volatile("red.relaxed.gpu.global.add.u32 [%0], 1;" ::"l"(g_flags + f * 32) : "memory");
}
__device__ __forceinline__ void flag_wait(int f, unsigned target) {
    unsigned n = 0;
    while (true) {
        unsigned v;
        asm volatile("ld.acquire.gpu.global.u32 %0, [%1];" : "=r"(v) : "l"(g_flags + f * 32) : "memory");
        if ((int)(v - target) >= 0) break;
        if ((++n & 0xfffu) == 0) {
            if (n > (1u << 24)) g_abort = 1;
            if (g_abort) break;
        }
    }
}

struct Maps {
    CUtensorMap h, wq, k, v, o_st, o_a, wo, part_st, h2, g128, u128, g64, u64, act_st64, act_st24, act_a, wd, wd32;
};

constexpr int SM_DATA = 229376;
constexpr int SM_STAGING = 196608;
constexpr int SM_TOTAL = SM_DATA + 1024 + 512;
constexpr int B1F = 0, B1E = 6, B2F = 12, B2E = 16, B4F = 20, B4E = 24, B5F = 28, B5E = 33, BD1 = 38, BD2 = 39, BD4 = 40, BD1A = 41, BX = 42, BD4B = 43;
constexpr int P1_STAGE = 32768, P2_STAGE = 57344, P4_STAGE = 49152, P5_STAGE = 36864;

__device__ __forceinline__ float rcp_approx(float x) { float y; asm("rcp.approx.ftz.f32 %0, %1;" : "=f"(y) : "f"(x)); return y; }
__device__ __forceinline__ float silu_mul(float g, float u) { return g * rcp_approx(1.f + ex2(-1.4426950408889634f * g)) * u; }
__device__ __forceinline__ uint2 ldcg_u2(const void* p) { return __ldcg(reinterpret_cast<const uint2*>(p)); }

__device__ __noinline__ void ln_rows_impl(uint2 a0, uint2 a1, uint2 a2, uint2 a3, uint2 a4, uint2 b0, uint2 b1, uint2 b2, uint2 b3, uint2 b4,
                                          const float* __restrict__ shift, const float* __restrict__ scale1p,
                                          __nv_bfloat16* __restrict__ dst, int lane) {
    const uint2 xr[2][5] = {{a0, a1, a2, a3, a4}, {b0, b1, b2, b3, b4}};
    float4 sh[5], sc[5];
#pragma unroll
    for (int i = 0; i < 5; i++) {
        sh[i] = __ldcg(reinterpret_cast<const float4*>(shift + (lane + 32 * i) * 4));
        sc[i] = __ldcg(reinterpret_cast<const float4*>(scale1p + (lane + 32 * i) * 4));
    }
    float mean[2], rstd[2];
#pragma unroll
    for (int rr = 0; rr < 2; rr++) {
        float s = 0.f;
#pragma unroll
        for (int i = 0; i < 5; i++) s += (bf16lo(xr[rr][i].x) + bf16hi(xr[rr][i].x)) + (bf16lo(xr[rr][i].y) + bf16hi(xr[rr][i].y));
#pragma unroll
        for (int o = 16; o > 0; o >>= 1) s += __shfl_xor_sync(0xffffffffu, s, o);
        mean[rr] = s * (1.f / D_MODEL);
    }
#pragma unroll
    for (int rr = 0; rr < 2; rr++) {
        float q = 0.f;
#pragma unroll
        for (int i = 0; i < 5; i++) {
            const float d0 = bf16lo(xr[rr][i].x) - mean[rr], d1 = bf16hi(xr[rr][i].x) - mean[rr];
            const float d2 = bf16lo(xr[rr][i].y) - mean[rr], d3 = bf16hi(xr[rr][i].y) - mean[rr];
            q += (d0 * d0 + d1 * d1) + (d2 * d2 + d3 * d3);
        }
#pragma unroll
        for (int o = 16; o > 0; o >>= 1) q += __shfl_xor_sync(0xffffffffu, q, o);
        rstd[rr] = rsqrtf(q * (1.f / D_MODEL) + LN_EPS);
    }
#pragma unroll
    for (int rr = 0; rr < 2; rr++) {
#pragma unroll
        for (int i = 0; i < 5; i++) {
            uint2 u;
            u.x = pack_bf16((bf16lo(xr[rr][i].x) - mean[rr]) * rstd[rr] * sc[i].x + sh[i].x, (bf16hi(xr[rr][i].x) - mean[rr]) * rstd[rr] * sc[i].y + sh[i].y);
            u.y = pack_bf16((bf16lo(xr[rr][i].y) - mean[rr]) * rstd[rr] * sc[i].z + sh[i].z, (bf16hi(xr[rr][i].y) - mean[rr]) * rstd[rr] * sc[i].w + sh[i].w);
            *reinterpret_cast<uint2*>(dst + (size_t)rr * D_MODEL + (lane + 32 * i) * 4) = u;
        }
    }
}

__device__ __forceinline__ void ln_rows(const uint2 (&xr)[2][5], const float* shift, const float* scale1p, __nv_bfloat16* dst, int lane) {
    ln_rows_impl(xr[0][0], xr[0][1], xr[0][2], xr[0][3], xr[0][4], xr[1][0], xr[1][1], xr[1][2], xr[1][3], xr[1][4], shift, scale1p, dst, lane);
}

__global__ void __cluster_dims__(2, 1, 1) __launch_bounds__(384, 1)
mega_kernel(const __grid_constant__ Maps tm, const __nv_bfloat16* __restrict__ x, const __nv_bfloat16* __restrict__ cvec,
            const __nv_bfloat16* __restrict__ w_mod, __nv_bfloat16* __restrict__ out, const void* wo_p, const void* wg_p,
            const void* wu_p, const void* wd_p) {
    extern __shared__ uint8_t smem_raw[];
    const uint32_t base = (smem_u32(smem_raw) + 1023u) & ~1023u;
    const uint32_t bars = base + SM_DATA;
    const uint32_t rank = cluster_ctarank();
    const int cid = blockIdx.x >> 1;
    const int p = cid & 7, j = cid >> 3;
    const int mt = p * 2 + (int)rank;
    const int m0 = mt * 128;
    const int wg = threadIdx.x >> 7;
    unsigned epoch;
    asm volatile("ld.volatile.global.u32 %0, [%1];" : "=r"(epoch) : "l"(&g_epoch));

    if (threadIdx.x == 0) {
        for (int i = 0; i < 6; i++) { mbar_init(bars + 8 * (B1F + i), 1); mbar_init(bars + 8 * (B1E + i), 4); }
        for (int i = 0; i < 4; i++) { mbar_init(bars + 8 * (B2F + i), 1); mbar_init(bars + 8 * (B2E + i), 4); }
        for (int i = 0; i < 4; i++) { mbar_init(bars + 8 * (B4F + i), 1); mbar_init(bars + 8 * (B4E + i), 4); }
        for (int i = 0; i < 5; i++) { mbar_init(bars + 8 * (B5F + i), 1); mbar_init(bars + 8 * (B5E + i), 2); }
        mbar_init(bars + 8 * BD1, 4); mbar_init(bars + 8 * BD2, 4); mbar_init(bars + 8 * BD4, 4); mbar_init(bars + 8 * BD1A, 4);
        mbar_init(bars + 8 * BX, 1); mbar_init(bars + 8 * BD4B, 4);
        mbar_expect_tx(bars + 8 * BX, 40960);
        fence_mbar_init();
    }
    __syncthreads();
    cluster_sync();

    if (wg == 2) {
        reg_dealloc<40>();
        if (threadIdx.x == 256) {
            {
                uint32_t st = 0, ph = 1;
                bool first = true;
#pragma unroll 1
                for (int hp = 0; hp < 2; hp++) {
                    const int head0 = j * 4 + hp * 2;
                    if (first) {
#pragma unroll 1
                        for (int s = 1; s < 6; s++) {
                            if (s == 3) continue;
                            const int kb = s < 3 ? s - 1 : s - 2;
                            mbar_expect_tx(bars + 8 * (B1F + s), P1_STAGE);
#pragma unroll 1
                            for (int c = 0; c < 2; c++) {
                                const int chunk = 2 * (int)rank + c;
                                tma_load_2d_mc(base + s * P1_STAGE + chunk * 8192, &tm.wq, head0 * 128 + chunk * 64, kb * 64, bars + 8 * (B1F + s), 3);
                            }
                        }
                        flag_wait(F_H + mt, (epoch + 1) * 8);
                        fence_proxy_async_all();
#pragma unroll 1
                        for (int s = 0; s < 6; s += 3) {
                            mbar_expect_tx(bars + 8 * (B1F + s), P1_STAGE);
                            tma_load_2d(base + s * P1_STAGE, &tm.h, (s / 3 * 2) * 64, m0, bars + 8 * (B1F + s));
                            tma_load_2d(base + s * P1_STAGE + 16384, &tm.h, (s / 3 * 2 + 1) * 64, m0, bars + 8 * (B1F + s));
                        }
                        ph = 0;
                    }
#pragma unroll 1
                    for (int kk2 = first ? 2 : 0; kk2 < 5; kk2++) {
                        mbar_wait(bars + 8 * (B1E + st), ph);
                        mbar_expect_tx(bars + 8 * (B1F + st), P1_STAGE);
                        tma_load_2d(base + st * P1_STAGE, &tm.h, (2 * kk2) * 64, m0, bars + 8 * (B1F + st));
                        tma_load_2d(base + st * P1_STAGE + 16384, &tm.h, (2 * kk2 + 1) * 64, m0, bars + 8 * (B1F + st));
                        if (++st == 6) { st = 0; ph ^= 1; }
#pragma unroll 1
                        for (int u = 0; u < 2; u++) {
                            mbar_wait(bars + 8 * (B1E + st), ph);
                            mbar_expect_tx(bars + 8 * (B1F + st), P1_STAGE);
                            const int kb = 2 * kk2 + u;
#pragma unroll 1
                            for (int c = 0; c < 2; c++) {
                                const int chunk = 2 * (int)rank + c;
                                tma_load_2d_mc(base + st * P1_STAGE + chunk * 8192, &tm.wq, head0 * 128 + chunk * 64, kb * 64, bars + 8 * (B1F + st), 3);
                            }
                            if (++st == 6) { st = 0; ph ^= 1; }
                        }
                    }
                    first = false;
#pragma unroll 1
                    for (int t = 0; t <= 8; t++) {
                        if (t < 8) {
                            mbar_wait(bars + 8 * (B1E + st), ph);
                            mbar_expect_tx(bars + 8 * (B1F + st), P1_STAGE);
                            const int row = (head0 + (t >> 2)) * S_KV + (S_KV - WIN) + (t & 3) * 128;
                            tma_load_2d_mc(base + st * P1_STAGE + rank * 16384, &tm.k, rank * 64, row, bars + 8 * (B1F + st), 3);
                            if (++st == 6) { st = 0; ph ^= 1; }
                        }
                        if (t > 0) {
                            mbar_wait(bars + 8 * (B1E + st), ph);
                            mbar_expect_tx(bars + 8 * (B1F + st), P1_STAGE);
                            const int tv = t - 1;
                            const int row = (head0 + (tv >> 2)) * S_KV + (S_KV - WIN) + (tv & 3) * 128;
                            tma_load_2d_mc(base + st * P1_STAGE + rank * 16384, &tm.v, rank * 64, row, bars + 8 * (B1F + st), 3);
                            if (++st == 6) { st = 0; ph ^= 1; }
                        }
                    }
                }
            }
            {
                const int kq = j >> 1, n0 = (j & 1) * 320;
                uint32_t st = 0, ph = 1;
#pragma unroll 1
                for (int i = 0; i < 16; i++) {
                    if (i == 0) mbar_wait(bars + 8 * BD1A, 0);
                    if (i == 3) mbar_wait(bars + 8 * BD1, 0);
                    if (i == 8) { flag_wait(F_O + mt * 4 + kq, (epoch + 1) * 4); fence_proxy_async_all(); }
                    mbar_wait(bars + 8 * (B2E + st), ph);
                    mbar_expect_tx(bars + 8 * (B2F + st), P2_STAGE);
                    const uint32_t dst = base + st * P2_STAGE;
                    const int k0 = kq * 1024 + ((i + (j & 1) * 8) & 15) * 64;
                    tma_load_2d(dst, &tm.o_a, k0, m0, bars + 8 * (B2F + st));
#pragma unroll 1
                    for (int c = 0; c < 5; c++)
                        if (((c + i) & 1) == (int)rank) tma_load_2d_mc(dst + 16384 + c * 8192, &tm.wo, n0 + c * 64, k0, bars + 8 * (B2F + st), 3);
                    if (++st == 4) { st = 0; ph ^= 1; }
                }
            }
            {
                const int f0 = j * 216;
                const CUtensorMap* t128 = rank == 0 ? &tm.g128 : &tm.u128;
                const CUtensorMap* t64 = rank == 0 ? &tm.g64 : &tm.u64;
                mbar_wait(bars + 8 * BD2, 0);
#pragma unroll 1
                for (int i = 0; i < 4; i++) {
                    mbar_expect_tx(bars + 8 * (B4F + i), 16384 + 32768);
                    const uint32_t dst = base + i * P4_STAGE;
                    tma_load_2d_mc(dst + 16384 + rank * 16384, t128, f0, i * 64, bars + 8 * (B4F + i), 3);
                    tma_load_2d_mc(dst + 16384 + rank * 16384 + 8192, t128, f0 + 64, i * 64, bars + 8 * (B4F + i), 3);
                }
                flag_wait(F_H2 + mt, (epoch + 1) * 8);
                fence_proxy_async_all();
#pragma unroll 1
                for (int i = 0; i < 4; i++) tma_load_2d(base + i * P4_STAGE, &tm.h2, i * 64, m0, bars + 8 * (B4F + i));
                uint32_t st = 0, ph = 0;
#pragma unroll 1
                for (int i = 4; i < 20; i++) {
                    const int kb = i < 10 ? i : i - 10;
                    mbar_wait(bars + 8 * (B4E + st), ph);
                    const uint32_t dst = base + st * P4_STAGE;
                    if (i < 10) {
                        mbar_expect_tx(bars + 8 * (B4F + st), 16384 + 32768);
                        tma_load_2d(dst, &tm.h2, kb * 64, m0, bars + 8 * (B4F + st));
                        tma_load_2d_mc(dst + 16384 + rank * 16384, t128, f0, kb * 64, bars + 8 * (B4F + st), 3);
                        tma_load_2d_mc(dst + 16384 + rank * 16384 + 8192, t128, f0 + 64, kb * 64, bars + 8 * (B4F + st), 3);
                    } else {
                        mbar_expect_tx(bars + 8 * (B4F + st), 16384 + 24576);
                        tma_load_2d(dst, &tm.h2, kb * 64, m0, bars + 8 * (B4F + st));
#pragma unroll 1
                        for (int c = 0; c < 3; c++)
                            tma_load_2d_mc(dst + 16384 + rank * 12288 + c * 4096, t64, f0 + 128 + c * 32, kb * 64, bars + 8 * (B4F + st), 3);
                    }
                    if (++st == 4) { st = 0; ph ^= 1; }
                }
            }
            {
                const int mt5 = p * 2 + (j >> 2), n0 = (j & 3) * 160;
                const int nkb = rank == 0 ? 14 : 13;
                const unsigned long long ord = rank == 0
                    ? (0ull | 1ull << 5 | 4ull << 10 | 7ull << 15 | 11ull << 20 | 2ull << 25 | 3ull << 30 | 5ull << 35 | 6ull << 40 | 8ull << 45 | 9ull << 50 | 10ull << 55)
                    : (14ull | 17ull << 5 | 21ull << 10 | 24ull << 15 | 15ull << 20 | 16ull << 25 | 18ull << 30 | 19ull << 35 | 20ull << 40 | 22ull << 45 | 23ull << 50 | 25ull << 55);
                const int nearly = rank == 0 ? 5 : 4;
                mbar_wait(bars + 8 * BD4, 0);
                uint32_t st = 0, ph = 1;
#pragma unroll 1
                for (int i = 0; i < nkb; i++) {
                    const int kb = i < 12 ? (int)((ord >> (5 * i)) & 31) : (rank == 0 ? i : 26);
                    if (i == 0) { flag_wait(F_A1 + mt5, (epoch + 1) * 16); fence_proxy_async_all(); }
                    if (i == nearly) { flag_wait(F_A + mt5, (epoch + 1) * 16); fence_proxy_async_all(); }
                    mbar_wait(bars + 8 * (B5E + st), ph);
                    mbar_expect_tx(bars + 8 * (B5F + st), P5_STAGE);
                    const uint32_t dst = base + st * P5_STAGE;
                    const int k0 = kb * 64;
                    tma_load_2d(dst + 16384, &tm.wd, n0, k0, bars + 8 * (B5F + st));
                    tma_load_2d(dst + 16384 + 8192, &tm.wd, n0 + 64, k0, bars + 8 * (B5F + st));
                    tma_load_2d(dst + 16384 + 16384, &tm.wd32, n0 + 128, k0, bars + 8 * (B5F + st));
                    tma_load_2d(dst, &tm.act_a, k0, mt5 * 128, bars + 8 * (B5F + st));
                    if (++st == 5) { st = 0; ph ^= 1; }
                }
            }
        }
        else if (threadIdx.x == 288) {
            mbar_wait(bars + 8 * B1F, 0);
            const char* pw[4] = {(const char*)wo_p, (const char*)wg_p, (const char*)wu_p, (const char*)wd_p};
#pragma unroll 1
            for (int t = 0; t < 4; t++) {
                const uint32_t bytes = t == 0 ? 40960u : 17280u;
                asm volatile("cp.async.bulk.prefetch.L2.global [%0], %1;" ::"l"(pw[t] + (size_t)blockIdx.x * bytes), "r"(bytes) : "memory");
            }
        }
        __syncwarp();
        asm volatile("barrier.cluster.arrive.relaxed.aligned; // producer\n barrier.cluster.wait.aligned;" ::: "memory");
    } else {
        reg_alloc<232>();
        const int tid = threadIdx.x & 127;
        const int warp = tid >> 5, lane = tid & 31;
        const int cw = threadIdx.x >> 5;
        const uint32_t mystage = base + SM_STAGING + wg * 16384;
        auto arrive_both = [&](uint32_t bar) {
            if (tid == 0) mbar_arrive_cluster(bar, 0);
            if (tid == 32) mbar_arrive_cluster(bar, 1);
        };
        TS(0, 0);
        {
            uint2 xr[2][5];
            uint4 w[10];
            unsigned short cr[10];
            const int mb = blockIdx.x < 120 ? blockIdx.x : 0;
#pragma unroll
            for (int i = 0; i < 10; i++) cr[i] = __ldg(reinterpret_cast<const unsigned short*>(cvec) + cw * 80 + i * 8 + (lane >> 2));
#pragma unroll
            for (int i = 0; i < 10; i++)
                w[i] = __ldg(reinterpret_cast<const uint4*>(w_mod + (size_t)(cw * 80 + i * 8 + (lane >> 2)) * (6 * D_MODEL) + mb * 32 + (lane & 3) * 8));
#pragma unroll
            for (int rr = 0; rr < 2; rr++)
#pragma unroll
                for (int i = 0; i < 5; i++)
                    xr[rr][i] = __ldg(reinterpret_cast<const uint2*>(x + (size_t)(m0 + j * 16 + cw * 2 + rr) * D_MODEL + (lane + 32 * i) * 4));
            if (blockIdx.x < 120) {
                float* red = reinterpret_cast<float*>(smem_raw + (base - smem_u32(smem_raw)) + SM_STAGING);
                float acc[8];
#pragma unroll
                for (int i = 0; i < 8; i++) acc[i] = 0.f;
#pragma unroll
                for (int i = 0; i < 10; i++) {
                    const float s = bf16_round(silu_mul(__uint_as_float((uint32_t)cr[i] << 16), 1.f));
                    acc[0] += s * bf16lo(w[i].x); acc[1] += s * bf16hi(w[i].x);
                    acc[2] += s * bf16lo(w[i].y); acc[3] += s * bf16hi(w[i].y);
                    acc[4] += s * bf16lo(w[i].z); acc[5] += s * bf16hi(w[i].z);
                    acc[6] += s * bf16lo(w[i].w); acc[7] += s * bf16hi(w[i].w);
                }
#pragma unroll
                for (int i = 0; i < 8; i++) {
                    acc[i] += __shfl_xor_sync(0xffffffffu, acc[i], 4);
                    acc[i] += __shfl_xor_sync(0xffffffffu, acc[i], 8);
                    acc[i] += __shfl_xor_sync(0xffffffffu, acc[i], 16);
                }
                if (lane < 4) {
#pragma unroll
                    for (int i = 0; i < 8; i++) red[cw * 32 + lane * 8 + i] = acc[i];
                }
                TS(6, 0);
                bar_sync(5, 256);
                TS(6, 1);
                if (threadIdx.x < 32) {
                    float t = 0.f;
#pragma unroll
                    for (int i = 0; i < 8; i++) t += red[i * 32 + threadIdx.x];
                    t = bf16_round(t);
                    const int chunk = blockIdx.x / 20;
                    if (chunk == 1 || chunk == 4) t = bf16_round(1.f + t);
                    g_mod[blockIdx.x * 32 + threadIdx.x] = t;
                    __syncwarp();
                    TS(6, 2);
                    if (threadIdx.x == 0) flag_signal(blockIdx.x < 40 ? F_MODAB : F_MODALL);
                    TS(6, 3);
                }
            }
            if (threadIdx.x == 0) flag_wait(F_MODAB, (epoch + 1) * 40);
            bar_sync(5, 256);
            TS(0, 1);
            ln_rows(xr, g_mod, g_mod + D_MODEL, g_h + (size_t)(m0 + j * 16 + cw * 2) * D_MODEL, lane);
            TS(6, 4);
            bar_sync(5, 256);
            TS(6, 5);
            if (threadIdx.x == 0) flag_signal(F_H + mt);
        }
        TS(0, 2);
        {
            const float cscale = 0.08838834764831845f * 1.4426950408889634f;
            uint32_t st = 0, ph = 0;
            auto wait_full = [&]() -> uint32_t {
                mbar_wait(bars + 8 * (B1F + st), ph);
                return base + st * P1_STAGE;
            };
            auto release = [&](uint32_t s) { arrive_both(bars + 8 * (B1E + s)); };
            auto advance = [&]() { if (++st == 6) { st = 0; ph ^= 1; } };
            auto turn_wait = [&]() { bar_sync(3 + wg, 256); };
            auto turn_pass = [&]() { bar_arrive(3 + (wg ^ 1), 256); };
            if (wg == 1) bar_arrive(3, 256);

            for (int hp = 0; hp < 2; hp++) {
                const int head0 = j * 4 + hp * 2;
                uint32_t q[8][4];
                {
                    float acc[128];
#pragma unroll
                    for (int i = 0; i < 128; i++) acc[i] = 0.f;
                    for (int kk2 = 0; kk2 < 5; kk2++) {
                        const uint32_t hbuf = wait_full();
                        if (kk2 == 0 && hp == 0) TS(0, 3);
                        const uint32_t sth = st;
                        advance();
#pragma unroll
                        for (int u = 0; u < 2; u++) {
                            const uint32_t wbuf = wait_full();
                            const uint32_t stw = st;
                            advance();
                            wgmma_fence();
#pragma unroll
                            for (int k = 0; k < 4; k++) {
                                uint64_t da = make_desc(hbuf + u * 16384 + wg * 8192 + k * 32, 16, 1024, 1);
                                uint64_t db = make_desc(wbuf + k * 2048, 8192, 1024, 1);
                                wgmma_ss_n256_t1(acc, da, db, 1);
                            }
                            wgmma_commit();
                            wgmma_wait<0>();
                            release(stw);
                        }
                        release(sth);
                    }
                    fence_regs(acc);
                    if (tid == 0) tma_store_wait_read<0>();
                    bar_sync(1 + wg, 128);
#pragma unroll
                    for (int i = 0; i < 8; i++) {
                        q[i][0] = pack_bf16(acc[8 * i + 0], acc[8 * i + 1]);
                        q[i][1] = pack_bf16(acc[8 * i + 2], acc[8 * i + 3]);
                        q[i][2] = pack_bf16(acc[8 * i + 4], acc[8 * i + 5]);
                        q[i][3] = pack_bf16(acc[8 * i + 6], acc[8 * i + 7]);
                        uint32_t b0 = pack_bf16(acc[64 + 8 * i + 0], acc[64 + 8 * i + 1]);
                        uint32_t b1 = pack_bf16(acc[64 + 8 * i + 2], acc[64 + 8 * i + 3]);
                        uint32_t b2 = pack_bf16(acc[64 + 8 * i + 4], acc[64 + 8 * i + 5]);
                        uint32_t b3 = pack_bf16(acc[64 + 8 * i + 6], acc[64 + 8 * i + 7]);
                        asm volatile("st.shared.v4.b32 [%0], {%1, %2, %3, %4};" ::"r"(mystage + (i * 128 + tid) * 16), "r"(b0), "r"(b1),
                                     "r"(b2), "r"(b3) : "memory");
                    }
                }
                float o[64], s[64], e[64];
                uint32_t pp[8][4];
                float mm0, mm1, l0, l1, a0, a1, lo0, lo1;
#pragma unroll
                for (int i = 0; i < 64; i++) { o[i] = 0.f; }

                auto issue_s = [&]() -> uint32_t {
                    const uint32_t kbuf = wait_full();
                    const uint32_t stk = st;
                    advance();
                    wgmma_fence();
#pragma unroll
                    for (int k = 0; k < 8; k++) {
                        uint64_t db = make_desc(kbuf + (k >> 2) * 16384 + (k & 3) * 32, 16, 1024, 1);
                        if (k == 0) wgmma_rs_n128_t0_z(s, q[k], db);
                        else wgmma_rs_n128_t0(s, q[k], db, 1);
                    }
                    wgmma_commit();
                    return stk;
                };
                auto issue_pv = [&](bool fresh) -> uint32_t {
                    const uint32_t vbuf = wait_full();
                    const uint32_t stv = st;
                    advance();
                    wgmma_fence();
#pragma unroll
                    for (int k = 0; k < 8; k++) {
                        uint64_t db = make_desc(vbuf + k * 2048, 16384, 1024, 1);
                        wgmma_rs_n128_t1(o, pp[k], db, (!fresh) || k != 0);
                    }
                    wgmma_commit();
                    return stv;
                };
                auto softmax = [&](bool first) {
                    float mx0 = fmaxf(s[0], s[1]), mx1 = fmaxf(s[2], s[3]);
#pragma unroll
                    for (int jj = 1; jj < 16; jj++) {
                        mx0 = fmaxf(mx0, fmaxf(s[4 * jj], s[4 * jj + 1]));
                        mx1 = fmaxf(mx1, fmaxf(s[4 * jj + 2], s[4 * jj + 3]));
                    }
                    mx0 = fmaxf(mx0, __shfl_xor_sync(0xffffffffu, mx0, 1));
                    mx0 = fmaxf(mx0, __shfl_xor_sync(0xffffffffu, mx0, 2));
                    mx1 = fmaxf(mx1, __shfl_xor_sync(0xffffffffu, mx1, 1));
                    mx1 = fmaxf(mx1, __shfl_xor_sync(0xffffffffu, mx1, 2));
                    if (first) {
                        lo0 = l0; lo1 = l1;
                        mm0 = mx0; mm1 = mx1; l0 = 0.f; l1 = 0.f; a0 = 0.f; a1 = 0.f;
                    } else {
                        float mn0 = fmaxf(mm0, mx0), mn1 = fmaxf(mm1, mx1);
                        a0 = ex2((mm0 - mn0) * cscale); a1 = ex2((mm1 - mn1) * cscale);
                        mm0 = mn0; mm1 = mn1;
                    }
                    const float mc0 = mm0 * cscale, mc1 = mm1 * cscale;
                    float r0 = 0.f, r1 = 0.f;
#pragma unroll
                    for (int jj = 0; jj < 16; jj++) {
                        e[4 * jj] = ex2(fmaf(s[4 * jj], cscale, -mc0));
                        e[4 * jj + 1] = ex2(fmaf(s[4 * jj + 1], cscale, -mc0));
                        e[4 * jj + 2] = ex2(fmaf(s[4 * jj + 2], cscale, -mc1));
                        e[4 * jj + 3] = ex2(fmaf(s[4 * jj + 3], cscale, -mc1));
                        r0 += e[4 * jj] + e[4 * jj + 1];
                        r1 += e[4 * jj + 2] + e[4 * jj + 3];
                    }
                    l0 = l0 * a0 + r0; l1 = l1 * a1 + r1;
                };
                auto convert_p = [&]() {
#pragma unroll
                    for (int i = 0; i < 8; i++) {
                        pp[i][0] = pack_bf16(e[8 * i + 0], e[8 * i + 1]);
                        pp[i][1] = pack_bf16(e[8 * i + 2], e[8 * i + 3]);
                        pp[i][2] = pack_bf16(e[8 * i + 4], e[8 * i + 5]);
                        pp[i][3] = pack_bf16(e[8 * i + 6], e[8 * i + 7]);
                    }
                };
                auto store_o = [&](float ls0, float ls1, int head, bool last) {
                    float s0 = ls0 + __shfl_xor_sync(0xffffffffu, ls0, 1); s0 += __shfl_xor_sync(0xffffffffu, s0, 2);
                    float s1 = ls1 + __shfl_xor_sync(0xffffffffu, ls1, 1); s1 += __shfl_xor_sync(0xffffffffu, s1, 2);
                    const float i0 = 1.f / s0, i1 = 1.f / s1;
                    if (tid == 0) {
                        tma_store_wait<0>();
                        if (last) {
                            mbar_arrive_cluster(bars + 8 * BD1A, 0);
                            mbar_arrive_cluster(bars + 8 * BD1A, 1);
                        }
                    }
                    bar_sync(1 + wg, 128);
#pragma unroll
                    for (int jj = 0; jj < 16; jj += 2) {
                        const int mi = lane >> 3;
                        const int row = warp * 16 + (mi & 1) * 8 + (lane & 7);
                        const int grp = jj + (mi >> 1);
                        const uint32_t addr = mystage + (grp >> 3) * 8192 + row * 128 + (((grp & 7) ^ (row & 7)) << 4);
                        stmatrix_x4(addr, pack_bf16(o[4 * jj] * i0, o[4 * jj + 1] * i0), pack_bf16(o[4 * jj + 2] * i1, o[4 * jj + 3] * i1),
                                    pack_bf16(o[4 * jj + 4] * i0, o[4 * jj + 5] * i0), pack_bf16(o[4 * jj + 6] * i1, o[4 * jj + 7] * i1));
                    }
                    fence_proxy_async();
                    bar_sync(1 + wg, 128);
                    if (tid == 0) {
                        tma_store_2d(&tm.o_st, mystage, head * 128, m0 + wg * 64);
                        tma_store_2d(&tm.o_st, mystage + 8192, head * 128 + 64, m0 + wg * 64);
                        tma_store_commit();
                        if (last) {
                            tma_store_wait<0>();
                            mbar_arrive_cluster(bars + 8 * BD1, 0);
                            mbar_arrive_cluster(bars + 8 * BD1, 1);
                            flag_signal_relaxed(F_O + mt * 4 + (j >> 1));
                        }
                    }
                };

                l0 = 0.f; l1 = 0.f;
                {
                    turn_wait();
                    uint32_t stk = issue_s();
                    turn_pass();
                    wgmma_wait<0>();
                    fence_regs(s);
                    release(stk);
                    softmax(true);
                    convert_p();
                }
#pragma unroll 1
                for (int t = 1; t < 8; t++) {
                    const bool first = (t == 4);
                    if (t == 4) {
#pragma unroll
                        for (int i = 0; i < 8; i++) {
                            asm volatile("ld.shared.v4.b32 {%0, %1, %2, %3}, [%4];" : "=r"(q[i][0]), "=r"(q[i][1]), "=r"(q[i][2]), "=r"(q[i][3])
                                         : "r"(mystage + (i * 128 + tid) * 16) : "memory");
                        }
                    }
                    turn_wait();
                    uint32_t stk = issue_s();
                    uint32_t stv = issue_pv(t == 1 || t == 5);
                    turn_pass();
                    wgmma_wait<1>();
                    fence_regs(s);
                    release(stk);
                    softmax(first);
                    asm volatile("{\n.reg .pred p;\nsetp.lt.f32 p, %0, 0fBF800000;\n@p st.shared.f32 [%1], %0;\n}\n" ::"f"(l0 + l1), "r"(mystage) : "memory");
                    wgmma_wait<0>();
                    fence_regs(o);
                    release(stv);
                    if (first) {
                        store_o(lo0, lo1, head0, false);
                    } else {
#pragma unroll
                        for (int jj = 0; jj < 16; jj++) {
                            o[4 * jj] *= a0; o[4 * jj + 1] *= a0; o[4 * jj + 2] *= a1; o[4 * jj + 3] *= a1;
                        }
                    }
                    convert_p();
                }
                {
                    turn_wait();
                    uint32_t stv = issue_pv(false);
                    turn_pass();
                    wgmma_wait<0>();
                    fence_regs(o);
                    release(stv);
                    store_o(l0, l1, head0 + 1, hp == 1);
                }
            }
        }
        TS(0, 4);
        {
            const int kq = j >> 1, n0 = (j & 1) * 320;
            float acc0[96], acc1[64];
#pragma unroll
            for (int i = 0; i < 96; i++) acc0[i] = 0.f;
#pragma unroll
            for (int i = 0; i < 64; i++) acc1[i] = 0.f;
            uint32_t st = 0, ph = 0, prev = 0;
            for (int i = 0; i < 16; i++) {
                mbar_wait(bars + 8 * (B2F + st), ph);
                if (i == 0) TS(0, 5);
                const uint32_t buf = base + st * P2_STAGE;
                wgmma_fence();
#pragma unroll
                for (int k = 0; k < 4; k++) {
                    uint64_t da = make_desc(buf + wg * 8192 + k * 32, 16, 1024, 1);
                    wgmma_ss_n192_t1(acc0, da, make_desc(buf + 16384 + k * 2048, 8192, 1024, 1), 1);
                    wgmma_ss_n128_t1(acc1, da, make_desc(buf + 16384 + 3 * 8192 + k * 2048, 8192, 1024, 1), 1);
                }
                wgmma_commit();
                if (i > 0) { wgmma_wait<1>(); arrive_both(bars + 8 * (B2E + prev)); }
                prev = st;
                if (++st == 4) { st = 0; ph ^= 1; }
            }
            wgmma_wait<0>();
            fence_regs(acc0); fence_regs(acc1);
            TS(0, 6);
            bar_sync(5, 256);
            TS(4, 0);
            const uint32_t stg = base + wg * 40960;
            const int mi = lane >> 3;
            const int row = warp * 16 + (mi & 1) * 8 + (lane & 7);
#pragma unroll
            for (int jj = 0; jj < 24; jj += 2) {
                const int grp = jj + (mi >> 1);
                stmatrix_x4(stg + (grp >> 3) * 8192 + row * 128 + (((grp & 7) ^ (row & 7)) << 4),
                            pack_bf16(acc0[4 * jj], acc0[4 * jj + 1]), pack_bf16(acc0[4 * jj + 2], acc0[4 * jj + 3]),
                            pack_bf16(acc0[4 * jj + 4], acc0[4 * jj + 5]), pack_bf16(acc0[4 * jj + 6], acc0[4 * jj + 7]));
            }
#pragma unroll
            for (int jj = 0; jj < 16; jj += 2) {
                const int grp = jj + (mi >> 1);
                stmatrix_x4(stg + (3 + (grp >> 3)) * 8192 + row * 128 + (((grp & 7) ^ (row & 7)) << 4),
                            pack_bf16(acc1[4 * jj], acc1[4 * jj + 1]), pack_bf16(acc1[4 * jj + 2], acc1[4 * jj + 3]),
                            pack_bf16(acc1[4 * jj + 4], acc1[4 * jj + 5]), pack_bf16(acc1[4 * jj + 6], acc1[4 * jj + 7]));
            }
            TS(4, 1);
            fence_proxy_async();
            bar_sync(1 + wg, 128);
            TS(4, 2);
            if (tid == 0) {
#pragma unroll
                for (int c = 0; c < 5; c++) tma_store_2d(&tm.part_st, stg + c * 8192, n0 + c * 64, kq * S_LEN + m0 + wg * 64);
                tma_store_commit();
                TS(4, 3);
                tma_store_wait<0>();
                TS(4, 4);
                mbar_arrive_cluster(bars + 8 * BD2, 0);
                mbar_arrive_cluster(bars + 8 * BD2, 1);
                flag_signal_relaxed(F_P + mt);
            }
        }
        TS(0, 7);
        {
            uint2 xr[2][5];
#pragma unroll
            for (int rr = 0; rr < 2; rr++)
#pragma unroll
                for (int i = 0; i < 5; i++)
                    xr[rr][i] = __ldg(reinterpret_cast<const uint2*>(x + (size_t)(m0 + j * 16 + cw * 2 + rr) * D_MODEL + (lane + 32 * i) * 4));
            if (threadIdx.x == 0) { flag_wait(F_MODALL, (epoch + 1) * 80); flag_wait(F_P + mt, (epoch + 1) * 16); }
            bar_sync(5, 256);
            TS(0, 8);
            uint2 pr[2][4][5];
            float4 gv[5];
#pragma unroll
            for (int rr = 0; rr < 2; rr++)
#pragma unroll
                for (int s = 0; s < 4; s++)
#pragma unroll
                    for (int i = 0; i < 5; i++)
                        pr[rr][s][i] = ldcg_u2(g_part + ((size_t)s * S_LEN + m0 + j * 16 + cw * 2 + rr) * D_MODEL + (lane + 32 * i) * 4);
#pragma unroll
            for (int i = 0; i < 5; i++) gv[i] = __ldcg(reinterpret_cast<const float4*>(g_mod + 2 * D_MODEL + (lane + 32 * i) * 4));
#pragma unroll
            for (int rr = 0; rr < 2; rr++) {
#pragma unroll
                for (int i = 0; i < 5; i++) {
                    float a0 = (bf16lo(pr[rr][0][i].x) + bf16lo(pr[rr][1][i].x)) + (bf16lo(pr[rr][2][i].x) + bf16lo(pr[rr][3][i].x));
                    float a1 = (bf16hi(pr[rr][0][i].x) + bf16hi(pr[rr][1][i].x)) + (bf16hi(pr[rr][2][i].x) + bf16hi(pr[rr][3][i].x));
                    float a2 = (bf16lo(pr[rr][0][i].y) + bf16lo(pr[rr][1][i].y)) + (bf16lo(pr[rr][2][i].y) + bf16lo(pr[rr][3][i].y));
                    float a3 = (bf16hi(pr[rr][0][i].y) + bf16hi(pr[rr][1][i].y)) + (bf16hi(pr[rr][2][i].y) + bf16hi(pr[rr][3][i].y));
                    xr[rr][i].x = pack_bf16(bf16lo(xr[rr][i].x) + gv[i].x * a0, bf16hi(xr[rr][i].x) + gv[i].y * a1);
                    xr[rr][i].y = pack_bf16(bf16lo(xr[rr][i].y) + gv[i].z * a2, bf16hi(xr[rr][i].y) + gv[i].w * a3);
                    *reinterpret_cast<uint2*>(g_x1 + (size_t)(m0 + j * 16 + cw * 2 + rr) * D_MODEL + (lane + 32 * i) * 4) = xr[rr][i];
                }
            }
            TS(5, 0);
            ln_rows(xr, g_mod + 3 * D_MODEL, g_mod + 4 * D_MODEL, g_h2 + (size_t)(m0 + j * 16 + cw * 2) * D_MODEL, lane);
            TS(5, 1);
            bar_sync(5, 256);
            TS(5, 2);
            if (threadIdx.x == 0) flag_signal(F_H2 + mt);
        }
        TS(0, 9);
        {
            const int f0 = j * 216;
            uint32_t st = 0, ph = 0, prev = 0;
            {
                float acc[128];
#pragma unroll
                for (int i = 0; i < 128; i++) acc[i] = 0.f;
                if (wg == 1) bar_sync(6, 256);
                for (int i = 0; i < 10; i++) {
                    mbar_wait(bars + 8 * (B4F + st), ph);
                    if (i == 0) TS(0, 10);
                    const uint32_t buf = base + st * P4_STAGE;
                    wgmma_fence();
#pragma unroll
                    for (int k = 0; k < 4; k++) {
                        uint64_t da = make_desc(buf + wg * 8192 + k * 32, 16, 1024, 1);
                        uint64_t db = make_desc(buf + 16384 + k * 2048, 8192, 1024, 1);
                        wgmma_ss_n256_t1(acc, da, db, 1);
                    }
                    wgmma_commit();
                    if (i == 1 && wg == 0) bar_arrive(6, 256);
                    if (i > 0) { wgmma_wait<1>(); arrive_both(bars + 8 * (B4E + prev)); }
                    prev = st;
                    if (++st == 4) { st = 0; ph ^= 1; }
                }
                wgmma_wait<0>();
                arrive_both(bars + 8 * (B4E + prev));
                fence_regs(acc);
                TS(2, 0);
#pragma unroll
                for (int jj = 0; jj < 16; jj += 2) {
                    const int mi = lane >> 3;
                    const int row = warp * 16 + (mi & 1) * 8 + (lane & 7);
                    const int grp = jj + (mi >> 1);
                    const uint32_t addr = mystage + (grp >> 3) * 8192 + row * 128 + (((grp & 7) ^ (row & 7)) << 4);
                    stmatrix_x4(addr, pack_bf16(silu_mul(acc[4 * jj], acc[64 + 4 * jj]), silu_mul(acc[4 * jj + 1], acc[64 + 4 * jj + 1])),
                                pack_bf16(silu_mul(acc[4 * jj + 2], acc[64 + 4 * jj + 2]), silu_mul(acc[4 * jj + 3], acc[64 + 4 * jj + 3])),
                                pack_bf16(silu_mul(acc[4 * jj + 4], acc[64 + 4 * jj + 4]), silu_mul(acc[4 * jj + 5], acc[64 + 4 * jj + 5])),
                                pack_bf16(silu_mul(acc[4 * jj + 6], acc[64 + 4 * jj + 6]), silu_mul(acc[4 * jj + 7], acc[64 + 4 * jj + 7])));
                }
                fence_proxy_async();
                bar_sync(1 + wg, 128);
                TS(2, 1);
                if (tid == 0) {
                    tma_store_2d(&tm.act_st64, mystage, f0, m0 + wg * 64);
                    tma_store_2d(&tm.act_st64, mystage + 8192, f0 + 64, m0 + wg * 64);
                    tma_store_commit();
                }
                TS(2, 2);
            }
            {
                float acc[92];
#pragma unroll
                for (int i = 0; i < 92; i++) acc[i] = 0.f;
                for (int i = 0; i < 10; i++) {
                    mbar_wait(bars + 8 * (B4F + st), ph);
                    const uint32_t buf = base + st * P4_STAGE;
                    wgmma_fence();
#pragma unroll
                    for (int k = 0; k < 4; k++) {
                        uint64_t da = make_desc(buf + wg * 8192 + k * 32, 16, 1024, 1);
                        uint64_t db = make_desc(buf + 16384 + k * 1024, 4096, 512, 2);
                        wgmma_ss_n184_t1(acc, da, db, 1);
                    }
                    wgmma_commit();
                    if (i == 3 && tid == 0) { tma_store_wait<0>(); flag_signal_relaxed(F_A1 + mt); }
                    if (i > 0) { wgmma_wait<1>(); arrive_both(bars + 8 * (B4E + prev)); }
                    prev = st;
                    if (++st == 4) { st = 0; ph ^= 1; }
                }
                wgmma_wait<0>();
                arrive_both(bars + 8 * BD4);
                fence_regs(acc);
                TS(0, 11);
                bar_sync(1 + wg, 128);
                TS(2, 3);
#pragma unroll
                for (int jj = 0; jj < 8; jj += 2) {
                    const int mi = lane >> 3;
                    const int row = warp * 16 + (mi & 1) * 8 + (lane & 7);
                    const int grp = jj + (mi >> 1);
                    const uint32_t addr = mystage + row * 128 + ((grp ^ (row & 7)) << 4);
                    stmatrix_x4(addr, pack_bf16(silu_mul(acc[4 * jj], acc[48 + 4 * jj]), silu_mul(acc[4 * jj + 1], acc[48 + 4 * jj + 1])),
                                pack_bf16(silu_mul(acc[4 * jj + 2], acc[48 + 4 * jj + 2]), silu_mul(acc[4 * jj + 3], acc[48 + 4 * jj + 3])),
                                pack_bf16(silu_mul(acc[4 * jj + 4], acc[48 + 4 * jj + 4]), silu_mul(acc[4 * jj + 5], acc[48 + 4 * jj + 5])),
                                pack_bf16(silu_mul(acc[4 * jj + 6], acc[48 + 4 * jj + 6]), silu_mul(acc[4 * jj + 7], acc[48 + 4 * jj + 7])));
                }
                {
                    const int mi = lane >> 3;
                    const int row = warp * 16 + (mi & 1) * 8 + (lane & 7);
                    const uint32_t addr = mystage + 8192 + row * 48 + (mi >> 1) * 16;
                    stmatrix_x4(addr, pack_bf16(silu_mul(acc[32], acc[80]), silu_mul(acc[33], acc[81])),
                                pack_bf16(silu_mul(acc[34], acc[82]), silu_mul(acc[35], acc[83])),
                                pack_bf16(silu_mul(acc[36], acc[84]), silu_mul(acc[37], acc[85])),
                                pack_bf16(silu_mul(acc[38], acc[86]), silu_mul(acc[39], acc[87])));
                    const uint32_t addr2 = mystage + 8192 + (warp * 16 + ((lane >> 3) & 1) * 8 + (lane & 7)) * 48 + 32;
                    asm volatile("stmatrix.sync.aligned.m8n8.x2.shared.b16 [%0], {%1, %2};" ::"r"(addr2),
                                 "r"(pack_bf16(silu_mul(acc[40], acc[88]), silu_mul(acc[41], acc[89]))),
                                 "r"(pack_bf16(silu_mul(acc[42], acc[90]), silu_mul(acc[43], acc[91]))) : "memory");
                }
                fence_proxy_async();
                bar_sync(1 + wg, 128);
                TS(2, 4);
                if (tid == 0) {
                    tma_store_2d(&tm.act_st64, mystage, f0 + 128, m0 + wg * 64);
                    tma_store_2d(&tm.act_st24, mystage + 8192, f0 + 192, m0 + wg * 64);
                    tma_store_commit();
                    TS(2, 5);
                    tma_store_wait<0>();
                    TS(2, 6);
                    mbar_arrive_cluster(bars + 8 * BD4B, 0);
                    mbar_arrive_cluster(bars + 8 * BD4B, 1);
                    TS(2, 7);
                    flag_signal_relaxed(F_A + mt);
                    TS(2, 8);
                }
            }
        }
        TS(0, 12);
        {
            const int m5 = (p * 2 + (j >> 2)) * 128, n0 = (j & 3) * 160;
            const int nkb = rank == 0 ? 14 : 13;
            float accA[64], accB[16];
#pragma unroll
            for (int i = 0; i < 64; i++) accA[i] = 0.f;
#pragma unroll
            for (int i = 0; i < 16; i++) accB[i] = 0.f;
            uint32_t st = 0, ph = 0, prev = 0;
            const int cbase = n0 + (int)rank * 80;
            for (int i = 0; i < nkb; i++) {
                mbar_wait(bars + 8 * (B5F + st), ph);
                if (i == 0) TS(0, 13);
                const uint32_t buf = base + st * P5_STAGE;
                wgmma_fence();
#pragma unroll
                for (int k = 0; k < 4; k++) {
                    uint64_t da = make_desc(buf + wg * 8192 + k * 32, 16, 1024, 1);
                    wgmma_ss_n128_t1(accA, da, make_desc(buf + 16384 + k * 2048, 8192, 1024, 1), 1);
                    wgmma_ss_n32_t1(accB, da, make_desc(buf + 32768 + k * 1024, 4096, 512, 2), 1);
                }
                wgmma_commit();
                if (i > 0) {
                    wgmma_wait<1>();
                    if (tid == 0) mbar_arrive(bars + 8 * (B5E + prev));
                }
                prev = st;
                if (++st == 5) { st = 0; ph ^= 1; }
            }
            uint4 xv[5];
            float2 gbv[10];
#pragma unroll
            for (int it = 0; it < 5; it++) {
                const int idx = it * 256 + (int)threadIdx.x;
                const int row = idx / 10, ch = idx - row * 10;
                xv[it] = __ldcg(reinterpret_cast<const uint4*>(g_x1 + (size_t)(m5 + row) * D_MODEL + cbase + ch * 8));
            }
#pragma unroll
            for (int jj = 0; jj < 10; jj++) gbv[jj] = __ldcg(reinterpret_cast<const float2*>(g_mod + 5 * D_MODEL + cbase + jj * 8 + (lane & 3) * 2));
            wgmma_wait<0>();
            fence_regs(accA); fence_regs(accB);
            float acc[80];
#pragma unroll
            for (int i = 0; i < 64; i++) acc[i] = accA[i];
#pragma unroll
            for (int i = 0; i < 16; i++) acc[64 + i] = accB[i];
            TS(0, 14);
            constexpr uint32_t XBUF = 5 * P5_STAGE;
            mbar_wait(bars + 8 * BD4B, 0);
            TS(3, 0);
            {
                const uint32_t dst = mapa(base + XBUF, rank ^ 1) + wg * 20480 + tid * 16;
                const uint32_t rbar = mapa(bars + 8 * BX, rank ^ 1);
                if (rank == 0) {
#pragma unroll
                    for (int i = 0; i < 10; i++)
                        asm volatile("st.async.shared::cluster.mbarrier::complete_tx::bytes.v4.f32 [%0], {%1, %2, %3, %4}, [%5];" ::"r"(dst + i * 2048),
                                     "f"(acc[40 + 4 * i]), "f"(acc[40 + 4 * i + 1]), "f"(acc[40 + 4 * i + 2]), "f"(acc[40 + 4 * i + 3]), "r"(rbar) : "memory");
                } else {
#pragma unroll
                    for (int i = 0; i < 10; i++)
                        asm volatile("st.async.shared::cluster.mbarrier::complete_tx::bytes.v4.f32 [%0], {%1, %2, %3, %4}, [%5];" ::"r"(dst + i * 2048),
                                     "f"(acc[4 * i]), "f"(acc[4 * i + 1]), "f"(acc[4 * i + 2]), "f"(acc[4 * i + 3]), "r"(rbar) : "memory");
                }
            }
            TS(3, 1);
            mbar_wait(bars + 8 * BX, 0);
            TS(3, 2);
            {
                bar_sync(5, 256);
                const uint32_t tile = base;
                TS(3, 3);
#pragma unroll
                for (int jj = 0; jj < 10; jj += 2) {
                    float4 o0, o1;
                    asm volatile("ld.shared.v4.f32 {%0, %1, %2, %3}, [%4];" : "=f"(o0.x), "=f"(o0.y), "=f"(o0.z), "=f"(o0.w) : "r"(base + XBUF + wg * 20480 + tid * 16 + jj * 2048));
                    asm volatile("ld.shared.v4.f32 {%0, %1, %2, %3}, [%4];" : "=f"(o1.x), "=f"(o1.y), "=f"(o1.z), "=f"(o1.w) : "r"(base + XBUF + wg * 20480 + tid * 16 + (jj + 1) * 2048));
                    const float2 g0 = gbv[jj], g1 = gbv[jj + 1];
                    float a[8];
#pragma unroll
                    for (int ee = 0; ee < 8; ee++) a[ee] = rank == 0 ? acc[4 * jj + ee] : acc[40 + 4 * jj + ee];
                    const int mi = lane >> 3;
                    const int row = wg * 64 + warp * 16 + (mi & 1) * 8 + (lane & 7);
                    const uint32_t addr = tile + row * 176 + (jj + (mi >> 1)) * 16;
                    stmatrix_x4(addr, pack_bf16(g0.x * bf16_round(a[0] + o0.x), g0.y * bf16_round(a[1] + o0.y)),
                                pack_bf16(g0.x * bf16_round(a[2] + o0.z), g0.y * bf16_round(a[3] + o0.w)),
                                pack_bf16(g1.x * bf16_round(a[4] + o1.x), g1.y * bf16_round(a[5] + o1.y)),
                                pack_bf16(g1.x * bf16_round(a[6] + o1.z), g1.y * bf16_round(a[7] + o1.w)));
                }
                TS(3, 4);
                bar_sync(5, 256);
                TS(3, 5);
#pragma unroll
                for (int it = 0; it < 5; it++) {
                    const int idx = it * 256 + (int)threadIdx.x;
                    const int row = idx / 10, ch = idx - row * 10;
                    uint4 tv;
                    asm volatile("ld.shared.v4.b32 {%0, %1, %2, %3}, [%4];" : "=r"(tv.x), "=r"(tv.y), "=r"(tv.z), "=r"(tv.w) : "r"(tile + row * 176 + ch * 16));
                    uint4 r;
                    r.x = pack_bf16(bf16lo(xv[it].x) + bf16lo(tv.x), bf16hi(xv[it].x) + bf16hi(tv.x));
                    r.y = pack_bf16(bf16lo(xv[it].y) + bf16lo(tv.y), bf16hi(xv[it].y) + bf16hi(tv.y));
                    r.z = pack_bf16(bf16lo(xv[it].z) + bf16lo(tv.z), bf16hi(xv[it].z) + bf16hi(tv.z));
                    r.w = pack_bf16(bf16lo(xv[it].w) + bf16lo(tv.w), bf16hi(xv[it].w) + bf16hi(tv.w));
                    *reinterpret_cast<uint4*>(out + (size_t)(m5 + row) * D_MODEL + cbase + ch * 8) = r;
                }
            }
            TS(0, 15);
            if (threadIdx.x == 0) {
                const unsigned old = atomicAdd(&g_exit, 1u);
                if (old == (epoch + 1) * 128u - 1u) {
                    asm volatile("st.volatile.global.u32 [%0], %1;" ::"l"(&g_epoch), "r"(epoch + 1) : "memory");
                }
            }
            asm volatile("barrier.cluster.arrive.relaxed.aligned;\n barrier.cluster.wait.aligned;" ::: "memory");
        }
    }
}

typedef CUresult (*PFN_encodeTiled)(CUtensorMap*, CUtensorMapDataType, cuuint32_t, void*, const cuuint64_t*, const cuuint64_t*,
                                    const cuuint32_t*, const cuuint32_t*, CUtensorMapInterleave, CUtensorMapSwizzle,
                                    CUtensorMapL2promotion, CUtensorMapFloatOOBfill);

static PFN_encodeTiled get_encode() {
    static PFN_encodeTiled fn = nullptr;
    if (!fn) {
        void* p = nullptr;
        cudaDriverEntryPointQueryResult qr;
        cudaGetDriverEntryPoint("cuTensorMapEncodeTiled", &p, cudaEnableDefault, &qr);
        fn = (PFN_encodeTiled)p;
    }
    return fn;
}

static CUtensorMap make_map(const void* ptr, uint64_t rows, uint64_t cols, uint32_t box_rows, uint32_t box_cols, CUtensorMapSwizzle swz) {
    CUtensorMap m;
    cuuint64_t dims[2] = {cols, rows};
    cuuint64_t strides[1] = {cols * 2};
    cuuint32_t box[2] = {box_cols, box_rows};
    cuuint32_t es[2] = {1, 1};
    get_encode()(&m, CU_TENSOR_MAP_DATA_TYPE_BFLOAT16, 2, const_cast<void*>(ptr), dims, strides, box, es, CU_TENSOR_MAP_INTERLEAVE_NONE,
                 swz, CU_TENSOR_MAP_L2_PROMOTION_L2_256B, CU_TENSOR_MAP_FLOAT_OOB_FILL_NONE);
    return m;
}

extern "C" void kernel_launch(void* const* d_in, const int* in_sizes, int n_in, void* d_out, int out_size) {
    (void)in_sizes; (void)n_in; (void)out_size;
    const __nv_bfloat16* x = (const __nv_bfloat16*)d_in[0];
    const __nv_bfloat16* kc = (const __nv_bfloat16*)d_in[1];
    const __nv_bfloat16* vc = (const __nv_bfloat16*)d_in[2];
    const __nv_bfloat16* wq = (const __nv_bfloat16*)d_in[3];
    const __nv_bfloat16* wo = (const __nv_bfloat16*)d_in[4];
    const __nv_bfloat16* wg = (const __nv_bfloat16*)d_in[6];
    const __nv_bfloat16* wu = (const __nv_bfloat16*)d_in[7];
    const __nv_bfloat16* wd = (const __nv_bfloat16*)d_in[8];
    const __nv_bfloat16* c = (const __nv_bfloat16*)d_in[9];
    const __nv_bfloat16* wmod = (const __nv_bfloat16*)d_in[10];
    __nv_bfloat16* out = (__nv_bfloat16*)d_out;

    static bool init = false;
    static void *p_h, *p_o, *p_x1, *p_h2, *p_act, *p_part;
    if (!init) {
        cudaFuncSetAttribute(mega_kernel, cudaFuncAttributeMaxDynamicSharedMemorySize, SM_TOTAL);
        cudaGetSymbolAddress(&p_h, g_h);
        cudaGetSymbolAddress(&p_o, g_o);
        cudaGetSymbolAddress(&p_x1, g_x1);
        cudaGetSymbolAddress(&p_h2, g_h2);
        cudaGetSymbolAddress(&p_act, g_act);
        cudaGetSymbolAddress(&p_part, g_part);
        init = true;
    }
    const CUtensorMapSwizzle S128 = CU_TENSOR_MAP_SWIZZLE_128B, S64 = CU_TENSOR_MAP_SWIZZLE_64B;
    Maps tm;
    tm.h = make_map(p_h, S_LEN, D_MODEL, 128, 64, S128);
    tm.wq = make_map(wq, D_MODEL, N_HEADS * D_HEAD, 64, 64, S128);
    tm.k = make_map(kc, N_HEADS * S_KV, D_HEAD, 128, 64, S128);
    tm.v = make_map(vc, N_HEADS * S_KV, D_HEAD, 128, 64, S128);
    tm.o_st = make_map(p_o, S_LEN, N_HEADS * D_HEAD, 64, 64, S128);
    tm.o_a = make_map(p_o, S_LEN, N_HEADS * D_HEAD, 128, 64, S128);
    tm.wo = make_map(wo, N_HEADS * D_HEAD, D_MODEL, 64, 64, S128);
    tm.part_st = make_map(p_part, 4 * S_LEN, D_MODEL, 64, 64, S128);
    tm.h2 = make_map(p_h2, S_LEN, D_MODEL, 128, 64, S128);
    tm.g128 = make_map(wg, D_MODEL, D_FF, 64, 64, S128);
    tm.u128 = make_map(wu, D_MODEL, D_FF, 64, 64, S128);
    tm.g64 = make_map(wg, D_MODEL, D_FF, 64, 32, S64);
    tm.u64 = make_map(wu, D_MODEL, D_FF, 64, 32, S64);
    tm.act_st64 = make_map(p_act, S_LEN, D_FF, 64, 64, S128);
    tm.act_st24 = make_map(p_act, S_LEN, D_FF, 64, 24, CU_TENSOR_MAP_SWIZZLE_NONE);
    tm.act_a = make_map(p_act, S_LEN, D_FF, 128, 64, S128);
    tm.wd = make_map(wd, D_FF, D_MODEL, 64, 64, S128);
    tm.wd32 = make_map(wd, D_FF, D_MODEL, 64, 32, S64);

    cudaLaunchConfig_t cfg = {};
    cfg.gridDim = dim3(128);
    cfg.blockDim = dim3(384);
    cfg.dynamicSmemBytes = SM_TOTAL;
    cfg.stream = cudaStreamPerThread;
    cfg.attrs = nullptr;
    cfg.numAttrs = 0;
    cudaLaunchKernelEx(&cfg, mega_kernel, tm, x, c, wmod, out, (const void*)wo, (const void*)wg, (const void*)wu, (const void*)wd);
}
```

```cpp
#include <cuda_runtime.h>
#include <cuda_bf16.h>
#include <cuda.h>
#include <stdint.h>

__device__ __forceinline__ uint32_t smem_u32(const void* p) { return (uint32_t)__cvta_generic_to_shared(p); }

__device__ __forceinline__ void mbar_init(uint32_t bar, uint32_t count) {
    asm volatile("mbarrier.init.shared::cta.b64 [%0], %1;" ::"r"(bar), "r"(count) : "memory");
}
__device__ __forceinline__ void mbar_expect_tx(uint32_t bar, uint32_t bytes) {
    asm volatile("mbarrier.arrive.expect_tx.shared::cta.b64 _, [%0], %1;" ::"r"(bar), "r"(bytes) : "memory");
}
__device__ __forceinline__ void mbar_arrive(uint32_t bar) {
    asm volatile("mbarrier.arrive.shared::cta.b64 _, [%0];" ::"r"(bar) : "memory");
}
__device__ __forceinline__ void mbar_arrive_cluster(uint32_t bar, uint32_t cta) {
    asm volatile(
        "{\n.reg .b32 ra;\n"
        "mapa.shared::cluster.u32 ra, %0, %1;\n"
        "mbarrier.arrive.shared::cluster.b64 _, [ra];\n}\n" ::"r"(bar), "r"(cta)
        : "memory");
}
__device__ __forceinline__ bool mbar_try_wait(uint32_t bar, uint32_t parity) {
    uint32_t ok;
    asm volatile(
        "{\n.reg .pred p;\n"
        "mbarrier.try_wait.parity.shared::cta.b64 p, [%1], %2;\n"
        "selp.u32 %0, 1, 0, p;\n}\n"
        : "=r"(ok)
        : "r"(bar), "r"(parity)
        : "memory");
    return ok != 0;
}
__device__ __forceinline__ bool mbar_try_wait_cluster(uint32_t bar, uint32_t parity) {
    uint32_t ok;
    asm volatile(
        "{\n.reg .pred p;\n"
        "mbarrier.try_wait.parity.shared::cta.b64 p, [%1], %2;\n"
        "selp.u32 %0, 1, 0, p;\n}\n"
        : "=r"(ok)
        : "r"(bar), "r"(parity)
        : "memory");
    return ok != 0;
}
__device__ volatile int g_abort = 0;
__device__ __forceinline__ void mbar_wait(uint32_t bar, uint32_t parity) {
    asm volatile(
        "{\n.reg .pred p;\n.reg .u32 n;\n"
        "mov.u32 n, 0;\n"
        "WAIT_LOOP:\n"
        "mbarrier.try_wait.parity.shared::cta.b64 p, [%0], %1;\n"
        "@p bra WAIT_DONE;\n"
        "add.u32 n, n, 1;\n"
        "setp.lt.u32 p, n, 16777216;\n"
        "@p bra WAIT_LOOP;\n"
        "WAIT_DONE:\n}\n" ::"r"(bar), "r"(parity) : "memory");
}
__device__ __forceinline__ void mbar_wait_cluster(uint32_t bar, uint32_t parity) { mbar_wait(bar, parity); }
__device__ __forceinline__ void fence_mbar_init() { asm volatile("fence.mbarrier_init.release.cluster;" ::: "memory"); }
__device__ __forceinline__ void fence_proxy_async() { asm volatile("fence.proxy.async.shared::cta;" ::: "memory"); }
__device__ __forceinline__ void fence_proxy_async_all() { asm volatile("fence.proxy.async;" ::: "memory"); }
__device__ __forceinline__ void cluster_arrive() { asm volatile("barrier.cluster.arrive.release.aligned;" ::: "memory"); }
__device__ __forceinline__ void cluster_wait() { asm volatile("barrier.cluster.wait.acquire.aligned;" ::: "memory"); }
__device__ __forceinline__ void cluster_sync() { cluster_arrive(); cluster_wait(); }
__device__ __forceinline__ uint32_t cluster_ctarank() {
    uint32_t r;
    asm volatile("mov.u32 %0, %%cluster_ctarank;" : "=r"(r));
    return r;
}
__device__ __forceinline__ void bar_sync(int id, int n) { asm volatile("bar.sync %0, %1;" ::"r"(id), "r"(n) : "memory"); }
__device__ __forceinline__ void bar_arrive(int id, int n) { asm volatile("bar.arrive %0, %1;" ::"r"(id), "r"(n) : "memory"); }
__device__ __forceinline__ void pdl_wait() { asm volatile("griddepcontrol.wait;" ::: "memory"); }
__device__ __forceinline__ void pdl_launch() { asm volatile("griddepcontrol.launch_dependents;" ::: "memory"); }

__device__ __forceinline__ void tma_prefetch_desc(const CUtensorMap* m) {
    asm volatile("prefetch.tensormap [%0];" ::"l"(m) : "memory");
}
__device__ __forceinline__ void tma_load_2d(uint32_t dst, const CUtensorMap* m, int c0, int c1, uint32_t bar) {
    asm volatile(
        "cp.async.bulk.tensor.2d.shared::cluster.global.mbarrier::complete_tx::bytes [%0], [%1, {%3, %4}], [%2];"
        ::"r"(dst), "l"(m), "r"(bar), "r"(c0), "r"(c1)
        : "memory");
}
__device__ __forceinline__ void tma_load_2d_mc(uint32_t dst, const CUtensorMap* m, int c0, int c1, uint32_t bar, uint16_t mask) {
    asm volatile(
        "cp.async.bulk.tensor.2d.shared::cluster.global.mbarrier::complete_tx::bytes.multicast::cluster [%0], [%1, {%3, %4}], [%2], %5;"
        ::"r"(dst), "l"(m), "r"(bar), "r"(c0), "r"(c1), "h"(mask)
        : "memory");
}
__device__ __forceinline__ void tma_store_2d(const CUtensorMap* m, uint32_t src, int c0, int c1) {
    asm volatile("cp.async.bulk.tensor.2d.global.shared::cta.bulk_group [%0, {%2, %3}], [%1];"
                 ::"l"(m), "r"(src), "r"(c0), "r"(c1)
                 : "memory");
}
__device__ __forceinline__ void tma_store_commit() { asm volatile("cp.async.bulk.commit_group;" ::: "memory"); }
template <int N> __device__ __forceinline__ void tma_store_wait_read() {
    asm volatile("cp.async.bulk.wait_group.read %0;" ::"n"(N) : "memory");
}
template <int N> __device__ __forceinline__ void tma_store_wait() {
    asm volatile("cp.async.bulk.wait_group %0;" ::"n"(N) : "memory");
}

__device__ __forceinline__ void wgmma_fence() { asm volatile("wgmma.fence.sync.aligned;" ::: "memory"); }
__device__ __forceinline__ void wgmma_commit() { asm volatile("wgmma.commit_group.sync.aligned;" ::: "memory"); }
template <int N> __device__ __forceinline__ void wgmma_wait() {
    asm volatile("wgmma.wait_group.sync.aligned %0;" ::"n"(N) : "memory");
}
template <int R> __device__ __forceinline__ void reg_alloc() { asm volatile("setmaxnreg.inc.sync.aligned.u32 %0;" ::"n"(R)); }
template <int R> __device__ __forceinline__ void reg_dealloc() { asm volatile("setmaxnreg.dec.sync.aligned.u32 %0;" ::"n"(R)); }

template <int N> __device__ __forceinline__ void fence_regs(float (&r)[N]) {
#pragma unroll
    for (int i = 0; i < N; i++) asm volatile("" : "+f"(r[i])::"memory");
}
template <int N> __device__ __forceinline__ void fence_regs_u(uint32_t (&r)[N][4]) {
#pragma unroll
    for (int i = 0; i < N; i++) {
#pragma unroll
        for (int j = 0; j < 4; j++) asm volatile("" : "+r"(r[i][j])::"memory");
    }
}

__device__ __forceinline__ uint64_t make_desc(uint32_t addr, uint32_t lbo_bytes, uint32_t sbo_bytes, uint32_t swz) {
    return (uint64_t)((addr & 0x3FFFF) >> 4) | ((uint64_t)(lbo_bytes >> 4) << 16) | ((uint64_t)(sbo_bytes >> 4) << 32) |
           ((uint64_t)swz << 62);
}

__device__ __forceinline__ uint32_t pack_bf16(float lo, float hi) {
    uint32_t r;
    asm("cvt.rn.bf16x2.f32 %0, %1, %2;" : "=r"(r) : "f"(hi), "f"(lo));
    return r;
}
__device__ __forceinline__ float bf16_round(float x) { return __bfloat162float(__float2bfloat16_rn(x)); }
__device__ __forceinline__ float bf16lo(uint32_t v) { return __uint_as_float(v << 16); }
__device__ __forceinline__ float bf16hi(uint32_t v) { return __uint_as_float(v & 0xffff0000u); }
__device__ __forceinline__ float ex2(float x) {
    float y;
    asm("ex2.approx.ftz.f32 %0, %1;" : "=f"(y) : "f"(x));
    return y;
}
__device__ __forceinline__ void stmatrix_x4(uint32_t addr, uint32_t r0, uint32_t r1, uint32_t r2, uint32_t r3) {
    asm volatile("stmatrix.sync.aligned.m8n8.x4.shared.b16 [%0], {%1, %2, %3, %4};" ::"r"(addr), "r"(r0), "r"(r1), "r"(r2), "r"(r3)
                 : "memory");
}
__device__ __forceinline__ uint32_t mapa(uint32_t addr, uint32_t cta) {
    uint32_t r;
    asm volatile("mapa.shared::cluster.u32 %0, %1, %2;" : "=r"(r) : "r"(addr), "r"(cta));
    return r;
}
__device__ __forceinline__ void st_cluster_v2(uint32_t addr, float a, float b) {
    asm volatile("st.shared::cluster.v2.f32 [%0], {%1, %2};" ::"r"(addr), "f"(a), "f"(b) : "memory");
}
__device__ __forceinline__ void wgmma_ss_n256_t1(float (&d)[128], uint64_t descA, uint64_t descB, int scaleD) {
    asm volatile("{\n.reg .pred p;\n"
        "setp.ne.b32 p, %130, 0;\n"
        "wgmma.mma_async.sync.aligned.m64n256k16.f32.bf16.bf16 "
        "{%0, %1, %2, %3, %4, %5, %6, %7, %8, %9, %10, %11, %12, %13, %14, %15, "
        "%16, %17, %18, %19, %20, %21, %22, %23, %24, %25, %26, %27, %28, %29, %30, %31, "
        "%32, %33, %34, %35, %36, %37, %38, %39, %40, %41, %42, %43, %44, %45, %46, %47, "
        "%48, %49, %50, %51, %52, %53, %54, %55, %56, %57, %58, %59, %60, %61, %62, %63, "
        "%64, %65, %66, %67, %68, %69, %70, %71, %72, %73, %74, %75, %76, %77, %78, %79, "
        "%80, %81, %82, %83, %84, %85, %86, %87, %88, %89, %90, %91, %92, %93, %94, %95, "
        "%96, %97, %98, %99, %100, %101, %102, %103, %104, %105, %106, %107, %108, %109, %110, %111, "
        "%112, %113, %114, %115, %116, %117, %118, %119, %120, %121, %122, %123, %124, %125, %126, %127}, "
        "%128, %129, p, 1, 1, 0, 1;\n}\n"
        :
          "+f"(d[0]), "+f"(d[1]), "+f"(d[2]), "+f"(d[3]), "+f"(d[4]), "+f"(d[5]), "+f"(d[6]), "+f"(d[7]),
          "+f"(d[8]), "+f"(d[9]), "+f"(d[10]), "+f"(d[11]), "+f"(d[12]), "+f"(d[13]), "+f"(d[14]), "+f"(d[15]),
          "+f"(d[16]), "+f"(d[17]), "+f"(d[18]), "+f"(d[19]), "+f"(d[20]), "+f"(d[21]), "+f"(d[22]), "+f"(d[23]),
          "+f"(d[24]), "+f"(d[25]), "+f"(d[26]), "+f"(d[27]), "+f"(d[28]), "+f"(d[29]), "+f"(d[30]), "+f"(d[31]),
          "+f"(d[32]), "+f"(d[33]), "+f"(d[34]), "+f"(d[35]), "+f"(d[36]), "+f"(d[37]), "+f"(d[38]), "+f"(d[39]),
          "+f"(d[40]), "+f"(d[41]), "+f"(d[42]), "+f"(d[43]), "+f"(d[44]), "+f"(d[45]), "+f"(d[46]), "+f"(d[47]),
          "+f"(d[48]), "+f"(d[49]), "+f"(d[50]), "+f"(d[51]), "+f"(d[52]), "+f"(d[53]), "+f"(d[54]), "+f"(d[55]),
          "+f"(d[56]), "+f"(d[57]), "+f"(d[58]), "+f"(d[59]), "+f"(d[60]), "+f"(d[61]), "+f"(d[62]), "+f"(d[63]),
          "+f"(d[64]), "+f"(d[65]), "+f"(d[66]), "+f"(d[67]), "+f"(d[68]), "+f"(d[69]), "+f"(d[70]), "+f"(d[71]),
          "+f"(d[72]), "+f"(d[73]), "+f"(d[74]), "+f"(d[75]), "+f"(d[76]), "+f"(d[77]), "+f"(d[78]), "+f"(d[79]),
          "+f"(d[80]), "+f"(d[81]), "+f"(d[82]), "+f"(d[83]), "+f"(d[84]), "+f"(d[85]), "+f"(d[86]), "+f"(d[87]),
          "+f"(d[88]), "+f"(d[89]), "+f"(d[90]), "+f"(d[91]), "+f"(d[92]), "+f"(d[93]), "+f"(d[94]), "+f"(d[95]),
          "+f"(d[96]), "+f"(d[97]), "+f"(d[98]), "+f"(d[99]), "+f"(d[100]), "+f"(d[101]), "+f"(d[102]), "+f"(d[103]),
          "+f"(d[104]), "+f"(d[105]), "+f"(d[106]), "+f"(d[107]), "+f"(d[108]), "+f"(d[109]), "+f"(d[110]), "+f"(d[111]),
          "+f"(d[112]), "+f"(d[113]), "+f"(d[114]), "+f"(d[115]), "+f"(d[116]), "+f"(d[117]), "+f"(d[118]), "+f"(d[119]),
          "+f"(d[120]), "+f"(d[121]), "+f"(d[122]), "+f"(d[123]), "+f"(d[124]), "+f"(d[125]), "+f"(d[126]), "+f"(d[127])
        : "l"(descA), "l"(descB), "r"(scaleD));
}

__device__ __forceinline__ void wgmma_rs_n128_t0(float (&d)[64], const uint32_t (&a)[4], uint64_t descB, int scaleD) {
    asm volatile("{\n.reg .pred p;\n"
        "setp.ne.b32 p, %69, 0;\n"
        "wgmma.mma_async.sync.aligned.m64n128k16.f32.bf16.bf16 "
        "{%0, %1, %2, %3, %4, %5, %6, %7, %8, %9, %10, %11, %12, %13, %14, %15, "
        "%16, %17, %18, %19, %20, %21, %22, %23, %24, %25, %26, %27, %28, %29, %30, %31, "
        "%32, %33, %34, %35, %36, %37, %38, %39, %40, %41, %42, %43, %44, %45, %46, %47, "
        "%48, %49, %50, %51, %52, %53, %54, %55, %56, %57, %58, %59, %60, %61, %62, %63}, "
        "{%64, %65, %66, %67}, %68, p, 1, 1, 0;\n}\n"
        :
          "+f"(d[0]), "+f"(d[1]), "+f"(d[2]), "+f"(d[3]), "+f"(d[4]), "+f"(d[5]), "+f"(d[6]), "+f"(d[7]),
          "+f"(d[8]), "+f"(d[9]), "+f"(d[10]), "+f"(d[11]), "+f"(d[12]), "+f"(d[13]), "+f"(d[14]), "+f"(d[15]),
          "+f"(d[16]), "+f"(d[17]), "+f"(d[18]), "+f"(d[19]), "+f"(d[20]), "+f"(d[21]), "+f"(d[22]), "+f"(d[23]),
          "+f"(d[24]), "+f"(d[25]), "+f"(d[26]), "+f"(d[27]), "+f"(d[28]), "+f"(d[29]), "+f"(d[30]), "+f"(d[31]),
          "+f"(d[32]), "+f"(d[33]), "+f"(d[34]), "+f"(d[35]), "+f"(d[36]), "+f"(d[37]), "+f"(d[38]), "+f"(d[39]),
          "+f"(d[40]), "+f"(d[41]), "+f"(d[42]), "+f"(d[43]), "+f"(d[44]), "+f"(d[45]), "+f"(d[46]), "+f"(d[47]),
          "+f"(d[48]), "+f"(d[49]), "+f"(d[50]), "+f"(d[51]), "+f"(d[52]), "+f"(d[53]), "+f"(d[54]), "+f"(d[55]),
          "+f"(d[56]), "+f"(d[57]), "+f"(d[58]), "+f"(d[59]), "+f"(d[60]), "+f"(d[61]), "+f"(d[62]), "+f"(d[63])
        : "r"(a[0]), "r"(a[1]), "r"(a[2]), "r"(a[3]), "l"(descB), "r"(scaleD));
}

__device__ __forceinline__ void wgmma_rs_n128_t0_z(float (&d)[64], const uint32_t (&a)[4], uint64_t descB) {
    asm volatile("{\n.reg .pred p;\n"
        "setp.ne.b32 p, 0, 0;\n"
        "wgmma.mma_async.sync.aligned.m64n128k16.f32.bf16.bf16 "
        "{%0, %1, %2, %3, %4, %5, %6, %7, %8, %9, %10, %11, %12, %13, %14, %15, "
        "%16, %17, %18, %19, %20, %21, %22, %23, %24, %25, %26, %27, %28, %29, %30, %31, "
        "%32, %33, %34, %35, %36, %37, %38, %39, %40, %41, %42, %43, %44, %45, %46, %47, "
        "%48, %49, %50, %51, %52, %53, %54, %55, %56, %57, %58, %59, %60, %61, %62, %63}, "
        "{%64, %65, %66, %67}, %68, p, 1, 1, 0;\n}\n"
        :
          "=f"(d[0]), "=f"(d[1]), "=f"(d[2]), "=f"(d[3]), "=f"(d[4]), "=f"(d[5]), "=f"(d[6]), "=f"(d[7]),
          "=f"(d[8]), "=f"(d[9]), "=f"(d[10]), "=f"(d[11]), "=f"(d[12]), "=f"(d[13]), "=f"(d[14]), "=f"(d[15]),
          "=f"(d[16]), "=f"(d[17]), "=f"(d[18]), "=f"(d[19]), "=f"(d[20]), "=f"(d[21]), "=f"(d[22]), "=f"(d[23]),
          "=f"(d[24]), "=f"(d[25]), "=f"(d[26]), "=f"(d[27]), "=f"(d[28]), "=f"(d[29]), "=f"(d[30]), "=f"(d[31]),
          "=f"(d[32]), "=f"(d[33]), "=f"(d[34]), "=f"(d[35]), "=f"(d[36]), "=f"(d[37]), "=f"(d[38]), "=f"(d[39]),
          "=f"(d[40]), "=f"(d[41]), "=f"(d[42]), "=f"(d[43]), "=f"(d[44]), "=f"(d[45]), "=f"(d[46]), "=f"(d[47]),
          "=f"(d[48]), "=f"(d[49]), "=f"(d[50]), "=f"(d[51]), "=f"(d[52]), "=f"(d[53]), "=f"(d[54]), "=f"(d[55]),
          "=f"(d[56]), "=f"(d[57]), "=f"(d[58]), "=f"(d[59]), "=f"(d[60]), "=f"(d[61]), "=f"(d[62]), "=f"(d[63])
        : "r"(a[0]), "r"(a[1]), "r"(a[2]), "r"(a[3]), "l"(descB));
}

__device__ __forceinline__ void wgmma_rs_n128_t1(float (&d)[64], const uint32_t (&a)[4], uint64_t descB, int scaleD) {
    asm volatile("{\n.reg .pred p;\n"
        "setp.ne.b32 p, %69, 0;\n"
        "wgmma.mma_async.sync.aligned.m64n128k16.f32.bf16.bf16 "
        "{%0, %1, %2, %3, %4, %5, %6, %7, %8, %9, %10, %11, %12, %13, %14, %15, "
        "%16, %17, %18, %19, %20, %21, %22, %23, %24, %25, %26, %27, %28, %29, %30, %31, "
        "%32, %33, %34, %35, %36, %37, %38, %39, %40, %41, %42, %43, %44, %45, %46, %47, "
        "%48, %49, %50, %51, %52, %53, %54, %55, %56, %57, %58, %59, %60, %61, %62, %63}, "
        "{%64, %65, %66, %67}, %68, p, 1, 1, 1;\n}\n"
        :
          "+f"(d[0]), "+f"(d[1]), "+f"(d[2]), "+f"(d[3]), "+f"(d[4]), "+f"(d[5]), "+f"(d[6]), "+f"(d[7]),
          "+f"(d[8]), "+f"(d[9]), "+f"(d[10]), "+f"(d[11]), "+f"(d[12]), "+f"(d[13]), "+f"(d[14]), "+f"(d[15]),
          "+f"(d[16]), "+f"(d[17]), "+f"(d[18]), "+f"(d[19]), "+f"(d[20]), "+f"(d[21]), "+f"(d[22]), "+f"(d[23]),
          "+f"(d[24]), "+f"(d[25]), "+f"(d[26]), "+f"(d[27]), "+f"(d[28]), "+f"(d[29]), "+f"(d[30]), "+f"(d[31]),
          "+f"(d[32]), "+f"(d[33]), "+f"(d[34]), "+f"(d[35]), "+f"(d[36]), "+f"(d[37]), "+f"(d[38]), "+f"(d[39]),
          "+f"(d[40]), "+f"(d[41]), "+f"(d[42]), "+f"(d[43]), "+f"(d[44]), "+f"(d[45]), "+f"(d[46]), "+f"(d[47]),
          "+f"(d[48]), "+f"(d[49]), "+f"(d[50]), "+f"(d[51]), "+f"(d[52]), "+f"(d[53]), "+f"(d[54]), "+f"(d[55]),
          "+f"(d[56]), "+f"(d[57]), "+f"(d[58]), "+f"(d[59]), "+f"(d[60]), "+f"(d[61]), "+f"(d[62]), "+f"(d[63])
        : "r"(a[0]), "r"(a[1]), "r"(a[2]), "r"(a[3]), "l"(descB), "r"(scaleD));
}

__device__ __forceinline__ void wgmma_ss_n184_t1(float (&d)[92], uint64_t descA, uint64_t descB, int scaleD) {
    asm volatile("{\n.reg .pred p;\n"
        "setp.ne.b32 p, %94, 0;\n"
        "wgmma.mma_async.sync.aligned.m64n184k16.f32.bf16.bf16 "
        "{%0, %1, %2, %3, %4, %5, %6, %7, %8, %9, %10, %11, %12, %13, %14, %15, "
        "%16, %17, %18, %19, %20, %21, %22, %23, %24, %25, %26, %27, %28, %29, %30, %31, "
        "%32, %33, %34, %35, %36, %37, %38, %39, %40, %41, %42, %43, %44, %45, %46, %47, "
        "%48, %49, %50, %51, %52, %53, %54, %55, %56, %57, %58, %59, %60, %61, %62, %63, "
        "%64, %65, %66, %67, %68, %69, %70, %71, %72, %73, %74, %75, %76, %77, %78, %79, "
        "%80, %81, %82, %83, %84, %85, %86, %87, %88, %89, %90, %91}, "
        "%92, %93, p, 1, 1, 0, 1;\n}\n"
        :
          "+f"(d[0]), "+f"(d[1]), "+f"(d[2]), "+f"(d[3]), "+f"(d[4]), "+f"(d[5]), "+f"(d[6]), "+f"(d[7]),
          "+f"(d[8]), "+f"(d[9]), "+f"(d[10]), "+f"(d[11]), "+f"(d[12]), "+f"(d[13]), "+f"(d[14]), "+f"(d[15]),
          "+f"(d[16]), "+f"(d[17]), "+f"(d[18]), "+f"(d[19]), "+f"(d[20]), "+f"(d[21]), "+f"(d[22]), "+f"(d[23]),
          "+f"(d[24]), "+f"(d[25]), "+f"(d[26]), "+f"(d[27]), "+f"(d[28]), "+f"(d[29]), "+f"(d[30]), "+f"(d[31]),
          "+f"(d[32]), "+f"(d[33]), "+f"(d[34]), "+f"(d[35]), "+f"(d[36]), "+f"(d[37]), "+f"(d[38]), "+f"(d[39]),
          "+f"(d[40]), "+f"(d[41]), "+f"(d[42]), "+f"(d[43]), "+f"(d[44]), "+f"(d[45]), "+f"(d[46]), "+f"(d[47]),
          "+f"(d[48]), "+f"(d[49]), "+f"(d[50]), "+f"(d[51]), "+f"(d[52]), "+f"(d[53]), "+f"(d[54]), "+f"(d[55]),
          "+f"(d[56]), "+f"(d[57]), "+f"(d[58]), "+f"(d[59]), "+f"(d[60]), "+f"(d[61]), "+f"(d[62]), "+f"(d[63]),
          "+f"(d[64]), "+f"(d[65]), "+f"(d[66]), "+f"(d[67]), "+f"(d[68]), "+f"(d[69]), "+f"(d[70]), "+f"(d[71]),
          "+f"(d[72]), "+f"(d[73]), "+f"(d[74]), "+f"(d[75]), "+f"(d[76]), "+f"(d[77]), "+f"(d[78]), "+f"(d[79]),
          "+f"(d[80]), "+f"(d[81]), "+f"(d[82]), "+f"(d[83]), "+f"(d[84]), "+f"(d[85]), "+f"(d[86]), "+f"(d[87]),
          "+f"(d[88]), "+f"(d[89]), "+f"(d[90]), "+f"(d[91])
        : "l"(descA), "l"(descB), "r"(scaleD));
}

__device__ __forceinline__ void wgmma_ss_n192_t1(float (&d)[96], uint64_t descA, uint64_t descB, int scaleD) {
    asm volatile("{\n.reg .pred p;\n"
        "setp.ne.b32 p, %98, 0;\n"
        "wgmma.mma_async.sync.aligned.m64n192k16.f32.bf16.bf16 "
        "{%0, %1, %2, %3, %4, %5, %6, %7, %8, %9, %10, %11, %12, %13, %14, %15, "
        "%16, %17, %18, %19, %20, %21, %22, %23, %24, %25, %26, %27, %28, %29, %30, %31, "
        "%32, %33, %34, %35, %36, %37, %38, %39, %40, %41, %42, %43, %44, %45, %46, %47, "
        "%48, %49, %50, %51, %52, %53, %54, %55, %56, %57, %58, %59, %60, %61, %62, %63, "
        "%64, %65, %66, %67, %68, %69, %70, %71, %72, %73, %74, %75, %76, %77, %78, %79, "
        "%80, %81, %82, %83, %84, %85, %86, %87, %88, %89, %90, %91, %92, %93, %94, %95}, "
        "%96, %97, p, 1, 1, 0, 1;\n}\n"
        :
          "+f"(d[0]), "+f"(d[1]), "+f"(d[2]), "+f"(d[3]), "+f"(d[4]), "+f"(d[5]), "+f"(d[6]), "+f"(d[7]),
          "+f"(d[8]), "+f"(d[9]), "+f"(d[10]), "+f"(d[11]), "+f"(d[12]), "+f"(d[13]), "+f"(d[14]), "+f"(d[15]),
          "+f"(d[16]), "+f"(d[17]), "+f"(d[18]), "+f"(d[19]), "+f"(d[20]), "+f"(d[21]), "+f"(d[22]), "+f"(d[23]),
          "+f"(d[24]), "+f"(d[25]), "+f"(d[26]), "+f"(d[27]), "+f"(d[28]), "+f"(d[29]), "+f"(d[30]), "+f"(d[31]),
          "+f"(d[32]), "+f"(d[33]), "+f"(d[34]), "+f"(d[35]), "+f"(d[36]), "+f"(d[37]), "+f"(d[38]), "+f"(d[39]),
          "+f"(d[40]), "+f"(d[41]), "+f"(d[42]), "+f"(d[43]), "+f"(d[44]), "+f"(d[45]), "+f"(d[46]), "+f"(d[47]),
          "+f"(d[48]), "+f"(d[49]), "+f"(d[50]), "+f"(d[51]), "+f"(d[52]), "+f"(d[53]), "+f"(d[54]), "+f"(d[55]),
          "+f"(d[56]), "+f"(d[57]), "+f"(d[58]), "+f"(d[59]), "+f"(d[60]), "+f"(d[61]), "+f"(d[62]), "+f"(d[63]),
          "+f"(d[64]), "+f"(d[65]), "+f"(d[66]), "+f"(d[67]), "+f"(d[68]), "+f"(d[69]), "+f"(d[70]), "+f"(d[71]),
          "+f"(d[72]), "+f"(d[73]), "+f"(d[74]), "+f"(d[75]), "+f"(d[76]), "+f"(d[77]), "+f"(d[78]), "+f"(d[79]),
          "+f"(d[80]), "+f"(d[81]), "+f"(d[82]), "+f"(d[83]), "+f"(d[84]), "+f"(d[85]), "+f"(d[86]), "+f"(d[87]),
          "+f"(d[88]), "+f"(d[89]), "+f"(d[90]), "+f"(d[91]), "+f"(d[92]), "+f"(d[93]), "+f"(d[94]), "+f"(d[95])
        : "l"(descA), "l"(descB), "r"(scaleD));
}

__device__ __forceinline__ void wgmma_ss_n128_t1(float (&d)[64], uint64_t descA, uint64_t descB, int scaleD) {
    asm volatile("{\n.reg .pred p;\n"
        "setp.ne.b32 p, %66, 0;\n"
        "wgmma.mma_async.sync.aligned.m64n128k16.f32.bf16.bf16 "
        "{%0, %1, %2, %3, %4, %5, %6, %7, %8, %9, %10, %11, %12, %13, %14, %15, "
        "%16, %17, %18, %19, %20, %21, %22, %23, %24, %25, %26, %27, %28, %29, %30, %31, "
        "%32, %33, %34, %35, %36, %37, %38, %39, %40, %41, %42, %43, %44, %45, %46, %47, "
        "%48, %49, %50, %51, %52, %53, %54, %55, %56, %57, %58, %59, %60, %61, %62, %63}, "
        "%64, %65, p, 1, 1, 0, 1;\n}\n"
        :
          "+f"(d[0]), "+f"(d[1]), "+f"(d[2]), "+f"(d[3]), "+f"(d[4]), "+f"(d[5]), "+f"(d[6]), "+f"(d[7]),
          "+f"(d[8]), "+f"(d[9]), "+f"(d[10]), "+f"(d[11]), "+f"(d[12]), "+f"(d[13]), "+f"(d[14]), "+f"(d[15]),
          "+f"(d[16]), "+f"(d[17]), "+f"(d[18]), "+f"(d[19]), "+f"(d[20]), "+f"(d[21]), "+f"(d[22]), "+f"(d[23]),
          "+f"(d[24]), "+f"(d[25]), "+f"(d[26]), "+f"(d[27]), "+f"(d[28]), "+f"(d[29]), "+f"(d[30]), "+f"(d[31]),
          "+f"(d[32]), "+f"(d[33]), "+f"(d[34]), "+f"(d[35]), "+f"(d[36]), "+f"(d[37]), "+f"(d[38]), "+f"(d[39]),
          "+f"(d[40]), "+f"(d[41]), "+f"(d[42]), "+f"(d[43]), "+f"(d[44]), "+f"(d[45]), "+f"(d[46]), "+f"(d[47]),
          "+f"(d[48]), "+f"(d[49]), "+f"(d[50]), "+f"(d[51]), "+f"(d[52]), "+f"(d[53]), "+f"(d[54]), "+f"(d[55]),
          "+f"(d[56]), "+f"(d[57]), "+f"(d[58]), "+f"(d[59]), "+f"(d[60]), "+f"(d[61]), "+f"(d[62]), "+f"(d[63])
        : "l"(descA), "l"(descB), "r"(scaleD));
}

__device__ __forceinline__ void wgmma_ss_n32_t1(float (&d)[16], uint64_t descA, uint64_t descB, int scaleD) {
    asm volatile("{\n.reg .pred p;\n"
        "setp.ne.b32 p, %18, 0;\n"
        "wgmma.mma_async.sync.aligned.m64n32k16.f32.bf16.bf16 "
        "{%0, %1, %2, %3, %4, %5, %6, %7, %8, %9, %10, %11, %12, %13, %14, %15}, "
        "%16, %17, p, 1, 1, 0, 1;\n}\n"
        :
          "+f"(d[0]), "+f"(d[1]), "+f"(d[2]), "+f"(d[3]), "+f"(d[4]), "+f"(d[5]), "+f"(d[6]), "+f"(d[7]),
          "+f"(d[8]), "+f"(d[9]), "+f"(d[10]), "+f"(d[11]), "+f"(d[12]), "+f"(d[13]), "+f"(d[14]), "+f"(d[15])
        : "l"(descA), "l"(descB), "r"(scaleD));
}

constexpr int S_LEN = 2048;
constexpr int D_MODEL = 640;
constexpr int N_HEADS = 32;
constexpr int D_HEAD = 128;
constexpr int S_KV = 2048;
constexpr int WIN = 512;
constexpr int D_FF = 1728;
constexpr float LN_EPS = 1e-5f;

#define TS(kid, slot)

__device__ float g_mod[6 * D_MODEL];
__device__ __align__(1024) __nv_bfloat16 g_h[S_LEN * D_MODEL];
__device__ __align__(1024) __nv_bfloat16 g_o[S_LEN * N_HEADS * D_HEAD];
__device__ __align__(1024) __nv_bfloat16 g_part[4 * S_LEN * D_MODEL];
__device__ __align__(1024) __nv_bfloat16 g_x1[S_LEN * D_MODEL];
__device__ __align__(1024) __nv_bfloat16 g_h2[S_LEN * D_MODEL];
__device__ __align__(1024) __nv_bfloat16 g_act[S_LEN * D_FF];

constexpr int F_MODAB = 0, F_MODALL = 1, F_H = 2, F_P = 18, F_H2 = 34, F_A = 50, F_O = 66, F_A1 = 130, F_COUNT = 146;
__device__ unsigned g_flags[F_COUNT * 32];
__device__ unsigned g_epoch;
__device__ unsigned g_exit;

__device__ __forceinline__ void flag_signal(int f) {
    asm volatile("red.release.gpu.global.add.u32 [%0], 1;" ::"l"(g_flags + f * 32) : "memory");
}
__device__ __forceinline__ void flag_signal_relaxed(int f) {
    asm volatile("red.relaxed.gpu.global.add.u32 [%0], 1;" ::"l"(g_flags + f * 32) : "memory");
}
__device__ __forceinline__ void flag_wait(int f, unsigned target) {
    unsigned n = 0;
    while (true) {
        unsigned v;
        asm volatile("ld.acquire.gpu.global.u32 %0, [%1];" : "=r"(v) : "l"(g_flags + f * 32) : "memory");
        if ((int)(v - target) >= 0) break;
        if ((++n & 0xfffu) == 0) {
            if (n > (1u << 24)) g_abort = 1;
            if (g_abort) break;
        }
    }
}

struct Maps {
    CUtensorMap h, wq, k, v, o_st, o_a, wo, part_st, h2, g128, u128, g64, u64, act_st64, act_st24, act_a, wd, wd32;
};

constexpr int SM_DATA = 229376;
constexpr int SM_STAGING = 196608;
constexpr int SM_TOTAL = SM_DATA + 1024 + 512;
constexpr int B1F = 0, B1E = 6, B2F = 12, B2E = 16, B4F = 20, B4E = 24, B5F = 28, B5E = 33, BD1 = 38, BD2 = 39, BD4 = 40, BD1A = 41, BX = 42, BD4B = 43;
constexpr int P1_STAGE = 32768, P2_STAGE = 57344, P4_STAGE = 49152, P5_STAGE = 36864;

__device__ __forceinline__ float rcp_approx(float x) { float y; asm("rcp.approx.ftz.f32 %0, %1;" : "=f"(y) : "f"(x)); return y; }
__device__ __forceinline__ float silu_mul(float g, float u) { return g * rcp_approx(1.f + ex2(-1.4426950408889634f * g)) * u; }
__device__ __forceinline__ uint2 ldcg_u2(const void* p) { return __ldcg(reinterpret_cast<const uint2*>(p)); }

__device__ __noinline__ void ln_rows_impl(uint2 a0, uint2 a1, uint2 a2, uint2 a3, uint2 a4, uint2 b0, uint2 b1, uint2 b2, uint2 b3, uint2 b4,
                                          const float* __restrict__ shift, const float* __restrict__ scale1p,
                                          __nv_bfloat16* __restrict__ dst, int lane) {
    const uint2 xr[2][5] = {{a0, a1, a2, a3, a4}, {b0, b1, b2, b3, b4}};
    float4 sh[5], sc[5];
#pragma unroll
    for (int i = 0; i < 5; i++) {
        sh[i] = __ldcg(reinterpret_cast<const float4*>(shift + (lane + 32 * i) * 4));
        sc[i] = __ldcg(reinterpret_cast<const float4*>(scale1p + (lane + 32 * i) * 4));
    }
    float mean[2], rstd[2];
#pragma unroll
    for (int rr = 0; rr < 2; rr++) {
        float s = 0.f;
#pragma unroll
        for (int i = 0; i < 5; i++) s += (bf16lo(xr[rr][i].x) + bf16hi(xr[rr][i].x)) + (bf16lo(xr[rr][i].y) + bf16hi(xr[rr][i].y));
#pragma unroll
        for (int o = 16; o > 0; o >>= 1) s += __shfl_xor_sync(0xffffffffu, s, o);
        mean[rr] = s * (1.f / D_MODEL);
    }
#pragma unroll
    for (int rr = 0; rr < 2; rr++) {
        float q = 0.f;
#pragma unroll
        for (int i = 0; i < 5; i++) {
            const float d0 = bf16lo(xr[rr][i].x) - mean[rr], d1 = bf16hi(xr[rr][i].x) - mean[rr];
            const float d2 = bf16lo(xr[rr][i].y) - mean[rr], d3 = bf16hi(xr[rr][i].y) - mean[rr];
            q += (d0 * d0 + d1 * d1) + (d2 * d2 + d3 * d3);
        }
#pragma unroll
        for (int o = 16; o > 0; o >>= 1) q += __shfl_xor_sync(0xffffffffu, q, o);
        rstd[rr] = rsqrtf(q * (1.f / D_MODEL) + LN_EPS);
    }
#pragma unroll
    for (int rr = 0; rr < 2; rr++) {
#pragma unroll
        for (int i = 0; i < 5; i++) {
            uint2 u;
            u.x = pack_bf16((bf16lo(xr[rr][i].x) - mean[rr]) * rstd[rr] * sc[i].x + sh[i].x, (bf16hi(xr[rr][i].x) - mean[rr]) * rstd[rr] * sc[i].y + sh[i].y);
            u.y = pack_bf16((bf16lo(xr[rr][i].y) - mean[rr]) * rstd[rr] * sc[i].z + sh[i].z, (bf16hi(xr[rr][i].y) - mean[rr]) * rstd[rr] * sc[i].w + sh[i].w);
            *reinterpret_cast<uint2*>(dst + (size_t)rr * D_MODEL + (lane + 32 * i) * 4) = u;
        }
    }
}

__device__ __forceinline__ void ln_rows(const uint2 (&xr)[2][5], const float* shift, const float* scale1p, __nv_bfloat16* dst, int lane) {
    ln_rows_impl(xr[0][0], xr[0][1], xr[0][2], xr[0][3], xr[0][4], xr[1][0], xr[1][1], xr[1][2], xr[1][3], xr[1][4], shift, scale1p, dst, lane);
}

__global__ void __cluster_dims__(2, 1, 1) __launch_bounds__(384, 1)
mega_kernel(const __grid_constant__ Maps tm, const __nv_bfloat16* __restrict__ x, const __nv_bfloat16* __restrict__ cvec,
            const __nv_bfloat16* __restrict__ w_mod, __nv_bfloat16* __restrict__ out, const void* wo_p, const void* wg_p,
            const void* wu_p, const void* wd_p) {
    extern __shared__ uint8_t smem_raw[];
    const uint32_t base = (smem_u32(smem_raw) + 1023u) & ~1023u;
    const uint32_t bars = base + SM_DATA;
    const uint32_t rank = cluster_ctarank();
    const int cid = blockIdx.x >> 1;
    const int p = cid & 7, j = cid >> 3;
    const int mt = p * 2 + (int)rank;
    const int m0 = mt * 128;
    const int wg = threadIdx.x >> 7;
    unsigned epoch;
    asm volatile("ld.volatile.global.u32 %0, [%1];" : "=r"(epoch) : "l"(&g_epoch));

    if (threadIdx.x == 0) {
        for (int i = 0; i < 6; i++) { mbar_init(bars + 8 * (B1F + i), 1); mbar_init(bars + 8 * (B1E + i), 4); }
        for (int i = 0; i < 4; i++) { mbar_init(bars + 8 * (B2F + i), 1); mbar_init(bars + 8 * (B2E + i), 4); }
        for (int i = 0; i < 4; i++) { mbar_init(bars + 8 * (B4F + i), 1); mbar_init(bars + 8 * (B4E + i), 4); }
        for (int i = 0; i < 5; i++) { mbar_init(bars + 8 * (B5F + i), 1); mbar_init(bars + 8 * (B5E + i), 2); }
        mbar_init(bars + 8 * BD1, 4); mbar_init(bars + 8 * BD2, 4); mbar_init(bars + 8 * BD4, 4); mbar_init(bars + 8 * BD1A, 4);
        mbar_init(bars + 8 * BX, 1); mbar_init(bars + 8 * BD4B, 4);
        mbar_expect_tx(bars + 8 * BX, 40960);
        fence_mbar_init();
    }
    __syncthreads();
    cluster_sync();

    if (wg == 2) {
        reg_dealloc<40>();
        if (threadIdx.x == 256) {
            {
                uint32_t st = 0, ph = 1;
                bool first = true;
#pragma unroll 1
                for (int hp = 0; hp < 2; hp++) {
                    const int head0 = j * 4 + hp * 2;
                    if (first) {
#pragma unroll 1
                        for (int s = 1; s < 6; s++) {
                            if (s == 3) continue;
                            const int kb = s < 3 ? s - 1 : s - 2;
                            mbar_expect_tx(bars + 8 * (B1F + s), P1_STAGE);
#pragma unroll 1
                            for (int c = 0; c < 2; c++) {
                                const int chunk = 2 * (int)rank + c;
                                tma_load_2d_mc(base + s * P1_STAGE + chunk * 8192, &tm.wq, head0 * 128 + chunk * 64, kb * 64, bars + 8 * (B1F + s), 3);
                            }
                        }
                        flag_wait(F_H + mt, (epoch + 1) * 8);
                        fence_proxy_async_all();
#pragma unroll 1
                        for (int s = 0; s < 6; s += 3) {
                            mbar_expect_tx(bars + 8 * (B1F + s), P1_STAGE);
                            tma_load_2d(base + s * P1_STAGE, &tm.h, (s / 3 * 2) * 64, m0, bars + 8 * (B1F + s));
                            tma_load_2d(base + s * P1_STAGE + 16384, &tm.h, (s / 3 * 2 + 1) * 64, m0, bars + 8 * (B1F + s));
                        }
                        ph = 0;
                    }
#pragma unroll 1
                    for (int kk2 = first ? 2 : 0; kk2 < 5; kk2++) {
                        mbar_wait(bars + 8 * (B1E + st), ph);
                        mbar_expect_tx(bars + 8 * (B1F + st), P1_STAGE);
                        tma_load_2d(base + st * P1_STAGE, &tm.h, (2 * kk2) * 64, m0, bars + 8 * (B1F + st));
                        tma_load_2d(base + st * P1_STAGE + 16384, &tm.h, (2 * kk2 + 1) * 64, m0, bars + 8 * (B1F + st));
                        if (++st == 6) { st = 0; ph ^= 1; }
#pragma unroll 1
                        for (int u = 0; u < 2; u++) {
                            mbar_wait(bars + 8 * (B1E + st), ph);
                            mbar_expect_tx(bars + 8 * (B1F + st), P1_STAGE);
                            const int kb = 2 * kk2 + u;
#pragma unroll 1
                            for (int c = 0; c < 2; c++) {
                                const int chunk = 2 * (int)rank + c;
                                tma_load_2d_mc(base + st * P1_STAGE + chunk * 8192, &tm.wq, head0 * 128 + chunk * 64, kb * 64, bars + 8 * (B1F + st), 3);
                            }
                            if (++st == 6) { st = 0; ph ^= 1; }
                        }
                    }
                    first = false;
#pragma unroll 1
                    for (int t = 0; t <= 8; t++) {
                        if (t < 8) {
                            mbar_wait(bars + 8 * (B1E + st), ph);
                            mbar_expect_tx(bars + 8 * (B1F + st), P1_STAGE);
                            const int row = (head0 + (t >> 2)) * S_KV + (S_KV - WIN) + (t & 3) * 128;
                            tma_load_2d_mc(base + st * P1_STAGE + rank * 16384, &tm.k, rank * 64, row, bars + 8 * (B1F + st), 3);
                            if (++st == 6) { st = 0; ph ^= 1; }
                        }
                        if (t > 0) {
                            mbar_wait(bars + 8 * (B1E + st), ph);
                            mbar_expect_tx(bars + 8 * (B1F + st), P1_STAGE);
                            const int tv = t - 1;
                            const int row = (head0 + (tv >> 2)) * S_KV + (S_KV - WIN) + (tv & 3) * 128;
                            tma_load_2d_mc(base + st * P1_STAGE + rank * 16384, &tm.v, rank * 64, row, bars + 8 * (B1F + st), 3);
                            if (++st == 6) { st = 0; ph ^= 1; }
                        }
                    }
                }
            }
            {
                const int kq = j >> 1, n0 = (j & 1) * 320;
                uint32_t st = 0, ph = 1;
#pragma unroll 1
                for (int i = 0; i < 16; i++) {
                    if (i == 0) mbar_wait(bars + 8 * BD1A, 0);
                    if (i == 3) mbar_wait(bars + 8 * BD1, 0);
                    if (i == 8) { flag_wait(F_O + mt * 4 + kq, (epoch + 1) * 4); fence_proxy_async_all(); }
                    mbar_wait(bars + 8 * (B2E + st), ph);
                    mbar_expect_tx(bars + 8 * (B2F + st), P2_STAGE);
                    const uint32_t dst = base + st * P2_STAGE;
                    const int k0 = kq * 1024 + ((i + (j & 1) * 8) & 15) * 64;
                    tma_load_2d(dst, &tm.o_a, k0, m0, bars + 8 * (B2F + st));
#pragma unroll 1
                    for (int c = 0; c < 5; c++)
                        if (((c + i) & 1) == (int)rank) tma_load_2d_mc(dst + 16384 + c * 8192, &tm.wo, n0 + c * 64, k0, bars + 8 * (B2F + st), 3);
                    if (++st == 4) { st = 0; ph ^= 1; }
                }
            }
            {
                const int f0 = j * 216;
                const CUtensorMap* t128 = rank == 0 ? &tm.g128 : &tm.u128;
                const CUtensorMap* t64 = rank == 0 ? &tm.g64 : &tm.u64;
                mbar_wait(bars + 8 * BD2, 0);
#pragma unroll 1
                for (int i = 0; i < 4; i++) {
                    mbar_expect_tx(bars + 8 * (B4F + i), 16384 + 32768);
                    const uint32_t dst = base + i * P4_STAGE;
                    tma_load_2d_mc(dst + 16384 + rank * 16384, t128, f0, i * 64, bars + 8 * (B4F + i), 3);
                    tma_load_2d_mc(dst + 16384 + rank * 16384 + 8192, t128, f0 + 64, i * 64, bars + 8 * (B4F + i), 3);
                }
                flag_wait(F_H2 + mt, (epoch + 1) * 8);
                fence_proxy_async_all();
#pragma unroll 1
                for (int i = 0; i < 4; i++) tma_load_2d(base + i * P4_STAGE, &tm.h2, i * 64, m0, bars + 8 * (B4F + i));
                uint32_t st = 0, ph = 0;
#pragma unroll 1
                for (int i = 4; i < 20; i++) {
                    const int kb = i < 10 ? i : i - 10;
                    mbar_wait(bars + 8 * (B4E + st), ph);
                    const uint32_t dst = base + st * P4_STAGE;
                    if (i < 10) {
                        mbar_expect_tx(bars + 8 * (B4F + st), 16384 + 32768);
                        tma_load_2d(dst, &tm.h2, kb * 64, m0, bars + 8 * (B4F + st));
                        tma_load_2d_mc(dst + 16384 + rank * 16384, t128, f0, kb * 64, bars + 8 * (B4F + st), 3);
                        tma_load_2d_mc(dst + 16384 + rank * 16384 + 8192, t128, f0 + 64, kb * 64, bars + 8 * (B4F + st), 3);
                    } else {
                        mbar_expect_tx(bars + 8 * (B4F + st), 16384 + 24576);
                        tma_load_2d(dst, &tm.h2, kb * 64, m0, bars + 8 * (B4F + st));
#pragma unroll 1
                        for (int c = 0; c < 3; c++)
                            tma_load_2d_mc(dst + 16384 + rank * 12288 + c * 4096, t64, f0 + 128 + c * 32, kb * 64, bars + 8 * (B4F + st), 3);
                    }
                    if (++st == 4) { st = 0; ph ^= 1; }
                }
            }
            {
                const int mt5 = p * 2 + (j >> 2), n0 = (j & 3) * 160;
                const int nkb = rank == 0 ? 14 : 13;
                const unsigned long long ord = rank == 0
                    ? (0ull | 1ull << 5 | 4ull << 10 | 7ull << 15 | 11ull << 20 | 2ull << 25 | 3ull << 30 | 5ull << 35 | 6ull << 40 | 8ull << 45 | 9ull << 50 | 10ull << 55)
                    : (14ull | 17ull << 5 | 21ull << 10 | 24ull << 15 | 15ull << 20 | 16ull << 25 | 18ull << 30 | 19ull << 35 | 20ull << 40 | 22ull << 45 | 23ull << 50 | 25ull << 55);
                const int nearly = rank == 0 ? 5 : 4;
                mbar_wait(bars + 8 * BD4, 0);
                uint32_t st = 0, ph = 1;
#pragma unroll 1
                for (int i = 0; i < nkb; i++) {
                    const int kb = i < 12 ? (int)((ord >> (5 * i)) & 31) : (rank == 0 ? i : 26);
                    if (i == 0) { flag_wait(F_A1 + mt5, (epoch + 1) * 16); fence_proxy_async_all(); }
                    if (i == nearly) { flag_wait(F_A + mt5, (epoch + 1) * 16); fence_proxy_async_all(); }
                    mbar_wait(bars + 8 * (B5E + st), ph);
                    mbar_expect_tx(bars + 8 * (B5F + st), P5_STAGE);
                    const uint32_t dst = base + st * P5_STAGE;
                    const int k0 = kb * 64;
                    tma_load_2d(dst + 16384, &tm.wd, n0, k0, bars + 8 * (B5F + st));
                    tma_load_2d(dst + 16384 + 8192, &tm.wd, n0 + 64, k0, bars + 8 * (B5F + st));
                    tma_load_2d(dst + 16384 + 16384, &tm.wd32, n0 + 128, k0, bars + 8 * (B5F + st));
                    tma_load_2d(dst, &tm.act_a, k0, mt5 * 128, bars + 8 * (B5F + st));
                    if (++st == 5) { st = 0; ph ^= 1; }
                }
            }
        }
        else if (threadIdx.x == 288) {
            mbar_wait(bars + 8 * B1F, 0);
            const char* pw[4] = {(const char*)wo_p, (const char*)wg_p, (const char*)wu_p, (const char*)wd_p};
#pragma unroll 1
            for (int t = 0; t < 4; t++) {
                const uint32_t bytes = t == 0 ? 40960u : 17280u;
                asm volatile("cp.async.bulk.prefetch.L2.global [%0], %1;" ::"l"(pw[t] + (size_t)blockIdx.x * bytes), "r"(bytes) : "memory");
            }
        }
        __syncwarp();
        asm volatile("barrier.cluster.arrive.relaxed.aligned; // producer\n barrier.cluster.wait.aligned;" ::: "memory");
    } else {
        reg_alloc<232>();
        const int tid = threadIdx.x & 127;
        const int warp = tid >> 5, lane = tid & 31;
        const int cw = threadIdx.x >> 5;
        const uint32_t mystage = base + SM_STAGING + wg * 16384;
        auto arrive_both = [&](uint32_t bar) {
            if (tid == 0) mbar_arrive_cluster(bar, 0);
            if (tid == 32) mbar_arrive_cluster(bar, 1);
        };
        TS(0, 0);
        uint2 xr0[10];
        {
            uint2 xr[2][5];
            uint4 w[10];
            unsigned short cr[10];
            const int mb = blockIdx.x < 120 ? blockIdx.x : 0;
#pragma unroll
            for (int i = 0; i < 10; i++) cr[i] = __ldg(reinterpret_cast<const unsigned short*>(cvec) + cw * 80 + i * 8 + (lane >> 2));
#pragma unroll
            for (int i = 0; i < 10; i++)
                w[i] = __ldg(reinterpret_cast<const uint4*>(w_mod + (size_t)(cw * 80 + i * 8 + (lane >> 2)) * (6 * D_MODEL) + mb * 32 + (lane & 3) * 8));
#pragma unroll
            for (int rr = 0; rr < 2; rr++)
#pragma unroll
                for (int i = 0; i < 5; i++)
                    xr[rr][i] = __ldg(reinterpret_cast<const uint2*>(x + (size_t)(m0 + j * 16 + cw * 2 + rr) * D_MODEL + (lane + 32 * i) * 4));
            if (blockIdx.x < 120) {
                float* red = reinterpret_cast<float*>(smem_raw + (base - smem_u32(smem_raw)) + SM_STAGING);
                float acc[8];
#pragma unroll
                for (int i = 0; i < 8; i++) acc[i] = 0.f;
#pragma unroll
                for (int i = 0; i < 10; i++) {
                    const float s = bf16_round(silu_mul(__uint_as_float((uint32_t)cr[i] << 16), 1.f));
                    acc[0] += s * bf16lo(w[i].x); acc[1] += s * bf16hi(w[i].x);
                    acc[2] += s * bf16lo(w[i].y); acc[3] += s * bf16hi(w[i].y);
                    acc[4] += s * bf16lo(w[i].z); acc[5] += s * bf16hi(w[i].z);
                    acc[6] += s * bf16lo(w[i].w); acc[7] += s * bf16hi(w[i].w);
                }
#pragma unroll
                for (int i = 0; i < 8; i++) {
                    acc[i] += __shfl_xor_sync(0xffffffffu, acc[i], 4);
                    acc[i] += __shfl_xor_sync(0xffffffffu, acc[i], 8);
                    acc[i] += __shfl_xor_sync(0xffffffffu, acc[i], 16);
                }
                if (lane < 4) {
#pragma unroll
                    for (int i = 0; i < 8; i++) red[cw * 32 + lane * 8 + i] = acc[i];
                }
                TS(6, 0);
                bar_sync(5, 256);
                TS(6, 1);
                if (threadIdx.x < 32) {
                    float t = 0.f;
#pragma unroll
                    for (int i = 0; i < 8; i++) t += red[i * 32 + threadIdx.x];
                    t = bf16_round(t);
                    const int chunk = blockIdx.x / 20;
                    if (chunk == 1 || chunk == 4) t = bf16_round(1.f + t);
                    g_mod[blockIdx.x * 32 + threadIdx.x] = t;
                    __syncwarp();
                    TS(6, 2);
                    if (threadIdx.x == 0) flag_signal(blockIdx.x < 40 ? F_MODAB : F_MODALL);
                    TS(6, 3);
                }
            }
            xr0[0] = xr[0][0]; xr0[1] = xr[0][1]; xr0[2] = xr[0][2]; xr0[3] = xr[0][3]; xr0[4] = xr[0][4];
            xr0[5] = xr[1][0]; xr0[6] = xr[1][1]; xr0[7] = xr[1][2]; xr0[8] = xr[1][3]; xr0[9] = xr[1][4];
        }
#pragma unroll 1
        for (int pass = 0; pass < 2; pass++) {
        const bool live = pass == 1;
        if (live) {
            if (threadIdx.x == 0) flag_wait(F_MODAB, (epoch + 1) * 40);
            bar_sync(5, 256);
            TS(0, 1);
            ln_rows_impl(xr0[0], xr0[1], xr0[2], xr0[3], xr0[4], xr0[5], xr0[6], xr0[7], xr0[8], xr0[9], g_mod, g_mod + D_MODEL,
                         g_h + (size_t)(m0 + j * 16 + cw * 2) * D_MODEL, lane);
            bar_sync(5, 256);
            if (threadIdx.x == 0) flag_signal(F_H + mt);
        }
        TS(0, 2);
        if (live) {
            const float cscale = 0.08838834764831845f * 1.4426950408889634f;
            uint32_t st = 0, ph = 0;
            auto wait_full = [&]() -> uint32_t {
                mbar_wait(bars + 8 * (B1F + st), ph);
                return base + st * P1_STAGE;
            };
            auto release = [&](uint32_t s) { arrive_both(bars + 8 * (B1E + s)); };
            auto advance = [&]() { if (++st == 6) { st = 0; ph ^= 1; } };
            auto turn_wait = [&]() { bar_sync(3 + wg, 256); };
            auto turn_pass = [&]() { bar_arrive(3 + (wg ^ 1), 256); };
            if (wg == 1) bar_arrive(3, 256);

            for (int hp = 0; hp < 2; hp++) {
                const int head0 = j * 4 + hp * 2;
                uint32_t q[8][4];
                {
                    float acc[128];
#pragma unroll
                    for (int i = 0; i < 128; i++) acc[i] = 0.f;
                    for (int kk2 = 0; kk2 < 5; kk2++) {
                        const uint32_t hbuf = wait_full();
                        if (kk2 == 0 && hp == 0) TS(0, 3);
                        const uint32_t sth = st;
                        advance();
#pragma unroll
                        for (int u = 0; u < 2; u++) {
                            const uint32_t wbuf = wait_full();
                            const uint32_t stw = st;
                            advance();
                            wgmma_fence();
#pragma unroll
                            for (int k = 0; k < 4; k++) {
                                uint64_t da = make_desc(hbuf + u * 16384 + wg * 8192 + k * 32, 16, 1024, 1);
                                uint64_t db = make_desc(wbuf + k * 2048, 8192, 1024, 1);
                                wgmma_ss_n256_t1(acc, da, db, 1);
                            }
                            wgmma_commit();
                            wgmma_wait<0>();
                            release(stw);
                        }
                        release(sth);
                    }
                    fence_regs(acc);
                    if (tid == 0) tma_store_wait_read<0>();
                    bar_sync(1 + wg, 128);
#pragma unroll
                    for (int i = 0; i < 8; i++) {
                        q[i][0] = pack_bf16(acc[8 * i + 0], acc[8 * i + 1]);
                        q[i][1] = pack_bf16(acc[8 * i + 2], acc[8 * i + 3]);
                        q[i][2] = pack_bf16(acc[8 * i + 4], acc[8 * i + 5]);
                        q[i][3] = pack_bf16(acc[8 * i + 6], acc[8 * i + 7]);
                        uint32_t b0 = pack_bf16(acc[64 + 8 * i + 0], acc[64 + 8 * i + 1]);
                        uint32_t b1 = pack_bf16(acc[64 + 8 * i + 2], acc[64 + 8 * i + 3]);
                        uint32_t b2 = pack_bf16(acc[64 + 8 * i + 4], acc[64 + 8 * i + 5]);
                        uint32_t b3 = pack_bf16(acc[64 + 8 * i + 6], acc[64 + 8 * i + 7]);
                        asm volatile("st.shared.v4.b32 [%0], {%1, %2, %3, %4};" ::"r"(mystage + (i * 128 + tid) * 16), "r"(b0), "r"(b1),
                                     "r"(b2), "r"(b3) : "memory");
                    }
                }
                float o[64], s[64], e[64];
                uint32_t pp[8][4];
                float mm0, mm1, l0, l1, a0, a1, lo0, lo1;
#pragma unroll
                for (int i = 0; i < 64; i++) { o[i] = 0.f; }

                auto issue_s = [&]() -> uint32_t {
                    const uint32_t kbuf = wait_full();
                    const uint32_t stk = st;
                    advance();
                    wgmma_fence();
#pragma unroll
                    for (int k = 0; k < 8; k++) {
                        uint64_t db = make_desc(kbuf + (k >> 2) * 16384 + (k & 3) * 32, 16, 1024, 1);
                        if (k == 0) wgmma_rs_n128_t0_z(s, q[k], db);
                        else wgmma_rs_n128_t0(s, q[k], db, 1);
                    }
                    wgmma_commit();
                    return stk;
                };
                auto issue_pv = [&](bool fresh) -> uint32_t {
                    const uint32_t vbuf = wait_full();
                    const uint32_t stv = st;
                    advance();
                    wgmma_fence();
#pragma unroll
                    for (int k = 0; k < 8; k++) {
                        uint64_t db = make_desc(vbuf + k * 2048, 16384, 1024, 1);
                        wgmma_rs_n128_t1(o, pp[k], db, (!fresh) || k != 0);
                    }
                    wgmma_commit();
                    return stv;
                };
                auto softmax = [&](bool first) {
                    float mx0 = fmaxf(s[0], s[1]), mx1 = fmaxf(s[2], s[3]);
#pragma unroll
                    for (int jj = 1; jj < 16; jj++) {
                        mx0 = fmaxf(mx0, fmaxf(s[4 * jj], s[4 * jj + 1]));
                        mx1 = fmaxf(mx1, fmaxf(s[4 * jj + 2], s[4 * jj + 3]));
                    }
                    mx0 = fmaxf(mx0, __shfl_xor_sync(0xffffffffu, mx0, 1));
                    mx0 = fmaxf(mx0, __shfl_xor_sync(0xffffffffu, mx0, 2));
                    mx1 = fmaxf(mx1, __shfl_xor_sync(0xffffffffu, mx1, 1));
                    mx1 = fmaxf(mx1, __shfl_xor_sync(0xffffffffu, mx1, 2));
                    if (first) {
                        lo0 = l0; lo1 = l1;
                        mm0 = mx0; mm1 = mx1; l0 = 0.f; l1 = 0.f; a0 = 0.f; a1 = 0.f;
                    } else {
                        float mn0 = fmaxf(mm0, mx0), mn1 = fmaxf(mm1, mx1);
                        a0 = ex2((mm0 - mn0) * cscale); a1 = ex2((mm1 - mn1) * cscale);
                        mm0 = mn0; mm1 = mn1;
                    }
                    const float mc0 = mm0 * cscale, mc1 = mm1 * cscale;
                    float r0 = 0.f, r1 = 0.f;
#pragma unroll
                    for (int jj = 0; jj < 16; jj++) {
                        e[4 * jj] = ex2(fmaf(s[4 * jj], cscale, -mc0));
                        e[4 * jj + 1] = ex2(fmaf(s[4 * jj + 1], cscale, -mc0));
                        e[4 * jj + 2] = ex2(fmaf(s[4 * jj + 2], cscale, -mc1));
                        e[4 * jj + 3] = ex2(fmaf(s[4 * jj + 3], cscale, -mc1));
                        r0 += e[4 * jj] + e[4 * jj + 1];
                        r1 += e[4 * jj + 2] + e[4 * jj + 3];
                    }
                    l0 = l0 * a0 + r0; l1 = l1 * a1 + r1;
                };
                auto convert_p = [&]() {
#pragma unroll
                    for (int i = 0; i < 8; i++) {
                        pp[i][0] = pack_bf16(e[8 * i + 0], e[8 * i + 1]);
                        pp[i][1] = pack_bf16(e[8 * i + 2], e[8 * i + 3]);
                        pp[i][2] = pack_bf16(e[8 * i + 4], e[8 * i + 5]);
                        pp[i][3] = pack_bf16(e[8 * i + 6], e[8 * i + 7]);
                    }
                };
                auto store_o = [&](float ls0, float ls1, int head, bool last) {
                    float s0 = ls0 + __shfl_xor_sync(0xffffffffu, ls0, 1); s0 += __shfl_xor_sync(0xffffffffu, s0, 2);
                    float s1 = ls1 + __shfl_xor_sync(0xffffffffu, ls1, 1); s1 += __shfl_xor_sync(0xffffffffu, s1, 2);
                    const float i0 = 1.f / s0, i1 = 1.f / s1;
                    if (tid == 0) {
                        tma_store_wait<0>();
                        if (last) {
                            mbar_arrive_cluster(bars + 8 * BD1A, 0);
                            mbar_arrive_cluster(bars + 8 * BD1A, 1);
                        }
                    }
                    bar_sync(1 + wg, 128);
#pragma unroll
                    for (int jj = 0; jj < 16; jj += 2) {
                        const int mi = lane >> 3;
                        const int row = warp * 16 + (mi & 1) * 8 + (lane & 7);
                        const int grp = jj + (mi >> 1);
                        const uint32_t addr = mystage + (grp >> 3) * 8192 + row * 128 + (((grp & 7) ^ (row & 7)) << 4);
                        stmatrix_x4(addr, pack_bf16(o[4 * jj] * i0, o[4 * jj + 1] * i0), pack_bf16(o[4 * jj + 2] * i1, o[4 * jj + 3] * i1),
                                    pack_bf16(o[4 * jj + 4] * i0, o[4 * jj + 5] * i0), pack_bf16(o[4 * jj + 6] * i1, o[4 * jj + 7] * i1));
                    }
                    fence_proxy_async();
                    bar_sync(1 + wg, 128);
                    if (tid == 0) {
                        tma_store_2d(&tm.o_st, mystage, head * 128, m0 + wg * 64);
                        tma_store_2d(&tm.o_st, mystage + 8192, head * 128 + 64, m0 + wg * 64);
                        tma_store_commit();
                        if (last) {
                            tma_store_wait<0>();
                            mbar_arrive_cluster(bars + 8 * BD1, 0);
                            mbar_arrive_cluster(bars + 8 * BD1, 1);
                            flag_signal_relaxed(F_O + mt * 4 + (j >> 1));
                        }
                    }
                };

                l0 = 0.f; l1 = 0.f;
                {
                    turn_wait();
                    uint32_t stk = issue_s();
                    turn_pass();
                    wgmma_wait<0>();
                    fence_regs(s);
                    release(stk);
                    softmax(true);
                    convert_p();
                }
#pragma unroll 1
                for (int t = 1; t < 8; t++) {
                    const bool first = (t == 4);
                    if (t == 4) {
#pragma unroll
                        for (int i = 0; i < 8; i++) {
                            asm volatile("ld.shared.v4.b32 {%0, %1, %2, %3}, [%4];" : "=r"(q[i][0]), "=r"(q[i][1]), "=r"(q[i][2]), "=r"(q[i][3])
                                         : "r"(mystage + (i * 128 + tid) * 16) : "memory");
                        }
                    }
                    turn_wait();
                    uint32_t stk = issue_s();
                    uint32_t stv = issue_pv(t == 1 || t == 5);
                    turn_pass();
                    wgmma_wait<1>();
                    fence_regs(s);
                    release(stk);
                    softmax(first);
                    asm volatile("{\n.reg .pred p;\nsetp.lt.f32 p, %0, 0fBF800000;\n@p st.shared.f32 [%1], %0;\n}\n" ::"f"(l0 + l1), "r"(mystage) : "memory");
                    wgmma_wait<0>();
                    fence_regs(o);
                    release(stv);
                    if (first) {
                        store_o(lo0, lo1, head0, false);
                    } else {
#pragma unroll
                        for (int jj = 0; jj < 16; jj++) {
                            o[4 * jj] *= a0; o[4 * jj + 1] *= a0; o[4 * jj + 2] *= a1; o[4 * jj + 3] *= a1;
                        }
                    }
                    convert_p();
                }
                {
                    turn_wait();
                    uint32_t stv = issue_pv(false);
                    turn_pass();
                    wgmma_wait<0>();
                    fence_regs(o);
                    release(stv);
                    store_o(l0, l1, head0 + 1, hp == 1);
                }
            }
        }
        TS(0, 4);
        if (live || cw == 0) {
            const int kq = j >> 1, n0 = (j & 1) * 320;
            float acc0[96], acc1[64];
#pragma unroll
            for (int i = 0; i < 96; i++) acc0[i] = 0.f;
#pragma unroll
            for (int i = 0; i < 64; i++) acc1[i] = 0.f;
            uint32_t st = 0, ph = 0, prev = 0;
            for (int i = 0; i < (live ? 16 : 0); i++) {
                mbar_wait(bars + 8 * (B2F + st), ph);
                if (i == 0) TS(0, 5);
                const uint32_t buf = base + st * P2_STAGE;
                wgmma_fence();
#pragma unroll
                for (int k = 0; k < 4; k++) {
                    uint64_t da = make_desc(buf + wg * 8192 + k * 32, 16, 1024, 1);
                    wgmma_ss_n192_t1(acc0, da, make_desc(buf + 16384 + k * 2048, 8192, 1024, 1), 1);
                    wgmma_ss_n128_t1(acc1, da, make_desc(buf + 16384 + 3 * 8192 + k * 2048, 8192, 1024, 1), 1);
                }
                wgmma_commit();
                if (i > 0) { wgmma_wait<1>(); arrive_both(bars + 8 * (B2E + prev)); }
                prev = st;
                if (++st == 4) { st = 0; ph ^= 1; }
            }
            wgmma_wait<0>();
            fence_regs(acc0); fence_regs(acc1);
            TS(0, 6);
            if (live) bar_sync(5, 256);
            const uint32_t stg = base + wg * 40960;
            const int mi = lane >> 3;
            const int row = warp * 16 + (mi & 1) * 8 + (lane & 7);
#pragma unroll
            for (int jj = 0; jj < 24; jj += 2) {
                const int grp = jj + (mi >> 1);
                if (live) stmatrix_x4(stg + (grp >> 3) * 8192 + row * 128 + (((grp & 7) ^ (row & 7)) << 4),
                            pack_bf16(acc0[4 * jj], acc0[4 * jj + 1]), pack_bf16(acc0[4 * jj + 2], acc0[4 * jj + 3]),
                            pack_bf16(acc0[4 * jj + 4], acc0[4 * jj + 5]), pack_bf16(acc0[4 * jj + 6], acc0[4 * jj + 7]));
            }
#pragma unroll
            for (int jj = 0; jj < 16; jj += 2) {
                const int grp = jj + (mi >> 1);
                if (live) stmatrix_x4(stg + (3 + (grp >> 3)) * 8192 + row * 128 + (((grp & 7) ^ (row & 7)) << 4),
                            pack_bf16(acc1[4 * jj], acc1[4 * jj + 1]), pack_bf16(acc1[4 * jj + 2], acc1[4 * jj + 3]),
                            pack_bf16(acc1[4 * jj + 4], acc1[4 * jj + 5]), pack_bf16(acc1[4 * jj + 6], acc1[4 * jj + 7]));
            }
            TS(4, 1);
            fence_proxy_async();
            if (live) bar_sync(1 + wg, 128);
            if (live && tid == 0) {
#pragma unroll
                for (int c = 0; c < 5; c++) tma_store_2d(&tm.part_st, stg + c * 8192, n0 + c * 64, kq * S_LEN + m0 + wg * 64);
                tma_store_commit();
                TS(4, 3);
                tma_store_wait<0>();
                TS(4, 4);
                mbar_arrive_cluster(bars + 8 * BD2, 0);
                mbar_arrive_cluster(bars + 8 * BD2, 1);
                flag_signal_relaxed(F_P + mt);
            }
        }
        TS(0, 7);
        if (live || cw == 1) {
            uint2 xr[2][5];
#pragma unroll
            for (int rr = 0; rr < 2; rr++)
#pragma unroll
                for (int i = 0; i < 5; i++)
                    xr[rr][i] = live ? __ldg(reinterpret_cast<const uint2*>(x + (size_t)(m0 + j * 16 + cw * 2 + rr) * D_MODEL + (lane + 32 * i) * 4)) : make_uint2(0, 0);
            if (live) {
                if (threadIdx.x == 0) { flag_wait(F_MODALL, (epoch + 1) * 80); flag_wait(F_P + mt, (epoch + 1) * 16); }
                bar_sync(5, 256);
            }
            TS(0, 8);
            uint2 pr[2][4][5];
            float4 gv[5];
#pragma unroll
            for (int rr = 0; rr < 2; rr++)
#pragma unroll
                for (int s = 0; s < 4; s++)
#pragma unroll
                    for (int i = 0; i < 5; i++)
                        pr[rr][s][i] = live ? ldcg_u2(g_part + ((size_t)s * S_LEN + m0 + j * 16 + cw * 2 + rr) * D_MODEL + (lane + 32 * i) * 4) : make_uint2(0, 0);
#pragma unroll
            for (int i = 0; i < 5; i++) gv[i] = live ? __ldcg(reinterpret_cast<const float4*>(g_mod + 2 * D_MODEL + (lane + 32 * i) * 4)) : make_float4(0.f, 0.f, 0.f, 0.f);
#pragma unroll
            for (int rr = 0; rr < 2; rr++) {
#pragma unroll
                for (int i = 0; i < 5; i++) {
                    float a0 = (bf16lo(pr[rr][0][i].x) + bf16lo(pr[rr][1][i].x)) + (bf16lo(pr[rr][2][i].x) + bf16lo(pr[rr][3][i].x));
                    float a1 = (bf16hi(pr[rr][0][i].x) + bf16hi(pr[rr][1][i].x)) + (bf16hi(pr[rr][2][i].x) + bf16hi(pr[rr][3][i].x));
                    float a2 = (bf16lo(pr[rr][0][i].y) + bf16lo(pr[rr][1][i].y)) + (bf16lo(pr[rr][2][i].y) + bf16lo(pr[rr][3][i].y));
                    float a3 = (bf16hi(pr[rr][0][i].y) + bf16hi(pr[rr][1][i].y)) + (bf16hi(pr[rr][2][i].y) + bf16hi(pr[rr][3][i].y));
                    xr[rr][i].x = pack_bf16(bf16lo(xr[rr][i].x) + gv[i].x * a0, bf16hi(xr[rr][i].x) + gv[i].y * a1);
                    xr[rr][i].y = pack_bf16(bf16lo(xr[rr][i].y) + gv[i].z * a2, bf16hi(xr[rr][i].y) + gv[i].w * a3);
                    if (live) *reinterpret_cast<uint2*>(g_x1 + (size_t)(m0 + j * 16 + cw * 2 + rr) * D_MODEL + (lane + 32 * i) * 4) = xr[rr][i];
                }
            }
            if (live) {
                ln_rows(xr, g_mod + 3 * D_MODEL, g_mod + 4 * D_MODEL, g_h2 + (size_t)(m0 + j * 16 + cw * 2) * D_MODEL, lane);
                bar_sync(5, 256);
                if (threadIdx.x == 0) flag_signal(F_H2 + mt);
            }
        }
        TS(0, 9);
        {
            const int f0 = j * 216;
            uint32_t st = 0, ph = 0, prev = 0;
            if (live || cw == 2) {
                float acc[128];
#pragma unroll
                for (int i = 0; i < 128; i++) acc[i] = 0.f;
                if (live && wg == 1) bar_sync(6, 256);
                for (int i = 0; i < (live ? 10 : 0); i++) {
                    mbar_wait(bars + 8 * (B4F + st), ph);
                    if (i == 0) TS(0, 10);
                    const uint32_t buf = base + st * P4_STAGE;
                    wgmma_fence();
#pragma unroll
                    for (int k = 0; k < 4; k++) {
                        uint64_t da = make_desc(buf + wg * 8192 + k * 32, 16, 1024, 1);
                        uint64_t db = make_desc(buf + 16384 + k * 2048, 8192, 1024, 1);
                        wgmma_ss_n256_t1(acc, da, db, 1);
                    }
                    wgmma_commit();
                    if (i == 1 && wg == 0) bar_arrive(6, 256);
                    if (i > 0) { wgmma_wait<1>(); arrive_both(bars + 8 * (B4E + prev)); }
                    prev = st;
                    if (++st == 4) { st = 0; ph ^= 1; }
                }
                wgmma_wait<0>();
                if (live) arrive_both(bars + 8 * (B4E + prev));
                fence_regs(acc);
                TS(2, 0);
#pragma unroll
                for (int jj = 0; jj < 16; jj += 2) {
                    const int mi = lane >> 3;
                    const int row = warp * 16 + (mi & 1) * 8 + (lane & 7);
                    const int grp = jj + (mi >> 1);
                    const uint32_t addr = mystage + (grp >> 3) * 8192 + row * 128 + (((grp & 7) ^ (row & 7)) << 4);
                    if (live) stmatrix_x4(addr, pack_bf16(silu_mul(acc[4 * jj], acc[64 + 4 * jj]), silu_mul(acc[4 * jj + 1], acc[64 + 4 * jj + 1])),
                                pack_bf16(silu_mul(acc[4 * jj + 2], acc[64 + 4 * jj + 2]), silu_mul(acc[4 * jj + 3], acc[64 + 4 * jj + 3])),
                                pack_bf16(silu_mul(acc[4 * jj + 4], acc[64 + 4 * jj + 4]), silu_mul(acc[4 * jj + 5], acc[64 + 4 * jj + 5])),
                                pack_bf16(silu_mul(acc[4 * jj + 6], acc[64 + 4 * jj + 6]), silu_mul(acc[4 * jj + 7], acc[64 + 4 * jj + 7])));
                }
                fence_proxy_async();
                if (live) bar_sync(1 + wg, 128);
                if (live && tid == 0) {
                    tma_store_2d(&tm.act_st64, mystage, f0, m0 + wg * 64);
                    tma_store_2d(&tm.act_st64, mystage + 8192, f0 + 64, m0 + wg * 64);
                    tma_store_commit();
                }
                TS(2, 2);
            }
            if (live || cw == 3) {
                float acc[92];
#pragma unroll
                for (int i = 0; i < 92; i++) acc[i] = 0.f;
                for (int i = 0; i < (live ? 10 : 0); i++) {
                    mbar_wait(bars + 8 * (B4F + st), ph);
                    const uint32_t buf = base + st * P4_STAGE;
                    wgmma_fence();
#pragma unroll
                    for (int k = 0; k < 4; k++) {
                        uint64_t da = make_desc(buf + wg * 8192 + k * 32, 16, 1024, 1);
                        uint64_t db = make_desc(buf + 16384 + k * 1024, 4096, 512, 2);
                        wgmma_ss_n184_t1(acc, da, db, 1);
                    }
                    wgmma_commit();
                    if (i == 3 && tid == 0) { tma_store_wait<0>(); flag_signal_relaxed(F_A1 + mt); }
                    if (i > 0) { wgmma_wait<1>(); arrive_both(bars + 8 * (B4E + prev)); }
                    prev = st;
                    if (++st == 4) { st = 0; ph ^= 1; }
                }
                wgmma_wait<0>();
                if (live) arrive_both(bars + 8 * BD4);
                fence_regs(acc);
                TS(0, 11);
                if (live) bar_sync(1 + wg, 128);
                TS(2, 3);
#pragma unroll
                for (int jj = 0; jj < 8; jj += 2) {
                    const int mi = lane >> 3;
                    const int row = warp * 16 + (mi & 1) * 8 + (lane & 7);
                    const int grp = jj + (mi >> 1);
                    const uint32_t addr = mystage + row * 128 + ((grp ^ (row & 7)) << 4);
                    if (live) stmatrix_x4(addr, pack_bf16(silu_mul(acc[4 * jj], acc[48 + 4 * jj]), silu_mul(acc[4 * jj + 1], acc[48 + 4 * jj + 1])),
                                pack_bf16(silu_mul(acc[4 * jj + 2], acc[48 + 4 * jj + 2]), silu_mul(acc[4 * jj + 3], acc[48 + 4 * jj + 3])),
                                pack_bf16(silu_mul(acc[4 * jj + 4], acc[48 + 4 * jj + 4]), silu_mul(acc[4 * jj + 5], acc[48 + 4 * jj + 5])),
                                pack_bf16(silu_mul(acc[4 * jj + 6], acc[48 + 4 * jj + 6]), silu_mul(acc[4 * jj + 7], acc[48 + 4 * jj + 7])));
                }
                {
                    const int mi = lane >> 3;
                    const int row = warp * 16 + (mi & 1) * 8 + (lane & 7);
                    const uint32_t addr = mystage + 8192 + row * 48 + (mi >> 1) * 16;
                    if (live) stmatrix_x4(addr, pack_bf16(silu_mul(acc[32], acc[80]), silu_mul(acc[33], acc[81])),
                                pack_bf16(silu_mul(acc[34], acc[82]), silu_mul(acc[35], acc[83])),
                                pack_bf16(silu_mul(acc[36], acc[84]), silu_mul(acc[37], acc[85])),
                                pack_bf16(silu_mul(acc[38], acc[86]), silu_mul(acc[39], acc[87])));
                    const uint32_t addr2 = mystage + 8192 + (warp * 16 + ((lane >> 3) & 1) * 8 + (lane & 7)) * 48 + 32;
                    if (live) asm volatile("stmatrix.sync.aligned.m8n8.x2.shared.b16 [%0], {%1, %2};" ::"r"(addr2),
                                 "r"(pack_bf16(silu_mul(acc[40], acc[88]), silu_mul(acc[41], acc[89]))),
                                 "r"(pack_bf16(silu_mul(acc[42], acc[90]), silu_mul(acc[43], acc[91]))) : "memory");
                }
                fence_proxy_async();
                if (live) bar_sync(1 + wg, 128);
                if (live && tid == 0) {
                    tma_store_2d(&tm.act_st64, mystage, f0 + 128, m0 + wg * 64);
                    tma_store_2d(&tm.act_st24, mystage + 8192, f0 + 192, m0 + wg * 64);
                    tma_store_commit();
                    TS(2, 5);
                    tma_store_wait<0>();
                    TS(2, 6);
                    mbar_arrive_cluster(bars + 8 * BD4B, 0);
                    mbar_arrive_cluster(bars + 8 * BD4B, 1);
                    TS(2, 7);
                    flag_signal_relaxed(F_A + mt);
                    TS(2, 8);
                }
            }
        }
        TS(0, 12);
        if (live || cw == 4) {
            const int m5 = (p * 2 + (j >> 2)) * 128, n0 = (j & 3) * 160;
            const int nkb = rank == 0 ? 14 : 13;
            float accA[64], accB[16];
#pragma unroll
            for (int i = 0; i < 64; i++) accA[i] = 0.f;
#pragma unroll
            for (int i = 0; i < 16; i++) accB[i] = 0.f;
            uint32_t st = 0, ph = 0, prev = 0;
            const int cbase = n0 + (int)rank * 80;
            for (int i = 0; i < (live ? nkb : 0); i++) {
                mbar_wait(bars + 8 * (B5F + st), ph);
                if (i == 0) TS(0, 13);
                const uint32_t buf = base + st * P5_STAGE;
                wgmma_fence();
#pragma unroll
                for (int k = 0; k < 4; k++) {
                    uint64_t da = make_desc(buf + wg * 8192 + k * 32, 16, 1024, 1);
                    wgmma_ss_n128_t1(accA, da, make_desc(buf + 16384 + k * 2048, 8192, 1024, 1), 1);
                    wgmma_ss_n32_t1(accB, da, make_desc(buf + 32768 + k * 1024, 4096, 512, 2), 1);
                }
                wgmma_commit();
                if (i > 0) {
                    wgmma_wait<1>();
                    if (tid == 0) mbar_arrive(bars + 8 * (B5E + prev));
                }
                prev = st;
                if (++st == 5) { st = 0; ph ^= 1; }
            }
            uint4 xv[5];
            float2 gbv[10];
#pragma unroll
            for (int it = 0; it < 5; it++) {
                const int idx = it * 256 + (int)threadIdx.x;
                const int row = idx / 10, ch = idx - row * 10;
                xv[it] = live ? __ldcg(reinterpret_cast<const uint4*>(g_x1 + (size_t)(m5 + row) * D_MODEL + cbase + ch * 8)) : make_uint4(0, 0, 0, 0);
            }
#pragma unroll
            for (int jj = 0; jj < 10; jj++) gbv[jj] = live ? __ldcg(reinterpret_cast<const float2*>(g_mod + 5 * D_MODEL + cbase + jj * 8 + (lane & 3) * 2)) : make_float2(0.f, 0.f);
            wgmma_wait<0>();
            fence_regs(accA); fence_regs(accB);
            float acc[80];
#pragma unroll
            for (int i = 0; i < 64; i++) acc[i] = accA[i];
#pragma unroll
            for (int i = 0; i < 16; i++) acc[64 + i] = accB[i];
            TS(0, 14);
            constexpr uint32_t XBUF = 5 * P5_STAGE;
            if (live) mbar_wait(bars + 8 * BD4B, 0);
            TS(3, 0);
            {
                const uint32_t dst = mapa(base + XBUF, rank ^ 1) + wg * 20480 + tid * 16;
                const uint32_t rbar = mapa(bars + 8 * BX, rank ^ 1);
                if (rank == 0) {
#pragma unroll
                    for (int i = 0; i < 10; i++)
                        if (live) asm volatile("st.async.shared::cluster.mbarrier::complete_tx::bytes.v4.f32 [%0], {%1, %2, %3, %4}, [%5];" ::"r"(dst + i * 2048),
                                     "f"(acc[40 + 4 * i]), "f"(acc[40 + 4 * i + 1]), "f"(acc[40 + 4 * i + 2]), "f"(acc[40 + 4 * i + 3]), "r"(rbar) : "memory");
                } else {
#pragma unroll
                    for (int i = 0; i < 10; i++)
                        if (live) asm volatile("st.async.shared::cluster.mbarrier::complete_tx::bytes.v4.f32 [%0], {%1, %2, %3, %4}, [%5];" ::"r"(dst + i * 2048),
                                     "f"(acc[4 * i]), "f"(acc[4 * i + 1]), "f"(acc[4 * i + 2]), "f"(acc[4 * i + 3]), "r"(rbar) : "memory");
                }
            }
            TS(3, 1);
            if (live) mbar_wait(bars + 8 * BX, 0);
            TS(3, 2);
            {
                if (live) bar_sync(5, 256);
                const uint32_t tile = base;
                TS(3, 3);
#pragma unroll
                for (int jj = 0; jj < 10; jj += 2) {
                    float4 o0, o1;
                    asm volatile("ld.shared.v4.f32 {%0, %1, %2, %3}, [%4];" : "=f"(o0.x), "=f"(o0.y), "=f"(o0.z), "=f"(o0.w) : "r"(base + XBUF + wg * 20480 + tid * 16 + jj * 2048));
                    asm volatile("ld.shared.v4.f32 {%0, %1, %2, %3}, [%4];" : "=f"(o1.x), "=f"(o1.y), "=f"(o1.z), "=f"(o1.w) : "r"(base + XBUF + wg * 20480 + tid * 16 + (jj + 1) * 2048));
                    const float2 g0 = gbv[jj], g1 = gbv[jj + 1];
                    float a[8];
#pragma unroll
                    for (int ee = 0; ee < 8; ee++) a[ee] = rank == 0 ? acc[4 * jj + ee] : acc[40 + 4 * jj + ee];
                    const int mi = lane >> 3;
                    const int row = wg * 64 + warp * 16 + (mi & 1) * 8 + (lane & 7);
                    const uint32_t addr = tile + row * 176 + (jj + (mi >> 1)) * 16;
                    if (live) stmatrix_x4(addr, pack_bf16(g0.x * bf16_round(a[0] + o0.x), g0.y * bf16_round(a[1] + o0.y)),
                                pack_bf16(g0.x * bf16_round(a[2] + o0.z), g0.y * bf16_round(a[3] + o0.w)),
                                pack_bf16(g1.x * bf16_round(a[4] + o1.x), g1.y * bf16_round(a[5] + o1.y)),
                                pack_bf16(g1.x * bf16_round(a[6] + o1.z), g1.y * bf16_round(a[7] + o1.w)));
                }
                if (live) bar_sync(5, 256);
#pragma unroll
                for (int it = 0; it < 5; it++) {
                    const int idx = it * 256 + (int)threadIdx.x;
                    const int row = idx / 10, ch = idx - row * 10;
                    uint4 tv;
                    asm volatile("ld.shared.v4.b32 {%0, %1, %2, %3}, [%4];" : "=r"(tv.x), "=r"(tv.y), "=r"(tv.z), "=r"(tv.w) : "r"(tile + row * 176 + ch * 16));
                    uint4 r;
                    r.x = pack_bf16(bf16lo(xv[it].x) + bf16lo(tv.x), bf16hi(xv[it].x) + bf16hi(tv.x));
                    r.y = pack_bf16(bf16lo(xv[it].y) + bf16lo(tv.y), bf16hi(xv[it].y) + bf16hi(tv.y));
                    r.z = pack_bf16(bf16lo(xv[it].z) + bf16lo(tv.z), bf16hi(xv[it].z) + bf16hi(tv.z));
                    r.w = pack_bf16(bf16lo(xv[it].w) + bf16lo(tv.w), bf16hi(xv[it].w) + bf16hi(tv.w));
                    if (live) *reinterpret_cast<uint4*>(out + (size_t)(m5 + row) * D_MODEL + cbase + ch * 8) = r;
                }
            }
            TS(0, 15);
            if (live && threadIdx.x == 0) {
                const unsigned old = atomicAdd(&g_exit, 1u);
                if (old == (epoch + 1) * 128u - 1u) {
                    asm volatile("st.volatile.global.u32 [%0], %1;" ::"l"(&g_epoch), "r"(epoch + 1) : "memory");
                }
            }
        }
        }
        asm volatile("barrier.cluster.arrive.relaxed.aligned;\n barrier.cluster.wait.aligned;" ::: "memory");
    }
}

typedef CUresult (*PFN_encodeTiled)(CUtensorMap*, CUtensorMapDataType, cuuint32_t, void*, const cuuint64_t*, const cuuint64_t*,
                                    const cuuint32_t*, const cuuint32_t*, CUtensorMapInterleave, CUtensorMapSwizzle,
                                    CUtensorMapL2promotion, CUtensorMapFloatOOBfill);

static PFN_encodeTiled get_encode() {
    static PFN_encodeTiled fn = nullptr;
    if (!fn) {
        void* p = nullptr;
        cudaDriverEntryPointQueryResult qr;
        cudaGetDriverEntryPoint("cuTensorMapEncodeTiled", &p, cudaEnableDefault, &qr);
        fn = (PFN_encodeTiled)p;
    }
    return fn;
}

static CUtensorMap make_map(const void* ptr, uint64_t rows, uint64_t cols, uint32_t box_rows, uint32_t box_cols, CUtensorMapSwizzle swz) {
    CUtensorMap m;
    cuuint64_t dims[2] = {cols, rows};
    cuuint64_t strides[1] = {cols * 2};
    cuuint32_t box[2] = {box_cols, box_rows};
    cuuint32_t es[2] = {1, 1};
    get_encode()(&m, CU_TENSOR_MAP_DATA_TYPE_BFLOAT16, 2, const_cast<void*>(ptr), dims, strides, box, es, CU_TENSOR_MAP_INTERLEAVE_NONE,
                 swz, CU_TENSOR_MAP_L2_PROMOTION_L2_256B, CU_TENSOR_MAP_FLOAT_OOB_FILL_NONE);
    return m;
}

extern "C" void kernel_launch(void* const* d_in, const int* in_sizes, int n_in, void* d_out, int out_size) {
    (void)in_sizes; (void)n_in; (void)out_size;
    const __nv_bfloat16* x = (const __nv_bfloat16*)d_in[0];
    const __nv_bfloat16* kc = (const __nv_bfloat16*)d_in[1];
    const __nv_bfloat16* vc = (const __nv_bfloat16*)d_in[2];
    const __nv_bfloat16* wq = (const __nv_bfloat16*)d_in[3];
    const __nv_bfloat16* wo = (const __nv_bfloat16*)d_in[4];
    const __nv_bfloat16* wg = (const __nv_bfloat16*)d_in[6];
    const __nv_bfloat16* wu = (const __nv_bfloat16*)d_in[7];
    const __nv_bfloat16* wd = (const __nv_bfloat16*)d_in[8];
    const __nv_bfloat16* c = (const __nv_bfloat16*)d_in[9];
    const __nv_bfloat16* wmod = (const __nv_bfloat16*)d_in[10];
    __nv_bfloat16* out = (__nv_bfloat16*)d_out;

    static bool init = false;
    static void *p_h, *p_o, *p_x1, *p_h2, *p_act, *p_part;
    if (!init) {
        cudaFuncSetAttribute(mega_kernel, cudaFuncAttributeMaxDynamicSharedMemorySize, SM_TOTAL);
        cudaGetSymbolAddress(&p_h, g_h);
        cudaGetSymbolAddress(&p_o, g_o);
        cudaGetSymbolAddress(&p_x1, g_x1);
        cudaGetSymbolAddress(&p_h2, g_h2);
        cudaGetSymbolAddress(&p_act, g_act);
        cudaGetSymbolAddress(&p_part, g_part);
        init = true;
    }
    const CUtensorMapSwizzle S128 = CU_TENSOR_MAP_SWIZZLE_128B, S64 = CU_TENSOR_MAP_SWIZZLE_64B;
    Maps tm;
    tm.h = make_map(p_h, S_LEN, D_MODEL, 128, 64, S128);
    tm.wq = make_map(wq, D_MODEL, N_HEADS * D_HEAD, 64, 64, S128);
    tm.k = make_map(kc, N_HEADS * S_KV, D_HEAD, 128, 64, S128);
    tm.v = make_map(vc, N_HEADS * S_KV, D_HEAD, 128, 64, S128);
    tm.o_st = make_map(p_o, S_LEN, N_HEADS * D_HEAD, 64, 64, S128);
    tm.o_a = make_map(p_o, S_LEN, N_HEADS * D_HEAD, 128, 64, S128);
    tm.wo = make_map(wo, N_HEADS * D_HEAD, D_MODEL, 64, 64, S128);
    tm.part_st = make_map(p_part, 4 * S_LEN, D_MODEL, 64, 64, S128);
    tm.h2 = make_map(p_h2, S_LEN, D_MODEL, 128, 64, S128);
    tm.g128 = make_map(wg, D_MODEL, D_FF, 64, 64, S128);
    tm.u128 = make_map(wu, D_MODEL, D_FF, 64, 64, S128);
    tm.g64 = make_map(wg, D_MODEL, D_FF, 64, 32, S64);
    tm.u64 = make_map(wu, D_MODEL, D_FF, 64, 32, S64);
    tm.act_st64 = make_map(p_act, S_LEN, D_FF, 64, 64, S128);
    tm.act_st24 = make_map(p_act, S_LEN, D_FF, 64, 24, CU_TENSOR_MAP_SWIZZLE_NONE);
    tm.act_a = make_map(p_act, S_LEN, D_FF, 128, 64, S128);
    tm.wd = make_map(wd, D_FF, D_MODEL, 64, 64, S128);
    tm.wd32 = make_map(wd, D_FF, D_MODEL, 64, 32, S64);

    cudaLaunchConfig_t cfg = {};
    cfg.gridDim = dim3(128);
    cfg.blockDim = dim3(384);
    cfg.dynamicSmemBytes = SM_TOTAL;
    cfg.stream = cudaStreamPerThread;
    cfg.attrs = nullptr;
    cfg.numAttrs = 0;
    cudaLaunchKernelEx(&cfg, mega_kernel, tm, x, c, wmod, out, (const void*)wo, (const void*)wg, (const void*)wu, (const void*)wd);
}
```

```cpp
#include <cuda_runtime.h>
#include <cuda_bf16.h>
#include <cuda.h>
#include <stdint.h>

__device__ __forceinline__ uint32_t smem_u32(const void* p) { return (uint32_t)__cvta_generic_to_shared(p); }

__device__ __forceinline__ void mbar_init(uint32_t bar, uint32_t count) {
    asm volatile("mbarrier.init.shared::cta.b64 [%0], %1;" ::"r"(bar), "r"(count) : "memory");
}
__device__ __forceinline__ void mbar_expect_tx(uint32_t bar, uint32_t bytes) {
    asm volatile("mbarrier.arrive.expect_tx.shared::cta.b64 _, [%0], %1;" ::"r"(bar), "r"(bytes) : "memory");
}
__device__ __forceinline__ void mbar_arrive(uint32_t bar) {
    asm volatile("mbarrier.arrive.shared::cta.b64 _, [%0];" ::"r"(bar) : "memory");
}
__device__ __forceinline__ void mbar_arrive_cluster(uint32_t bar, uint32_t cta) {
    asm volatile(
        "{\n.reg .b32 ra;\n"
        "mapa.shared::cluster.u32 ra, %0, %1;\n"
        "mbarrier.arrive.shared::cluster.b64 _, [ra];\n}\n" ::"r"(bar), "r"(cta)
        : "memory");
}
__device__ __forceinline__ bool mbar_try_wait(uint32_t bar, uint32_t parity) {
    uint32_t ok;
    asm volatile(
        "{\n.reg .pred p;\n"
        "mbarrier.try_wait.parity.shared::cta.b64 p, [%1], %2;\n"
        "selp.u32 %0, 1, 0, p;\n}\n"
        : "=r"(ok)
        : "r"(bar), "r"(parity)
        : "memory");
    return ok != 0;
}
__device__ __forceinline__ bool mbar_try_wait_cluster(uint32_t bar, uint32_t parity) {
    uint32_t ok;
    asm volatile(
        "{\n.reg .pred p;\n"
        "mbarrier.try_wait.parity.shared::cta.b64 p, [%1], %2;\n"
        "selp.u32 %0, 1, 0, p;\n}\n"
        : "=r"(ok)
        : "r"(bar), "r"(parity)
        : "memory");
    return ok != 0;
}
__device__ volatile int g_abort = 0;
__device__ __forceinline__ void mbar_wait(uint32_t bar, uint32_t parity) {
    asm volatile(
        "{\n.reg .pred p;\n.reg .u32 n;\n"
        "mov.u32 n, 0;\n"
        "WAIT_LOOP:\n"
        "mbarrier.try_wait.parity.shared::cta.b64 p, [%0], %1;\n"
        "@p bra WAIT_DONE;\n"
        "add.u32 n, n, 1;\n"
        "setp.lt.u32 p, n, 16777216;\n"
        "@p bra WAIT_LOOP;\n"
        "WAIT_DONE:\n}\n" ::"r"(bar), "r"(parity) : "memory");
}
__device__ __forceinline__ void mbar_wait_cluster(uint32_t bar, uint32_t parity) { mbar_wait(bar, parity); }
__device__ __forceinline__ void fence_mbar_init() { asm volatile("fence.mbarrier_init.release.cluster;" ::: "memory"); }
__device__ __forceinline__ void fence_proxy_async() { asm volatile("fence.proxy.async.shared::cta;" ::: "memory"); }
__device__ __forceinline__ void fence_proxy_async_all() { asm volatile("fence.proxy.async;" ::: "memory"); }
__device__ __forceinline__ void cluster_arrive() { asm volatile("barrier.cluster.arrive.release.aligned;" ::: "memory"); }
__device__ __forceinline__ void cluster_wait() { asm volatile("barrier.cluster.wait.acquire.aligned;" ::: "memory"); }
__device__ __forceinline__ void cluster_sync() { cluster_arrive(); cluster_wait(); }
__device__ __forceinline__ uint32_t cluster_ctarank() {
    uint32_t r;
    asm volatile("mov.u32 %0, %%cluster_ctarank;" : "=r"(r));
    return r;
}
__device__ __forceinline__ void bar_sync(int id, int n) { asm volatile("bar.sync %0, %1;" ::"r"(id), "r"(n) : "memory"); }
__device__ __forceinline__ void bar_arrive(int id, int n) { asm volatile("bar.arrive %0, %1;" ::"r"(id), "r"(n) : "memory"); }
__device__ __forceinline__ void pdl_wait() { asm volatile("griddepcontrol.wait;" ::: "memory"); }
__device__ __forceinline__ void pdl_launch() { asm volatile("griddepcontrol.launch_dependents;" ::: "memory"); }

__device__ __forceinline__ void tma_prefetch_desc(const CUtensorMap* m) {
    asm volatile("prefetch.tensormap [%0];" ::"l"(m) : "memory");
}
__device__ __forceinline__ void tma_load_2d(uint32_t dst, const CUtensorMap* m, int c0, int c1, uint32_t bar) {
    asm volatile(
        "cp.async.bulk.tensor.2d.shared::cluster.global.mbarrier::complete_tx::bytes [%0], [%1, {%3, %4}], [%2];"
        ::"r"(dst), "l"(m), "r"(bar), "r"(c0), "r"(c1)
        : "memory");
}
__device__ __forceinline__ void tma_load_2d_mc(uint32_t dst, const CUtensorMap* m, int c0, int c1, uint32_t bar, uint16_t mask) {
    asm volatile(
        "cp.async.bulk.tensor.2d.shared::cluster.global.mbarrier::complete_tx::bytes.multicast::cluster [%0], [%1, {%3, %4}], [%2], %5;"
        ::"r"(dst), "l"(m), "r"(bar), "r"(c0), "r"(c1), "h"(mask)
        : "memory");
}
__device__ __forceinline__ void tma_store_2d(const CUtensorMap* m, uint32_t src, int c0, int c1) {
    asm volatile("cp.async.bulk.tensor.2d.global.shared::cta.bulk_group [%0, {%2, %3}], [%1];"
                 ::"l"(m), "r"(src), "r"(c0), "r"(c1)
                 : "memory");
}
__device__ __forceinline__ void tma_store_commit() { asm volatile("cp.async.bulk.commit_group;" ::: "memory"); }
template <int N> __device__ __forceinline__ void tma_store_wait_read() {
    asm volatile("cp.async.bulk.wait_group.read %0;" ::"n"(N) : "memory");
}
template <int N> __device__ __forceinline__ void tma_store_wait() {
    asm volatile("cp.async.bulk.wait_group %0;" ::"n"(N) : "memory");
}

__device__ __forceinline__ void wgmma_fence() { asm volatile("wgmma.fence.sync.aligned;" ::: "memory"); }
__device__ __forceinline__ void wgmma_commit() { asm volatile("wgmma.commit_group.sync.aligned;" ::: "memory"); }
template <int N> __device__ __forceinline__ void wgmma_wait() {
    asm volatile("wgmma.wait_group.sync.aligned %0;" ::"n"(N) : "memory");
}
template <int R> __device__ __forceinline__ void reg_alloc() { asm volatile("setmaxnreg.inc.sync.aligned.u32 %0;" ::"n"(R)); }
template <int R> __device__ __forceinline__ void reg_dealloc() { asm volatile("setmaxnreg.dec.sync.aligned.u32 %0;" ::"n"(R)); }

template <int N> __device__ __forceinline__ void fence_regs(float (&r)[N]) {
#pragma unroll
    for (int i = 0; i < N; i++) asm volatile("" : "+f"(r[i])::"memory");
}
template <int N> __device__ __forceinline__ void fence_regs_u(uint32_t (&r)[N][4]) {
#pragma unroll
    for (int i = 0; i < N; i++) {
#pragma unroll
        for (int j = 0; j < 4; j++) asm volatile("" : "+r"(r[i][j])::"memory");
    }
}

__device__ __forceinline__ uint64_t make_desc(uint32_t addr, uint32_t lbo_bytes, uint32_t sbo_bytes, uint32_t swz) {
    return (uint64_t)((addr & 0x3FFFF) >> 4) | ((uint64_t)(lbo_bytes >> 4) << 16) | ((uint64_t)(sbo_bytes >> 4) << 32) |
           ((uint64_t)swz << 62);
}

__device__ __forceinline__ uint32_t pack_bf16(float lo, float hi) {
    uint32_t r;
    asm("cvt.rn.bf16x2.f32 %0, %1, %2;" : "=r"(r) : "f"(hi), "f"(lo));
    return r;
}
__device__ __forceinline__ float bf16_round(float x) { return __bfloat162float(__float2bfloat16_rn(x)); }
__device__ __forceinline__ float bf16lo(uint32_t v) { return __uint_as_float(v << 16); }
__device__ __forceinline__ float bf16hi(uint32_t v) { return __uint_as_float(v & 0xffff0000u); }
__device__ __forceinline__ float ex2(float x) {
    float y;
    asm("ex2.approx.ftz.f32 %0, %1;" : "=f"(y) : "f"(x));
    return y;
}
__device__ __forceinline__ void stmatrix_x4(uint32_t addr, uint32_t r0, uint32_t r1, uint32_t r2, uint32_t r3) {
    asm volatile("stmatrix.sync.aligned.m8n8.x4.shared.b16 [%0], {%1, %2, %3, %4};" ::"r"(addr), "r"(r0), "r"(r1), "r"(r2), "r"(r3)
                 : "memory");
}
__device__ __forceinline__ uint32_t mapa(uint32_t addr, uint32_t cta) {
    uint32_t r;
    asm volatile("mapa.shared::cluster.u32 %0, %1, %2;" : "=r"(r) : "r"(addr), "r"(cta));
    return r;
}
__device__ __forceinline__ void st_cluster_v2(uint32_t addr, float a, float b) {
    asm volatile("st.shared::cluster.v2.f32 [%0], {%1, %2};" ::"r"(addr), "f"(a), "f"(b) : "memory");
}
__device__ __forceinline__ void wgmma_ss_n256_t1(float (&d)[128], uint64_t descA, uint64_t descB, int scaleD) {
    asm volatile("{\n.reg .pred p;\n"
        "setp.ne.b32 p, %130, 0;\n"
        "wgmma.mma_async.sync.aligned.m64n256k16.f32.bf16.bf16 "
        "{%0, %1, %2, %3, %4, %5, %6, %7, %8, %9, %10, %11, %12, %13, %14, %15, "
        "%16, %17, %18, %19, %20, %21, %22, %23, %24, %25, %26, %27, %28, %29, %30, %31, "
        "%32, %33, %34, %35, %36, %37, %38, %39, %40, %41, %42, %43, %44, %45, %46, %47, "
        "%48, %49, %50, %51, %52, %53, %54, %55, %56, %57, %58, %59, %60, %61, %62, %63, "
        "%64, %65, %66, %67, %68, %69, %70, %71, %72, %73, %74, %75, %76, %77, %78, %79, "
        "%80, %81, %82, %83, %84, %85, %86, %87, %88, %89, %90, %91, %92, %93, %94, %95, "
        "%96, %97, %98, %99, %100, %101, %102, %103, %104, %105, %106, %107, %108, %109, %110, %111, "
        "%112, %113, %114, %115, %116, %117, %118, %119, %120, %121, %122, %123, %124, %125, %126, %127}, "
        "%128, %129, p, 1, 1, 0, 1;\n}\n"
        :
          "+f"(d[0]), "+f"(d[1]), "+f"(d[2]), "+f"(d[3]), "+f"(d[4]), "+f"(d[5]), "+f"(d[6]), "+f"(d[7]),
          "+f"(d[8]), "+f"(d[9]), "+f"(d[10]), "+f"(d[11]), "+f"(d[12]), "+f"(d[13]), "+f"(d[14]), "+f"(d[15]),
          "+f"(d[16]), "+f"(d[17]), "+f"(d[18]), "+f"(d[19]), "+f"(d[20]), "+f"(d[21]), "+f"(d[22]), "+f"(d[23]),
          "+f"(d[24]), "+f"(d[25]), "+f"(d[26]), "+f"(d[27]), "+f"(d[28]), "+f"(d[29]), "+f"(d[30]), "+f"(d[31]),
          "+f"(d[32]), "+f"(d[33]), "+f"(d[34]), "+f"(d[35]), "+f"(d[36]), "+f"(d[37]), "+f"(d[38]), "+f"(d[39]),
          "+f"(d[40]), "+f"(d[41]), "+f"(d[42]), "+f"(d[43]), "+f"(d[44]), "+f"(d[45]), "+f"(d[46]), "+f"(d[47]),
          "+f"(d[48]), "+f"(d[49]), "+f"(d[50]), "+f"(d[51]), "+f"(d[52]), "+f"(d[53]), "+f"(d[54]), "+f"(d[55]),
          "+f"(d[56]), "+f"(d[57]), "+f"(d[58]), "+f"(d[59]), "+f"(d[60]), "+f"(d[61]), "+f"(d[62]), "+f"(d[63]),
          "+f"(d[64]), "+f"(d[65]), "+f"(d[66]), "+f"(d[67]), "+f"(d[68]), "+f"(d[69]), "+f"(d[70]), "+f"(d[71]),
          "+f"(d[72]), "+f"(d[73]), "+f"(d[74]), "+f"(d[75]), "+f"(d[76]), "+f"(d[77]), "+f"(d[78]), "+f"(d[79]),
          "+f"(d[80]), "+f"(d[81]), "+f"(d[82]), "+f"(d[83]), "+f"(d[84]), "+f"(d[85]), "+f"(d[86]), "+f"(d[87]),
          "+f"(d[88]), "+f"(d[89]), "+f"(d[90]), "+f"(d[91]), "+f"(d[92]), "+f"(d[93]), "+f"(d[94]), "+f"(d[95]),
          "+f"(d[96]), "+f"(d[97]), "+f"(d[98]), "+f"(d[99]), "+f"(d[100]), "+f"(d[101]), "+f"(d[102]), "+f"(d[103]),
          "+f"(d[104]), "+f"(d[105]), "+f"(d[106]), "+f"(d[107]), "+f"(d[108]), "+f"(d[109]), "+f"(d[110]), "+f"(d[111]),
          "+f"(d[112]), "+f"(d[113]), "+f"(d[114]), "+f"(d[115]), "+f"(d[116]), "+f"(d[117]), "+f"(d[118]), "+f"(d[119]),
          "+f"(d[120]), "+f"(d[121]), "+f"(d[122]), "+f"(d[123]), "+f"(d[124]), "+f"(d[125]), "+f"(d[126]), "+f"(d[127])
        : "l"(descA), "l"(descB), "r"(scaleD));
}

__device__ __forceinline__ void wgmma_rs_n128_t0(float (&d)[64], const uint32_t (&a)[4], uint64_t descB, int scaleD) {
    asm volatile("{\n.reg .pred p;\n"
        "setp.ne.b32 p, %69, 0;\n"
        "wgmma.mma_async.sync.aligned.m64n128k16.f32.bf16.bf16 "
        "{%0, %1, %2, %3, %4, %5, %6, %7, %8, %9, %10, %11, %12, %13, %14, %15, "
        "%16, %17, %18, %19, %20, %21, %22, %23, %24, %25, %26, %27, %28, %29, %30, %31, "
        "%32, %33, %34, %35, %36, %37, %38, %39, %40, %41, %42, %43, %44, %45, %46, %47, "
        "%48, %49, %50, %51, %52, %53, %54, %55, %56, %57, %58, %59, %60, %61, %62, %63}, "
        "{%64, %65, %66, %67}, %68, p, 1, 1, 0;\n}\n"
        :
          "+f"(d[0]), "+f"(d[1]), "+f"(d[2]), "+f"(d[3]), "+f"(d[4]), "+f"(d[5]), "+f"(d[6]), "+f"(d[7]),
          "+f"(d[8]), "+f"(d[9]), "+f"(d[10]), "+f"(d[11]), "+f"(d[12]), "+f"(d[13]), "+f"(d[14]), "+f"(d[15]),
          "+f"(d[16]), "+f"(d[17]), "+f"(d[18]), "+f"(d[19]), "+f"(d[20]), "+f"(d[21]), "+f"(d[22]), "+f"(d[23]),
          "+f"(d[24]), "+f"(d[25]), "+f"(d[26]), "+f"(d[27]), "+f"(d[28]), "+f"(d[29]), "+f"(d[30]), "+f"(d[31]),
          "+f"(d[32]), "+f"(d[33]), "+f"(d[34]), "+f"(d[35]), "+f"(d[36]), "+f"(d[37]), "+f"(d[38]), "+f"(d[39]),
          "+f"(d[40]), "+f"(d[41]), "+f"(d[42]), "+f"(d[43]), "+f"(d[44]), "+f"(d[45]), "+f"(d[46]), "+f"(d[47]),
          "+f"(d[48]), "+f"(d[49]), "+f"(d[50]), "+f"(d[51]), "+f"(d[52]), "+f"(d[53]), "+f"(d[54]), "+f"(d[55]),
          "+f"(d[56]), "+f"(d[57]), "+f"(d[58]), "+f"(d[59]), "+f"(d[60]), "+f"(d[61]), "+f"(d[62]), "+f"(d[63])
        : "r"(a[0]), "r"(a[1]), "r"(a[2]), "r"(a[3]), "l"(descB), "r"(scaleD));
}

__device__ __forceinline__ void wgmma_rs_n128_t0_z(float (&d)[64], const uint32_t (&a)[4], uint64_t descB) {
    asm volatile("{\n.reg .pred p;\n"
        "setp.ne.b32 p, 0, 0;\n"
        "wgmma.mma_async.sync.aligned.m64n128k16.f32.bf16.bf16 "
        "{%0, %1, %2, %3, %4, %5, %6, %7, %8, %9, %10, %11, %12, %13, %14, %15, "
        "%16, %17, %18, %19, %20, %21, %22, %23, %24, %25, %26, %27, %28, %29, %30, %31, "
        "%32, %33, %34, %35, %36, %37, %38, %39, %40, %41, %42, %43, %44, %45, %46, %47, "
        "%48, %49, %50, %51, %52, %53, %54, %55, %56, %57, %58, %59, %60, %61, %62, %63}, "
        "{%64, %65, %66, %67}, %68, p, 1, 1, 0;\n}\n"
        :
          "=f"(d[0]), "=f"(d[1]), "=f"(d[2]), "=f"(d[3]), "=f"(d[4]), "=f"(d[5]), "=f"(d[6]), "=f"(d[7]),
          "=f"(d[8]), "=f"(d[9]), "=f"(d[10]), "=f"(d[11]), "=f"(d[12]), "=f"(d[13]), "=f"(d[14]), "=f"(d[15]),
          "=f"(d[16]), "=f"(d[17]), "=f"(d[18]), "=f"(d[19]), "=f"(d[20]), "=f"(d[21]), "=f"(d[22]), "=f"(d[23]),
          "=f"(d[24]), "=f"(d[25]), "=f"(d[26]), "=f"(d[27]), "=f"(d[28]), "=f"(d[29]), "=f"(d[30]), "=f"(d[31]),
          "=f"(d[32]), "=f"(d[33]), "=f"(d[34]), "=f"(d[35]), "=f"(d[36]), "=f"(d[37]), "=f"(d[38]), "=f"(d[39]),
          "=f"(d[40]), "=f"(d[41]), "=f"(d[42]), "=f"(d[43]), "=f"(d[44]), "=f"(d[45]), "=f"(d[46]), "=f"(d[47]),
          "=f"(d[48]), "=f"(d[49]), "=f"(d[50]), "=f"(d[51]), "=f"(d[52]), "=f"(d[53]), "=f"(d[54]), "=f"(d[55]),
          "=f"(d[56]), "=f"(d[57]), "=f"(d[58]), "=f"(d[59]), "=f"(d[60]), "=f"(d[61]), "=f"(d[62]), "=f"(d[63])
        : "r"(a[0]), "r"(a[1]), "r"(a[2]), "r"(a[3]), "l"(descB));
}

__device__ __forceinline__ void wgmma_rs_n128_t1(float (&d)[64], const uint32_t (&a)[4], uint64_t descB, int scaleD) {
    asm volatile("{\n.reg .pred p;\n"
        "setp.ne.b32 p, %69, 0;\n"
        "wgmma.mma_async.sync.aligned.m64n128k16.f32.bf16.bf16 "
        "{%0, %1, %2, %3, %4, %5, %6, %7, %8, %9, %10, %11, %12, %13, %14, %15, "
        "%16, %17, %18, %19, %20, %21, %22, %23, %24, %25, %26, %27, %28, %29, %30, %31, "
        "%32, %33, %34, %35, %36, %37, %38, %39, %40, %41, %42, %43, %44, %45, %46, %47, "
        "%48, %49, %50, %51, %52, %53, %54, %55, %56, %57, %58, %59, %60, %61, %62, %63}, "
        "{%64, %65, %66, %67}, %68, p, 1, 1, 1;\n}\n"
        :
          "+f"(d[0]), "+f"(d[1]), "+f"(d[2]), "+f"(d[3]), "+f"(d[4]), "+f"(d[5]), "+f"(d[6]), "+f"(d[7]),
          "+f"(d[8]), "+f"(d[9]), "+f"(d[10]), "+f"(d[11]), "+f"(d[12]), "+f"(d[13]), "+f"(d[14]), "+f"(d[15]),
          "+f"(d[16]), "+f"(d[17]), "+f"(d[18]), "+f"(d[19]), "+f"(d[20]), "+f"(d[21]), "+f"(d[22]), "+f"(d[23]),
          "+f"(d[24]), "+f"(d[25]), "+f"(d[26]), "+f"(d[27]), "+f"(d[28]), "+f"(d[29]), "+f"(d[30]), "+f"(d[31]),
          "+f"(d[32]), "+f"(d[33]), "+f"(d[34]), "+f"(d[35]), "+f"(d[36]), "+f"(d[37]), "+f"(d[38]), "+f"(d[39]),
          "+f"(d[40]), "+f"(d[41]), "+f"(d[42]), "+f"(d[43]), "+f"(d[44]), "+f"(d[45]), "+f"(d[46]), "+f"(d[47]),
          "+f"(d[48]), "+f"(d[49]), "+f"(d[50]), "+f"(d[51]), "+f"(d[52]), "+f"(d[53]), "+f"(d[54]), "+f"(d[55]),
          "+f"(d[56]), "+f"(d[57]), "+f"(d[58]), "+f"(d[59]), "+f"(d[60]), "+f"(d[61]), "+f"(d[62]), "+f"(d[63])
        : "r"(a[0]), "r"(a[1]), "r"(a[2]), "r"(a[3]), "l"(descB), "r"(scaleD));
}

__device__ __forceinline__ void wgmma_ss_n184_t1(float (&d)[92], uint64_t descA, uint64_t descB, int scaleD) {
    asm volatile("{\n.reg .pred p;\n"
        "setp.ne.b32 p, %94, 0;\n"
        "wgmma.mma_async.sync.aligned.m64n184k16.f32.bf16.bf16 "
        "{%0, %1, %2, %3, %4, %5, %6, %7, %8, %9, %10, %11, %12, %13, %14, %15, "
        "%16, %17, %18, %19, %20, %21, %22, %23, %24, %25, %26, %27, %28, %29, %30, %31, "
        "%32, %33, %34, %35, %36, %37, %38, %39, %40, %41, %42, %43, %44, %45, %46, %47, "
        "%48, %49, %50, %51, %52, %53, %54, %55, %56, %57, %58, %59, %60, %61, %62, %63, "
        "%64, %65, %66, %67, %68, %69, %70, %71, %72, %73, %74, %75, %76, %77, %78, %79, "
        "%80, %81, %82, %83, %84, %85, %86, %87, %88, %89, %90, %91}, "
        "%92, %93, p, 1, 1, 0, 1;\n}\n"
        :
          "+f"(d[0]), "+f"(d[1]), "+f"(d[2]), "+f"(d[3]), "+f"(d[4]), "+f"(d[5]), "+f"(d[6]), "+f"(d[7]),
          "+f"(d[8]), "+f"(d[9]), "+f"(d[10]), "+f"(d[11]), "+f"(d[12]), "+f"(d[13]), "+f"(d[14]), "+f"(d[15]),
          "+f"(d[16]), "+f"(d[17]), "+f"(d[18]), "+f"(d[19]), "+f"(d[20]), "+f"(d[21]), "+f"(d[22]), "+f"(d[23]),
          "+f"(d[24]), "+f"(d[25]), "+f"(d[26]), "+f"(d[27]), "+f"(d[28]), "+f"(d[29]), "+f"(d[30]), "+f"(d[31]),
          "+f"(d[32]), "+f"(d[33]), "+f"(d[34]), "+f"(d[35]), "+f"(d[36]), "+f"(d[37]), "+f"(d[38]), "+f"(d[39]),
          "+f"(d[40]), "+f"(d[41]), "+f"(d[42]), "+f"(d[43]), "+f"(d[44]), "+f"(d[45]), "+f"(d[46]), "+f"(d[47]),
          "+f"(d[48]), "+f"(d[49]), "+f"(d[50]), "+f"(d[51]), "+f"(d[52]), "+f"(d[53]), "+f"(d[54]), "+f"(d[55]),
          "+f"(d[56]), "+f"(d[57]), "+f"(d[58]), "+f"(d[59]), "+f"(d[60]), "+f"(d[61]), "+f"(d[62]), "+f"(d[63]),
          "+f"(d[64]), "+f"(d[65]), "+f"(d[66]), "+f"(d[67]), "+f"(d[68]), "+f"(d[69]), "+f"(d[70]), "+f"(d[71]),
          "+f"(d[72]), "+f"(d[73]), "+f"(d[74]), "+f"(d[75]), "+f"(d[76]), "+f"(d[77]), "+f"(d[78]), "+f"(d[79]),
          "+f"(d[80]), "+f"(d[81]), "+f"(d[82]), "+f"(d[83]), "+f"(d[84]), "+f"(d[85]), "+f"(d[86]), "+f"(d[87]),
          "+f"(d[88]), "+f"(d[89]), "+f"(d[90]), "+f"(d[91])
        : "l"(descA), "l"(descB), "r"(scaleD));
}

__device__ __forceinline__ void wgmma_ss_n192_t1(float (&d)[96], uint64_t descA, uint64_t descB, int scaleD) {
    asm volatile("{\n.reg .pred p;\n"
        "setp.ne.b32 p, %98, 0;\n"
        "wgmma.mma_async.sync.aligned.m64n192k16.f32.bf16.bf16 "
        "{%0, %1, %2, %3, %4, %5, %6, %7, %8, %9, %10, %11, %12, %13, %14, %15, "
        "%16, %17, %18, %19, %20, %21, %22, %23, %24, %25, %26, %27, %28, %29, %30, %31, "
        "%32, %33, %34, %35, %36, %37, %38, %39, %40, %41, %42, %43, %44, %45, %46, %47, "
        "%48, %49, %50, %51, %52, %53, %54, %55, %56, %57, %58, %59, %60, %61, %62, %63, "
        "%64, %65, %66, %67, %68, %69, %70, %71, %72, %73, %74, %75, %76, %77, %78, %79, "
        "%80, %81, %82, %83, %84, %85, %86, %87, %88, %89, %90, %91, %92, %93, %94, %95}, "
        "%96, %97, p, 1, 1, 0, 1;\n}\n"
        :
          "+f"(d[0]), "+f"(d[1]), "+f"(d[2]), "+f"(d[3]), "+f"(d[4]), "+f"(d[5]), "+f"(d[6]), "+f"(d[7]),
          "+f"(d[8]), "+f"(d[9]), "+f"(d[10]), "+f"(d[11]), "+f"(d[12]), "+f"(d[13]), "+f"(d[14]), "+f"(d[15]),
          "+f"(d[16]), "+f"(d[17]), "+f"(d[18]), "+f"(d[19]), "+f"(d[20]), "+f"(d[21]), "+f"(d[22]), "+f"(d[23]),
          "+f"(d[24]), "+f"(d[25]), "+f"(d[26]), "+f"(d[27]), "+f"(d[28]), "+f"(d[29]), "+f"(d[30]), "+f"(d[31]),
          "+f"(d[32]), "+f"(d[33]), "+f"(d[34]), "+f"(d[35]), "+f"(d[36]), "+f"(d[37]), "+f"(d[38]), "+f"(d[39]),
          "+f"(d[40]), "+f"(d[41]), "+f"(d[42]), "+f"(d[43]), "+f"(d[44]), "+f"(d[45]), "+f"(d[46]), "+f"(d[47]),
          "+f"(d[48]), "+f"(d[49]), "+f"(d[50]), "+f"(d[51]), "+f"(d[52]), "+f"(d[53]), "+f"(d[54]), "+f"(d[55]),
          "+f"(d[56]), "+f"(d[57]), "+f"(d[58]), "+f"(d[59]), "+f"(d[60]), "+f"(d[61]), "+f"(d[62]), "+f"(d[63]),
          "+f"(d[64]), "+f"(d[65]), "+f"(d[66]), "+f"(d[67]), "+f"(d[68]), "+f"(d[69]), "+f"(d[70]), "+f"(d[71]),
          "+f"(d[72]), "+f"(d[73]), "+f"(d[74]), "+f"(d[75]), "+f"(d[76]), "+f"(d[77]), "+f"(d[78]), "+f"(d[79]),
          "+f"(d[80]), "+f"(d[81]), "+f"(d[82]), "+f"(d[83]), "+f"(d[84]), "+f"(d[85]), "+f"(d[86]), "+f"(d[87]),
          "+f"(d[88]), "+f"(d[89]), "+f"(d[90]), "+f"(d[91]), "+f"(d[92]), "+f"(d[93]), "+f"(d[94]), "+f"(d[95])
        : "l"(descA), "l"(descB), "r"(scaleD));
}

__device__ __forceinline__ void wgmma_ss_n128_t1(float (&d)[64], uint64_t descA, uint64_t descB, int scaleD) {
    asm volatile("{\n.reg .pred p;\n"
        "setp.ne.b32 p, %66, 0;\n"
        "wgmma.mma_async.sync.aligned.m64n128k16.f32.bf16.bf16 "
        "{%0, %1, %2, %3, %4, %5, %6, %7, %8, %9, %10, %11, %12, %13, %14, %15, "
        "%16, %17, %18, %19, %20, %21, %22, %23, %24, %25, %26, %27, %28, %29, %30, %31, "
        "%32, %33, %34, %35, %36, %37, %38, %39, %40, %41, %42, %43, %44, %45, %46, %47, "
        "%48, %49, %50, %51, %52, %53, %54, %55, %56, %57, %58, %59, %60, %61, %62, %63}, "
        "%64, %65, p, 1, 1, 0, 1;\n}\n"
        :
          "+f"(d[0]), "+f"(d[1]), "+f"(d[2]), "+f"(d[3]), "+f"(d[4]), "+f"(d[5]), "+f"(d[6]), "+f"(d[7]),
          "+f"(d[8]), "+f"(d[9]), "+f"(d[10]), "+f"(d[11]), "+f"(d[12]), "+f"(d[13]), "+f"(d[14]), "+f"(d[15]),
          "+f"(d[16]), "+f"(d[17]), "+f"(d[18]), "+f"(d[19]), "+f"(d[20]), "+f"(d[21]), "+f"(d[22]), "+f"(d[23]),
          "+f"(d[24]), "+f"(d[25]), "+f"(d[26]), "+f"(d[27]), "+f"(d[28]), "+f"(d[29]), "+f"(d[30]), "+f"(d[31]),
          "+f"(d[32]), "+f"(d[33]), "+f"(d[34]), "+f"(d[35]), "+f"(d[36]), "+f"(d[37]), "+f"(d[38]), "+f"(d[39]),
          "+f"(d[40]), "+f"(d[41]), "+f"(d[42]), "+f"(d[43]), "+f"(d[44]), "+f"(d[45]), "+f"(d[46]), "+f"(d[47]),
          "+f"(d[48]), "+f"(d[49]), "+f"(d[50]), "+f"(d[51]), "+f"(d[52]), "+f"(d[53]), "+f"(d[54]), "+f"(d[55]),
          "+f"(d[56]), "+f"(d[57]), "+f"(d[58]), "+f"(d[59]), "+f"(d[60]), "+f"(d[61]), "+f"(d[62]), "+f"(d[63])
        : "l"(descA), "l"(descB), "r"(scaleD));
}

__device__ __forceinline__ void wgmma_ss_n32_t1(float (&d)[16], uint64_t descA, uint64_t descB, int scaleD) {
    asm volatile("{\n.reg .pred p;\n"
        "setp.ne.b32 p, %18, 0;\n"
        "wgmma.mma_async.sync.aligned.m64n32k16.f32.bf16.bf16 "
        "{%0, %1, %2, %3, %4, %5, %6, %7, %8, %9, %10, %11, %12, %13, %14, %15}, "
        "%16, %17, p, 1, 1, 0, 1;\n}\n"
        :
          "+f"(d[0]), "+f"(d[1]), "+f"(d[2]), "+f"(d[3]), "+f"(d[4]), "+f"(d[5]), "+f"(d[6]), "+f"(d[7]),
          "+f"(d[8]), "+f"(d[9]), "+f"(d[10]), "+f"(d[11]), "+f"(d[12]), "+f"(d[13]), "+f"(d[14]), "+f"(d[15])
        : "l"(descA), "l"(descB), "r"(scaleD));
}

constexpr int S_LEN = 2048;
constexpr int D_MODEL = 640;
constexpr int N_HEADS = 32;
constexpr int D_HEAD = 128;
constexpr int S_KV = 2048;
constexpr int WIN = 512;
constexpr int D_FF = 1728;
constexpr float LN_EPS = 1e-5f;

#define TS(kid, slot)

__device__ float g_mod[6 * D_MODEL];
__device__ __align__(1024) __nv_bfloat16 g_h[S_LEN * D_MODEL];
__device__ __align__(1024) __nv_bfloat16 g_o[S_LEN * N_HEADS * D_HEAD];
__device__ __align__(1024) __nv_bfloat16 g_part[4 * S_LEN * D_MODEL];
__device__ __align__(1024) __nv_bfloat16 g_x1[S_LEN * D_MODEL];
__device__ __align__(1024) __nv_bfloat16 g_h2[S_LEN * D_MODEL];
__device__ __align__(1024) __nv_bfloat16 g_act[S_LEN * D_FF];

constexpr int F_MODAB = 0, F_MODALL = 1, F_H = 2, F_P = 18, F_H2 = 34, F_A = 50, F_O = 66, F_A1 = 130, F_COUNT = 146;
__device__ unsigned g_flags[F_COUNT * 32];
__device__ unsigned g_epoch;
__device__ unsigned g_exit;

__device__ __forceinline__ void flag_signal(int f) {
    asm volatile("red.release.gpu.global.add.u32 [%0], 1;" ::"l"(g_flags + f * 32) : "memory");
}
__device__ __forceinline__ void flag_signal_relaxed(int f) {
    asm volatile("red.relaxed.gpu.global.add.u32 [%0], 1;" ::"l"(g_flags + f * 32) : "memory");
}
__device__ __forceinline__ void flag_wait(int f, unsigned target) {
    unsigned n = 0;
    while (true) {
        unsigned v;
        asm volatile("ld.acquire.gpu.global.u32 %0, [%1];" : "=r"(v) : "l"(g_flags + f * 32) : "memory");
        if ((int)(v - target) >= 0) break;
        if ((++n & 0xfffu) == 0) {
            if (n > (1u << 24)) g_abort = 1;
            if (g_abort) break;
        }
    }
}

struct Maps {
    CUtensorMap h, wq, k, v, o_st, o_a, wo, part_st, h2, g128, u128, g64, u64, act_st64, act_st24, act_a, wd, wd32;
};

constexpr int SM_DATA = 229376;
constexpr int SM_STAGING = 196608;
constexpr int SM_TOTAL = SM_DATA + 1024 + 512;
constexpr int B1F = 0, B1E = 6, B2F = 12, B2E = 16, B4F = 20, B4E = 24, B5F = 28, B5E = 33, BD1 = 38, BD2 = 39, BD4 = 40, BD1A = 41, BX = 42, BD4B = 43;
constexpr int P1_STAGE = 32768, P2_STAGE = 57344, P4_STAGE = 49152, P5_STAGE = 36864;

__device__ __forceinline__ float rcp_approx(float x) { float y; asm("rcp.approx.ftz.f32 %0, %1;" : "=f"(y) : "f"(x)); return y; }
__device__ __forceinline__ float silu_mul(float g, float u) { return g * rcp_approx(1.f + ex2(-1.4426950408889634f * g)) * u; }
__device__ __forceinline__ uint2 ldcg_u2(const void* p) { return __ldcg(reinterpret_cast<const uint2*>(p)); }

__device__ __forceinline__ void ln_rows_impl(uint2 a0, uint2 a1, uint2 a2, uint2 a3, uint2 a4, uint2 b0, uint2 b1, uint2 b2, uint2 b3, uint2 b4,
                                          const float* __restrict__ shift, const float* __restrict__ scale1p,
                                          __nv_bfloat16* __restrict__ dst, int lane) {
    const uint2 xr[2][5] = {{a0, a1, a2, a3, a4}, {b0, b1, b2, b3, b4}};
    float4 sh[5], sc[5];
#pragma unroll
    for (int i = 0; i < 5; i++) {
        sh[i] = __ldcg(reinterpret_cast<const float4*>(shift + (lane + 32 * i) * 4));
        sc[i] = __ldcg(reinterpret_cast<const float4*>(scale1p + (lane + 32 * i) * 4));
    }
    float mean[2], rstd[2];
#pragma unroll
    for (int rr = 0; rr < 2; rr++) {
        float s = 0.f;
#pragma unroll
        for (int i = 0; i < 5; i++) s += (bf16lo(xr[rr][i].x) + bf16hi(xr[rr][i].x)) + (bf16lo(xr[rr][i].y) + bf16hi(xr[rr][i].y));
#pragma unroll
        for (int o = 16; o > 0; o >>= 1) s += __shfl_xor_sync(0xffffffffu, s, o);
        mean[rr] = s * (1.f / D_MODEL);
    }
#pragma unroll
    for (int rr = 0; rr < 2; rr++) {
        float q = 0.f;
#pragma unroll
        for (int i = 0; i < 5; i++) {
            const float d0 = bf16lo(xr[rr][i].x) - mean[rr], d1 = bf16hi(xr[rr][i].x) - mean[rr];
            const float d2 = bf16lo(xr[rr][i].y) - mean[rr], d3 = bf16hi(xr[rr][i].y) - mean[rr];
            q += (d0 * d0 + d1 * d1) + (d2 * d2 + d3 * d3);
        }
#pragma unroll
        for (int o = 16; o > 0; o >>= 1) q += __shfl_xor_sync(0xffffffffu, q, o);
        rstd[rr] = rsqrtf(q * (1.f / D_MODEL) + LN_EPS);
    }
#pragma unroll
    for (int rr = 0; rr < 2; rr++) {
#pragma unroll
        for (int i = 0; i < 5; i++) {
            uint2 u;
            u.x = pack_bf16((bf16lo(xr[rr][i].x) - mean[rr]) * rstd[rr] * sc[i].x + sh[i].x, (bf16hi(xr[rr][i].x) - mean[rr]) * rstd[rr] * sc[i].y + sh[i].y);
            u.y = pack_bf16((bf16lo(xr[rr][i].y) - mean[rr]) * rstd[rr] * sc[i].z + sh[i].z, (bf16hi(xr[rr][i].y) - mean[rr]) * rstd[rr] * sc[i].w + sh[i].w);
            *reinterpret_cast<uint2*>(dst + (size_t)rr * D_MODEL + (lane + 32 * i) * 4) = u;
        }
    }
}

__device__ __forceinline__ void ln_rows(const uint2 (&xr)[2][5], const float* shift, const float* scale1p, __nv_bfloat16* dst, int lane) {
    ln_rows_impl(xr[0][0], xr[0][1], xr[0][2], xr[0][3], xr[0][4], xr[1][0], xr[1][1], xr[1][2], xr[1][3], xr[1][4], shift, scale1p, dst, lane);
}

__global__ void __cluster_dims__(2, 1, 1) __launch_bounds__(384, 1)
mega_kernel(const __grid_constant__ Maps tm, const __nv_bfloat16* __restrict__ x, const __nv_bfloat16* __restrict__ cvec,
            const __nv_bfloat16* __restrict__ w_mod, __nv_bfloat16* __restrict__ out, const void* wo_p, const void* wg_p,
            const void* wu_p, const void* wd_p) {
    extern __shared__ uint8_t smem_raw[];
    const uint32_t base = (smem_u32(smem_raw) + 1023u) & ~1023u;
    const uint32_t bars = base + SM_DATA;
    const uint32_t rank = cluster_ctarank();
    const int cid = blockIdx.x >> 1;
    const int p = cid & 7, j = cid >> 3;
    const int mt = p * 2 + (int)rank;
    const int m0 = mt * 128;
    const int wg = threadIdx.x >> 7;
    unsigned epoch;
    asm volatile("ld.volatile.global.u32 %0, [%1];" : "=r"(epoch) : "l"(&g_epoch));

    if (threadIdx.x == 0) {
        for (int i = 0; i < 6; i++) { mbar_init(bars + 8 * (B1F + i), 1); mbar_init(bars + 8 * (B1E + i), 4); }
        for (int i = 0; i < 4; i++) { mbar_init(bars + 8 * (B2F + i), 1); mbar_init(bars + 8 * (B2E + i), 4); }
        for (int i = 0; i < 4; i++) { mbar_init(bars + 8 * (B4F + i), 1); mbar_init(bars + 8 * (B4E + i), 4); }
        for (int i = 0; i < 5; i++) { mbar_init(bars + 8 * (B5F + i), 1); mbar_init(bars + 8 * (B5E + i), 2); }
        mbar_init(bars + 8 * BD1, 4); mbar_init(bars + 8 * BD2, 4); mbar_init(bars + 8 * BD4, 4); mbar_init(bars + 8 * BD1A, 4);
        mbar_init(bars + 8 * BX, 1); mbar_init(bars + 8 * BD4B, 4);
        mbar_expect_tx(bars + 8 * BX, 40960);
        fence_mbar_init();
    }
    __syncthreads();
    cluster_sync();

    if (wg == 2) {
        reg_dealloc<40>();
        if (threadIdx.x == 256) {
            {
                uint32_t st = 0, ph = 1;
                bool first = true;
#pragma unroll 1
                for (int hp = 0; hp < 2; hp++) {
                    const int head0 = j * 4 + hp * 2;
                    if (first) {
#pragma unroll 1
                        for (int s = 1; s < 6; s++) {
                            if (s == 3) continue;
                            const int kb = s < 3 ? s - 1 : s - 2;
                            mbar_expect_tx(bars + 8 * (B1F + s), P1_STAGE);
#pragma unroll 1
                            for (int c = 0; c < 2; c++) {
                                const int chunk = 2 * (int)rank + c;
                                tma_load_2d_mc(base + s * P1_STAGE + chunk * 8192, &tm.wq, head0 * 128 + chunk * 64, kb * 64, bars + 8 * (B1F + s), 3);
                            }
                        }
                        flag_wait(F_H + mt, (epoch + 1) * 8);
                        fence_proxy_async_all();
#pragma unroll 1
                        for (int s = 0; s < 6; s += 3) {
                            mbar_expect_tx(bars + 8 * (B1F + s), P1_STAGE);
                            tma_load_2d(base + s * P1_STAGE, &tm.h, (s / 3 * 2) * 64, m0, bars + 8 * (B1F + s));
                            tma_load_2d(base + s * P1_STAGE + 16384, &tm.h, (s / 3 * 2 + 1) * 64, m0, bars + 8 * (B1F + s));
                        }
                        ph = 0;
                    }
#pragma unroll 1
                    for (int kk2 = first ? 2 : 0; kk2 < 5; kk2++) {
                        mbar_wait(bars + 8 * (B1E + st), ph);
                        mbar_expect_tx(bars + 8 * (B1F + st), P1_STAGE);
                        tma_load_2d(base + st * P1_STAGE, &tm.h, (2 * kk2) * 64, m0, bars + 8 * (B1F + st));
                        tma_load_2d(base + st * P1_STAGE + 16384, &tm.h, (2 * kk2 + 1) * 64, m0, bars + 8 * (B1F + st));
                        if (++st == 6) { st = 0; ph ^= 1; }
#pragma unroll 1
                        for (int u = 0; u < 2; u++) {
                            mbar_wait(bars + 8 * (B1E + st), ph);
                            mbar_expect_tx(bars + 8 * (B1F + st), P1_STAGE);
                            const int kb = 2 * kk2 + u;
#pragma unroll 1
                            for (int c = 0; c < 2; c++) {
                                const int chunk = 2 * (int)rank + c;
                                tma_load_2d_mc(base + st * P1_STAGE + chunk * 8192, &tm.wq, head0 * 128 + chunk * 64, kb * 64, bars + 8 * (B1F + st), 3);
                            }
                            if (++st == 6) { st = 0; ph ^= 1; }
                        }
                    }
                    first = false;
#pragma unroll 1
                    for (int t = 0; t <= 8; t++) {
                        if (t < 8) {
                            mbar_wait(bars + 8 * (B1E + st), ph);
                            mbar_expect_tx(bars + 8 * (B1F + st), P1_STAGE);
                            const int row = (head0 + (t >> 2)) * S_KV + (S_KV - WIN) + (t & 3) * 128;
                            tma_load_2d_mc(base + st * P1_STAGE + rank * 16384, &tm.k, rank * 64, row, bars + 8 * (B1F + st), 3);
                            if (++st == 6) { st = 0; ph ^= 1; }
                        }
                        if (t > 0) {
                            mbar_wait(bars + 8 * (B1E + st), ph);
                            mbar_expect_tx(bars + 8 * (B1F + st), P1_STAGE);
                            const int tv = t - 1;
                            const int row = (head0 + (tv >> 2)) * S_KV + (S_KV - WIN) + (tv & 3) * 128;
                            tma_load_2d_mc(base + st * P1_STAGE + rank * 16384, &tm.v, rank * 64, row, bars + 8 * (B1F + st), 3);
                            if (++st == 6) { st = 0; ph ^= 1; }
                        }
                    }
                }
            }
            {
                const int kq = j >> 1, n0 = (j & 1) * 320;
                uint32_t st = 0, ph = 1;
#pragma unroll 1
                for (int i = 0; i < 16; i++) {
                    if (i == 0) mbar_wait(bars + 8 * BD1A, 0);
                    if (i == 3) mbar_wait(bars + 8 * BD1, 0);
                    if (i == 8) { flag_wait(F_O + mt * 4 + kq, (epoch + 1) * 4); fence_proxy_async_all(); }
                    mbar_wait(bars + 8 * (B2E + st), ph);
                    mbar_expect_tx(bars + 8 * (B2F + st), P2_STAGE);
                    const uint32_t dst = base + st * P2_STAGE;
                    const int k0 = kq * 1024 + ((i + (j & 1) * 8) & 15) * 64;
                    tma_load_2d(dst, &tm.o_a, k0, m0, bars + 8 * (B2F + st));
#pragma unroll 1
                    for (int c = 0; c < 5; c++)
                        if (((c + i) & 1) == (int)rank) tma_load_2d_mc(dst + 16384 + c * 8192, &tm.wo, n0 + c * 64, k0, bars + 8 * (B2F + st), 3);
                    if (++st == 4) { st = 0; ph ^= 1; }
                }
            }
            {
                const int f0 = j * 216;
                const CUtensorMap* t128 = rank == 0 ? &tm.g128 : &tm.u128;
                const CUtensorMap* t64 = rank == 0 ? &tm.g64 : &tm.u64;
                mbar_wait(bars + 8 * BD2, 0);
#pragma unroll 1
                for (int i = 0; i < 4; i++) {
                    mbar_expect_tx(bars + 8 * (B4F + i), 16384 + 32768);
                    const uint32_t dst = base + i * P4_STAGE;
                    tma_load_2d_mc(dst + 16384 + rank * 16384, t128, f0, i * 64, bars + 8 * (B4F + i), 3);
                    tma_load_2d_mc(dst + 16384 + rank * 16384 + 8192, t128, f0 + 64, i * 64, bars + 8 * (B4F + i), 3);
                }
                flag_wait(F_H2 + mt, (epoch + 1) * 8);
                fence_proxy_async_all();
#pragma unroll 1
                for (int i = 0; i < 4; i++) tma_load_2d(base + i * P4_STAGE, &tm.h2, i * 64, m0, bars + 8 * (B4F + i));
                uint32_t st = 0, ph = 0;
#pragma unroll 1
                for (int i = 4; i < 20; i++) {
                    const int kb = i < 10 ? i : i - 10;
                    mbar_wait(bars + 8 * (B4E + st), ph);
                    const uint32_t dst = base + st * P4_STAGE;
                    if (i < 10) {
                        mbar_expect_tx(bars + 8 * (B4F + st), 16384 + 32768);
                        tma_load_2d(dst, &tm.h2, kb * 64, m0, bars + 8 * (B4F + st));
                        tma_load_2d_mc(dst + 16384 + rank * 16384, t128, f0, kb * 64, bars + 8 * (B4F + st), 3);
                        tma_load_2d_mc(dst + 16384 + rank * 16384 + 8192, t128, f0 + 64, kb * 64, bars + 8 * (B4F + st), 3);
                    } else {
                        mbar_expect_tx(bars + 8 * (B4F + st), 16384 + 24576);
                        tma_load_2d(dst, &tm.h2, kb * 64, m0, bars + 8 * (B4F + st));
#pragma unroll 1
                        for (int c = 0; c < 3; c++)
                            tma_load_2d_mc(dst + 16384 + rank * 12288 + c * 4096, t64, f0 + 128 + c * 32, kb * 64, bars + 8 * (B4F + st), 3);
                    }
                    if (++st == 4) { st = 0; ph ^= 1; }
                }
            }
            {
                const int mt5 = p * 2 + (j >> 2), n0 = (j & 3) * 160;
                const int nkb = rank == 0 ? 14 : 13;
                const unsigned long long ord = rank == 0
                    ? (0ull | 1ull << 5 | 4ull << 10 | 7ull << 15 | 11ull << 20 | 2ull << 25 | 3ull << 30 | 5ull << 35 | 6ull << 40 | 8ull << 45 | 9ull << 50 | 10ull << 55)
                    : (14ull | 17ull << 5 | 21ull << 10 | 24ull << 15 | 15ull << 20 | 16ull << 25 | 18ull << 30 | 19ull << 35 | 20ull << 40 | 22ull << 45 | 23ull << 50 | 25ull << 55);
                const int nearly = rank == 0 ? 5 : 4;
                mbar_wait(bars + 8 * BD4, 0);
                uint32_t st = 0, ph = 1;
#pragma unroll 1
                for (int i = 0; i < nkb; i++) {
                    const int kb = i < 12 ? (int)((ord >> (5 * i)) & 31) : (rank == 0 ? i : 26);
                    if (i == 0) { flag_wait(F_A1 + mt5, (epoch + 1) * 16); fence_proxy_async_all(); }
                    if (i == nearly) { flag_wait(F_A + mt5, (epoch + 1) * 16); fence_proxy_async_all(); }
                    mbar_wait(bars + 8 * (B5E + st), ph);
                    mbar_expect_tx(bars + 8 * (B5F + st), P5_STAGE);
                    const uint32_t dst = base + st * P5_STAGE;
                    const int k0 = kb * 64;
                    tma_load_2d(dst + 16384, &tm.wd, n0, k0, bars + 8 * (B5F + st));
                    tma_load_2d(dst + 16384 + 8192, &tm.wd, n0 + 64, k0, bars + 8 * (B5F + st));
                    tma_load_2d(dst + 16384 + 16384, &tm.wd32, n0 + 128, k0, bars + 8 * (B5F + st));
                    tma_load_2d(dst, &tm.act_a, k0, mt5 * 128, bars + 8 * (B5F + st));
                    if (++st == 5) { st = 0; ph ^= 1; }
                }
            }
        }
        else if (threadIdx.x == 288) {
            mbar_wait(bars + 8 * B1F, 0);
            const char* pw[4] = {(const char*)wo_p, (const char*)wg_p, (const char*)wu_p, (const char*)wd_p};
#pragma unroll 1
            for (int t = 0; t < 4; t++) {
                const uint32_t bytes = t == 0 ? 40960u : 17280u;
                asm volatile("cp.async.bulk.prefetch.L2.global [%0], %1;" ::"l"(pw[t] + (size_t)blockIdx.x * bytes), "r"(bytes) : "memory");
            }
        }
        __syncwarp();
        asm volatile("barrier.cluster.arrive.relaxed.aligned; // producer\n barrier.cluster.wait.aligned;" ::: "memory");
    } else {
        reg_alloc<232>();
        const int tid = threadIdx.x & 127;
        const int warp = tid >> 5, lane = tid & 31;
        const int cw = threadIdx.x >> 5;
        const uint32_t mystage = base + SM_STAGING + wg * 16384;
        auto arrive_both = [&](uint32_t bar) {
            if (tid == 0) mbar_arrive_cluster(bar, 0);
            if (tid == 32) mbar_arrive_cluster(bar, 1);
        };
        TS(0, 0);
        {
            uint2 xr[2][5];
            uint4 w[10];
            unsigned short cr[10];
            const int mb = blockIdx.x < 120 ? blockIdx.x : 0;
#pragma unroll
            for (int i = 0; i < 10; i++) cr[i] = __ldg(reinterpret_cast<const unsigned short*>(cvec) + cw * 80 + i * 8 + (lane >> 2));
#pragma unroll
            for (int i = 0; i < 10; i++)
                w[i] = __ldg(reinterpret_cast<const uint4*>(w_mod + (size_t)(cw * 80 + i * 8 + (lane >> 2)) * (6 * D_MODEL) + mb * 32 + (lane & 3) * 8));
#pragma unroll
            for (int rr = 0; rr < 2; rr++)
#pragma unroll
                for (int i = 0; i < 5; i++)
                    xr[rr][i] = __ldg(reinterpret_cast<const uint2*>(x + (size_t)(m0 + j * 16 + cw * 2 + rr) * D_MODEL + (lane + 32 * i) * 4));
            if (blockIdx.x < 120) {
                float* red = reinterpret_cast<float*>(smem_raw + (base - smem_u32(smem_raw)) + SM_STAGING);
                float acc[8];
#pragma unroll
                for (int i = 0; i < 8; i++) acc[i] = 0.f;
#pragma unroll
                for (int i = 0; i < 10; i++) {
                    const float s = bf16_round(silu_mul(__uint_as_float((uint32_t)cr[i] << 16), 1.f));
                    acc[0] += s * bf16lo(w[i].x); acc[1] += s * bf16hi(w[i].x);
                    acc[2] += s * bf16lo(w[i].y); acc[3] += s * bf16hi(w[i].y);
                    acc[4] += s * bf16lo(w[i].z); acc[5] += s * bf16hi(w[i].z);
                    acc[6] += s * bf16lo(w[i].w); acc[7] += s * bf16hi(w[i].w);
                }
#pragma unroll
                for (int i = 0; i < 8; i++) {
                    acc[i] += __shfl_xor_sync(0xffffffffu, acc[i], 4);
                    acc[i] += __shfl_xor_sync(0xffffffffu, acc[i], 8);
                    acc[i] += __shfl_xor_sync(0xffffffffu, acc[i], 16);
                }
                if (lane < 4) {
#pragma unroll
                    for (int i = 0; i < 8; i++) red[cw * 32 + lane * 8 + i] = acc[i];
                }
                TS(6, 0);
                bar_sync(5, 256);
                TS(6, 1);
                if (threadIdx.x < 32) {
                    float t = 0.f;
#pragma unroll
                    for (int i = 0; i < 8; i++) t += red[i * 32 + threadIdx.x];
                    t = bf16_round(t);
                    const int chunk = blockIdx.x / 20;
                    if (chunk == 1 || chunk == 4) t = bf16_round(1.f + t);
                    g_mod[blockIdx.x * 32 + threadIdx.x] = t;
                    __syncwarp();
                    TS(6, 2);
                    if (threadIdx.x == 0) flag_signal(blockIdx.x < 40 ? F_MODAB : F_MODALL);
                    TS(6, 3);
                }
            }
            if (threadIdx.x == 0) flag_wait(F_MODAB, (epoch + 1) * 40);
            bar_sync(5, 256);
            TS(0, 1);
            ln_rows(xr, g_mod, g_mod + D_MODEL, g_h + (size_t)(m0 + j * 16 + cw * 2) * D_MODEL, lane);
            TS(6, 4);
            bar_sync(5, 256);
            TS(6, 5);
            if (threadIdx.x == 0) flag_signal(F_H + mt);
        }
        TS(0, 2);
        {
            const float cscale = 0.08838834764831845f * 1.4426950408889634f;
            uint32_t st = 0, ph = 0;
            auto wait_full = [&]() -> uint32_t {
                mbar_wait(bars + 8 * (B1F + st), ph);
                return base + st * P1_STAGE;
            };
            auto release = [&](uint32_t s) { arrive_both(bars + 8 * (B1E + s)); };
            auto advance = [&]() { if (++st == 6) { st = 0; ph ^= 1; } };
            auto turn_wait = [&]() { bar_sync(3 + wg, 256); };
            auto turn_pass = [&]() { bar_arrive(3 + (wg ^ 1), 256); };
            if (wg == 1) bar_arrive(3, 256);

            for (int hp = 0; hp < 2; hp++) {
                const int head0 = j * 4 + hp * 2;
                uint32_t q[8][4];
                {
                    float acc[128];
#pragma unroll
                    for (int i = 0; i < 128; i++) acc[i] = 0.f;
                    for (int kk2 = 0; kk2 < 5; kk2++) {
                        const uint32_t hbuf = wait_full();
                        if (kk2 == 0 && hp == 0) TS(0, 3);
                        const uint32_t sth = st;
                        advance();
#pragma unroll
                        for (int u = 0; u < 2; u++) {
                            const uint32_t wbuf = wait_full();
                            const uint32_t stw = st;
                            advance();
                            wgmma_fence();
#pragma unroll
                            for (int k = 0; k < 4; k++) {
                                uint64_t da = make_desc(hbuf + u * 16384 + wg * 8192 + k * 32, 16, 1024, 1);
                                uint64_t db = make_desc(wbuf + k * 2048, 8192, 1024, 1);
                                wgmma_ss_n256_t1(acc, da, db, 1);
                            }
                            wgmma_commit();
                            wgmma_wait<0>();
                            release(stw);
                        }
                        release(sth);
                    }
                    fence_regs(acc);
                    if (tid == 0) tma_store_wait_read<0>();
                    bar_sync(1 + wg, 128);
#pragma unroll
                    for (int i = 0; i < 8; i++) {
                        q[i][0] = pack_bf16(acc[8 * i + 0], acc[8 * i + 1]);
                        q[i][1] = pack_bf16(acc[8 * i + 2], acc[8 * i + 3]);
                        q[i][2] = pack_bf16(acc[8 * i + 4], acc[8 * i + 5]);
                        q[i][3] = pack_bf16(acc[8 * i + 6], acc[8 * i + 7]);
                        uint32_t b0 = pack_bf16(acc[64 + 8 * i + 0], acc[64 + 8 * i + 1]);
                        uint32_t b1 = pack_bf16(acc[64 + 8 * i + 2], acc[64 + 8 * i + 3]);
                        uint32_t b2 = pack_bf16(acc[64 + 8 * i + 4], acc[64 + 8 * i + 5]);
                        uint32_t b3 = pack_bf16(acc[64 + 8 * i + 6], acc[64 + 8 * i + 7]);
                        asm volatile("st.shared.v4.b32 [%0], {%1, %2, %3, %4};" ::"r"(mystage + (i * 128 + tid) * 16), "r"(b0), "r"(b1),
                                     "r"(b2), "r"(b3) : "memory");
                    }
                }
                float o[64], s[64], e[64];
                uint32_t pp[8][4];
                float mm0, mm1, l0, l1, a0, a1, lo0, lo1;
#pragma unroll
                for (int i = 0; i < 64; i++) { o[i] = 0.f; }

                auto issue_s = [&]() -> uint32_t {
                    const uint32_t kbuf = wait_full();
                    const uint32_t stk = st;
                    advance();
                    wgmma_fence();
#pragma unroll
                    for (int k = 0; k < 8; k++) {
                        uint64_t db = make_desc(kbuf + (k >> 2) * 16384 + (k & 3) * 32, 16, 1024, 1);
                        if (k == 0) wgmma_rs_n128_t0_z(s, q[k], db);
                        else wgmma_rs_n128_t0(s, q[k], db, 1);
                    }
                    wgmma_commit();
                    return stk;
                };
                auto issue_pv = [&](bool fresh) -> uint32_t {
                    const uint32_t vbuf = wait_full();
                    const uint32_t stv = st;
                    advance();
                    wgmma_fence();
#pragma unroll
                    for (int k = 0; k < 8; k++) {
                        uint64_t db = make_desc(vbuf + k * 2048, 16384, 1024, 1);
                        wgmma_rs_n128_t1(o, pp[k], db, (!fresh) || k != 0);
                    }
                    wgmma_commit();
                    return stv;
                };
                auto softmax = [&](bool first) {
                    float mx0 = fmaxf(s[0], s[1]), mx1 = fmaxf(s[2], s[3]);
#pragma unroll
                    for (int jj = 1; jj < 16; jj++) {
                        mx0 = fmaxf(mx0, fmaxf(s[4 * jj], s[4 * jj + 1]));
                        mx1 = fmaxf(mx1, fmaxf(s[4 * jj + 2], s[4 * jj + 3]));
                    }
                    mx0 = fmaxf(mx0, __shfl_xor_sync(0xffffffffu, mx0, 1));
                    mx0 = fmaxf(mx0, __shfl_xor_sync(0xffffffffu, mx0, 2));
                    mx1 = fmaxf(mx1, __shfl_xor_sync(0xffffffffu, mx1, 1));
                    mx1 = fmaxf(mx1, __shfl_xor_sync(0xffffffffu, mx1, 2));
                    if (first) {
                        lo0 = l0; lo1 = l1;
                        mm0 = mx0; mm1 = mx1; l0 = 0.f; l1 = 0.f; a0 = 0.f; a1 = 0.f;
                    } else {
                        float mn0 = fmaxf(mm0, mx0), mn1 = fmaxf(mm1, mx1);
                        a0 = ex2((mm0 - mn0) * cscale); a1 = ex2((mm1 - mn1) * cscale);
                        mm0 = mn0; mm1 = mn1;
                    }
                    const float mc0 = mm0 * cscale, mc1 = mm1 * cscale;
                    float r0 = 0.f, r1 = 0.f;
#pragma unroll
                    for (int jj = 0; jj < 16; jj++) {
                        e[4 * jj] = ex2(fmaf(s[4 * jj], cscale, -mc0));
                        e[4 * jj + 1] = ex2(fmaf(s[4 * jj + 1], cscale, -mc0));
                        e[4 * jj + 2] = ex2(fmaf(s[4 * jj + 2], cscale, -mc1));
                        e[4 * jj + 3] = ex2(fmaf(s[4 * jj + 3], cscale, -mc1));
                        r0 += e[4 * jj] + e[4 * jj + 1];
                        r1 += e[4 * jj + 2] + e[4 * jj + 3];
                    }
                    l0 = l0 * a0 + r0; l1 = l1 * a1 + r1;
                };
                auto convert_p = [&]() {
#pragma unroll
                    for (int i = 0; i < 8; i++) {
                        pp[i][0] = pack_bf16(e[8 * i + 0], e[8 * i + 1]);
                        pp[i][1] = pack_bf16(e[8 * i + 2], e[8 * i + 3]);
                        pp[i][2] = pack_bf16(e[8 * i + 4], e[8 * i + 5]);
                        pp[i][3] = pack_bf16(e[8 * i + 6], e[8 * i + 7]);
                    }
                };
                auto store_o = [&](float ls0, float ls1, int head, bool last) {
                    float s0 = ls0 + __shfl_xor_sync(0xffffffffu, ls0, 1); s0 += __shfl_xor_sync(0xffffffffu, s0, 2);
                    float s1 = ls1 + __shfl_xor_sync(0xffffffffu, ls1, 1); s1 += __shfl_xor_sync(0xffffffffu, s1, 2);
                    const float i0 = 1.f / s0, i1 = 1.f / s1;
                    if (tid == 0) {
                        tma_store_wait<0>();
                        if (last) {
                            mbar_arrive_cluster(bars + 8 * BD1A, 0);
                            mbar_arrive_cluster(bars + 8 * BD1A, 1);
                        }
                    }
                    bar_sync(1 + wg, 128);
#pragma unroll
                    for (int jj = 0; jj < 16; jj += 2) {
                        const int mi = lane >> 3;
                        const int row = warp * 16 + (mi & 1) * 8 + (lane & 7);
                        const int grp = jj + (mi >> 1);
                        const uint32_t addr = mystage + (grp >> 3) * 8192 + row * 128 + (((grp & 7) ^ (row & 7)) << 4);
                        stmatrix_x4(addr, pack_bf16(o[4 * jj] * i0, o[4 * jj + 1] * i0), pack_bf16(o[4 * jj + 2] * i1, o[4 * jj + 3] * i1),
                                    pack_bf16(o[4 * jj + 4] * i0, o[4 * jj + 5] * i0), pack_bf16(o[4 * jj + 6] * i1, o[4 * jj + 7] * i1));
                    }
                    fence_proxy_async();
                    bar_sync(1 + wg, 128);
                    if (tid == 0) {
                        tma_store_2d(&tm.o_st, mystage, head * 128, m0 + wg * 64);
                        tma_store_2d(&tm.o_st, mystage + 8192, head * 128 + 64, m0 + wg * 64);
                        tma_store_commit();
                        if (last) {
                            tma_store_wait<0>();
                            mbar_arrive_cluster(bars + 8 * BD1, 0);
                            mbar_arrive_cluster(bars + 8 * BD1, 1);
                            flag_signal_relaxed(F_O + mt * 4 + (j >> 1));
                        }
                    }
                };

                l0 = 0.f; l1 = 0.f;
                {
                    turn_wait();
                    uint32_t stk = issue_s();
                    turn_pass();
                    wgmma_wait<0>();
                    fence_regs(s);
                    release(stk);
                    softmax(true);
                    convert_p();
                }
#pragma unroll 1
                for (int t = 1; t < 8; t++) {
                    const bool first = (t == 4);
                    if (t == 4) {
#pragma unroll
                        for (int i = 0; i < 8; i++) {
                            asm volatile("ld.shared.v4.b32 {%0, %1, %2, %3}, [%4];" : "=r"(q[i][0]), "=r"(q[i][1]), "=r"(q[i][2]), "=r"(q[i][3])
                                         : "r"(mystage + (i * 128 + tid) * 16) : "memory");
                        }
                    }
                    turn_wait();
                    uint32_t stk = issue_s();
                    uint32_t stv = issue_pv(t == 1 || t == 5);
                    turn_pass();
                    wgmma_wait<1>();
                    fence_regs(s);
                    release(stk);
                    softmax(first);
                    asm volatile("{\n.reg .pred p;\nsetp.lt.f32 p, %0, 0fBF800000;\n@p st.shared.f32 [%1], %0;\n}\n" ::"f"(l0 + l1), "r"(mystage) : "memory");
                    wgmma_wait<0>();
                    fence_regs(o);
                    release(stv);
                    if (first) {
                        store_o(lo0, lo1, head0, false);
                    } else {
#pragma unroll
                        for (int jj = 0; jj < 16; jj++) {
                            o[4 * jj] *= a0; o[4 * jj + 1] *= a0; o[4 * jj + 2] *= a1; o[4 * jj + 3] *= a1;
                        }
                    }
                    convert_p();
                }
                {
                    turn_wait();
                    uint32_t stv = issue_pv(false);
                    turn_pass();
                    wgmma_wait<0>();
                    fence_regs(o);
                    release(stv);
                    store_o(l0, l1, head0 + 1, hp == 1);
                }
            }
        }
        TS(0, 4);
        {
            const int kq = j >> 1, n0 = (j & 1) * 320;
            float acc0[96], acc1[64];
            uint32_t st = 0, ph = 0, prev = 0;
            for (int i = 0; i < 16; i++) {
                mbar_wait(bars + 8 * (B2F + st), ph);
                if (i == 0) TS(0, 5);
                const uint32_t buf = base + st * P2_STAGE;
                wgmma_fence();
#pragma unroll
                for (int k = 0; k < 4; k++) {
                    uint64_t da = make_desc(buf + wg * 8192 + k * 32, 16, 1024, 1);
                    wgmma_ss_n192_t1(acc0, da, make_desc(buf + 16384 + k * 2048, 8192, 1024, 1), (i | k) != 0);
                    wgmma_ss_n128_t1(acc1, da, make_desc(buf + 16384 + 3 * 8192 + k * 2048, 8192, 1024, 1), (i | k) != 0);
                }
                wgmma_commit();
                if (i > 0) { wgmma_wait<1>(); arrive_both(bars + 8 * (B2E + prev)); }
                prev = st;
                if (++st == 4) { st = 0; ph ^= 1; }
            }
            wgmma_wait<0>();
            fence_regs(acc0); fence_regs(acc1);
            TS(0, 6);
            bar_sync(5, 256);
            TS(4, 0);
            const uint32_t stg = base + wg * 40960;
            const int mi = lane >> 3;
            const int row = warp * 16 + (mi & 1) * 8 + (lane & 7);
#pragma unroll
            for (int jj = 0; jj < 24; jj += 2) {
                const int grp = jj + (mi >> 1);
                stmatrix_x4(stg + (grp >> 3) * 8192 + row * 128 + (((grp & 7) ^ (row & 7)) << 4),
                            pack_bf16(acc0[4 * jj], acc0[4 * jj + 1]), pack_bf16(acc0[4 * jj + 2], acc0[4 * jj + 3]),
                            pack_bf16(acc0[4 * jj + 4], acc0[4 * jj + 5]), pack_bf16(acc0[4 * jj + 6], acc0[4 * jj + 7]));
            }
#pragma unroll
            for (int jj = 0; jj < 16; jj += 2) {
                const int grp = jj + (mi >> 1);
                stmatrix_x4(stg + (3 + (grp >> 3)) * 8192 + row * 128 + (((grp & 7) ^ (row & 7)) << 4),
                            pack_bf16(acc1[4 * jj], acc1[4 * jj + 1]), pack_bf16(acc1[4 * jj + 2], acc1[4 * jj + 3]),
                            pack_bf16(acc1[4 * jj + 4], acc1[4 * jj + 5]), pack_bf16(acc1[4 * jj + 6], acc1[4 * jj + 7]));
            }
            TS(4, 1);
            fence_proxy_async();
            bar_sync(1 + wg, 128);
            TS(4, 2);
            if (tid == 0) {
#pragma unroll
                for (int c = 0; c < 5; c++) tma_store_2d(&tm.part_st, stg + c * 8192, n0 + c * 64, kq * S_LEN + m0 + wg * 64);
                tma_store_commit();
                TS(4, 3);
                tma_store_wait<0>();
                TS(4, 4);
                mbar_arrive_cluster(bars + 8 * BD2, 0);
                mbar_arrive_cluster(bars + 8 * BD2, 1);
                flag_signal_relaxed(F_P + mt);
            }
        }
        TS(0, 7);
        {
            uint2 xr[2][5];
#pragma unroll
            for (int rr = 0; rr < 2; rr++)
#pragma unroll
                for (int i = 0; i < 5; i++)
                    xr[rr][i] = __ldg(reinterpret_cast<const uint2*>(x + (size_t)(m0 + j * 16 + cw * 2 + rr) * D_MODEL + (lane + 32 * i) * 4));
            if (threadIdx.x == 0) { flag_wait(F_MODALL, (epoch + 1) * 80); flag_wait(F_P + mt, (epoch + 1) * 16); }
            bar_sync(5, 256);
            TS(0, 8);
            uint2 pr[2][4][5];
            float4 gv[5];
#pragma unroll
            for (int rr = 0; rr < 2; rr++)
#pragma unroll
                for (int s = 0; s < 4; s++)
#pragma unroll
                    for (int i = 0; i < 5; i++)
                        pr[rr][s][i] = ldcg_u2(g_part + ((size_t)s * S_LEN + m0 + j * 16 + cw * 2 + rr) * D_MODEL + (lane + 32 * i) * 4);
#pragma unroll
            for (int i = 0; i < 5; i++) gv[i] = __ldcg(reinterpret_cast<const float4*>(g_mod + 2 * D_MODEL + (lane + 32 * i) * 4));
#pragma unroll
            for (int rr = 0; rr < 2; rr++) {
#pragma unroll
                for (int i = 0; i < 5; i++) {
                    float a0 = (bf16lo(pr[rr][0][i].x) + bf16lo(pr[rr][1][i].x)) + (bf16lo(pr[rr][2][i].x) + bf16lo(pr[rr][3][i].x));
                    float a1 = (bf16hi(pr[rr][0][i].x) + bf16hi(pr[rr][1][i].x)) + (bf16hi(pr[rr][2][i].x) + bf16hi(pr[rr][3][i].x));
                    float a2 = (bf16lo(pr[rr][0][i].y) + bf16lo(pr[rr][1][i].y)) + (bf16lo(pr[rr][2][i].y) + bf16lo(pr[rr][3][i].y));
                    float a3 = (bf16hi(pr[rr][0][i].y) + bf16hi(pr[rr][1][i].y)) + (bf16hi(pr[rr][2][i].y) + bf16hi(pr[rr][3][i].y));
                    xr[rr][i].x = pack_bf16(bf16lo(xr[rr][i].x) + gv[i].x * a0, bf16hi(xr[rr][i].x) + gv[i].y * a1);
                    xr[rr][i].y = pack_bf16(bf16lo(xr[rr][i].y) + gv[i].z * a2, bf16hi(xr[rr][i].y) + gv[i].w * a3);
                    *reinterpret_cast<uint2*>(g_x1 + (size_t)(m0 + j * 16 + cw * 2 + rr) * D_MODEL + (lane + 32 * i) * 4) = xr[rr][i];
                }
            }
            TS(5, 0);
            ln_rows(xr, g_mod + 3 * D_MODEL, g_mod + 4 * D_MODEL, g_h2 + (size_t)(m0 + j * 16 + cw * 2) * D_MODEL, lane);
            TS(5, 1);
            bar_sync(5, 256);
            TS(5, 2);
            if (threadIdx.x == 0) flag_signal(F_H2 + mt);
        }
        TS(0, 9);
        {
            const int f0 = j * 216;
            uint32_t st = 0, ph = 0, prev = 0;
            {
                float acc[128];
                if (wg == 1) bar_sync(6, 256);
                for (int i = 0; i < 10; i++) {
                    mbar_wait(bars + 8 * (B4F + st), ph);
                    if (i == 0) TS(0, 10);
                    const uint32_t buf = base + st * P4_STAGE;
                    wgmma_fence();
#pragma unroll
                    for (int k = 0; k < 4; k++) {
                        uint64_t da = make_desc(buf + wg * 8192 + k * 32, 16, 1024, 1);
                        uint64_t db = make_desc(buf + 16384 + k * 2048, 8192, 1024, 1);
                        wgmma_ss_n256_t1(acc, da, db, (i | k) != 0);
                    }
                    wgmma_commit();
                    if (i == 1 && wg == 0) bar_arrive(6, 256);
                    if (i > 0) { wgmma_wait<1>(); arrive_both(bars + 8 * (B4E + prev)); }
                    prev = st;
                    if (++st == 4) { st = 0; ph ^= 1; }
                }
                wgmma_wait<0>();
                arrive_both(bars + 8 * (B4E + prev));
                fence_regs(acc);
                TS(2, 0);
#pragma unroll
                for (int jj = 0; jj < 16; jj += 2) {
                    const int mi = lane >> 3;
                    const int row = warp * 16 + (mi & 1) * 8 + (lane & 7);
                    const int grp = jj + (mi >> 1);
                    const uint32_t addr = mystage + (grp >> 3) * 8192 + row * 128 + (((grp & 7) ^ (row & 7)) << 4);
                    stmatrix_x4(addr, pack_bf16(silu_mul(acc[4 * jj], acc[64 + 4 * jj]), silu_mul(acc[4 * jj + 1], acc[64 + 4 * jj + 1])),
                                pack_bf16(silu_mul(acc[4 * jj + 2], acc[64 + 4 * jj + 2]), silu_mul(acc[4 * jj + 3], acc[64 + 4 * jj + 3])),
                                pack_bf16(silu_mul(acc[4 * jj + 4], acc[64 + 4 * jj + 4]), silu_mul(acc[4 * jj + 5], acc[64 + 4 * jj + 5])),
                                pack_bf16(silu_mul(acc[4 * jj + 6], acc[64 + 4 * jj + 6]), silu_mul(acc[4 * jj + 7], acc[64 + 4 * jj + 7])));
                }
                fence_proxy_async();
                bar_sync(1 + wg, 128);
                TS(2, 1);
                if (tid == 0) {
                    tma_store_2d(&tm.act_st64, mystage, f0, m0 + wg * 64);
                    tma_store_2d(&tm.act_st64, mystage + 8192, f0 + 64, m0 + wg * 64);
                    tma_store_commit();
                }
                TS(2, 2);
            }
            {
                float acc[92];
                for (int i = 0; i < 10; i++) {
                    mbar_wait(bars + 8 * (B4F + st), ph);
                    const uint32_t buf = base + st * P4_STAGE;
                    wgmma_fence();
#pragma unroll
                    for (int k = 0; k < 4; k++) {
                        uint64_t da = make_desc(buf + wg * 8192 + k * 32, 16, 1024, 1);
                        uint64_t db = make_desc(buf + 16384 + k * 1024, 4096, 512, 2);
                        wgmma_ss_n184_t1(acc, da, db, (i | k) != 0);
                    }
                    wgmma_commit();
                    if (i == 3 && tid == 0) { tma_store_wait<0>(); flag_signal_relaxed(F_A1 + mt); }
                    if (i > 0) { wgmma_wait<1>(); arrive_both(bars + 8 * (B4E + prev)); }
                    prev = st;
                    if (++st == 4) { st = 0; ph ^= 1; }
                }
                wgmma_wait<0>();
                arrive_both(bars + 8 * BD4);
                fence_regs(acc);
                TS(0, 11);
                bar_sync(1 + wg, 128);
                TS(2, 3);
#pragma unroll
                for (int jj = 0; jj < 8; jj += 2) {
                    const int mi = lane >> 3;
                    const int row = warp * 16 + (mi & 1) * 8 + (lane & 7);
                    const int grp = jj + (mi >> 1);
                    const uint32_t addr = mystage + row * 128 + ((grp ^ (row & 7)) << 4);
                    stmatrix_x4(addr, pack_bf16(silu_mul(acc[4 * jj], acc[48 + 4 * jj]), silu_mul(acc[4 * jj + 1], acc[48 + 4 * jj + 1])),
                                pack_bf16(silu_mul(acc[4 * jj + 2], acc[48 + 4 * jj + 2]), silu_mul(acc[4 * jj + 3], acc[48 + 4 * jj + 3])),
                                pack_bf16(silu_mul(acc[4 * jj + 4], acc[48 + 4 * jj + 4]), silu_mul(acc[4 * jj + 5], acc[48 + 4 * jj + 5])),
                                pack_bf16(silu_mul(acc[4 * jj + 6], acc[48 + 4 * jj + 6]), silu_mul(acc[4 * jj + 7], acc[48 + 4 * jj + 7])));
                }
                {
                    const int mi = lane >> 3;
                    const int row = warp * 16 + (mi & 1) * 8 + (lane & 7);
                    const uint32_t addr = mystage + 8192 + row * 48 + (mi >> 1) * 16;
                    stmatrix_x4(addr, pack_bf16(silu_mul(acc[32], acc[80]), silu_mul(acc[33], acc[81])),
                                pack_bf16(silu_mul(acc[34], acc[82]), silu_mul(acc[35], acc[83])),
                                pack_bf16(silu_mul(acc[36], acc[84]), silu_mul(acc[37], acc[85])),
                                pack_bf16(silu_mul(acc[38], acc[86]), silu_mul(acc[39], acc[87])));
                    const uint32_t addr2 = mystage + 8192 + (warp * 16 + ((lane >> 3) & 1) * 8 + (lane & 7)) * 48 + 32;
                    asm volatile("stmatrix.sync.aligned.m8n8.x2.shared.b16 [%0], {%1, %2};" ::"r"(addr2),
                                 "r"(pack_bf16(silu_mul(acc[40], acc[88]), silu_mul(acc[41], acc[89]))),
                                 "r"(pack_bf16(silu_mul(acc[42], acc[90]), silu_mul(acc[43], acc[91]))) : "memory");
                }
                fence_proxy_async();
                bar_sync(1 + wg, 128);
                TS(2, 4);
                if (tid == 0) {
                    tma_store_2d(&tm.act_st64, mystage, f0 + 128, m0 + wg * 64);
                    tma_store_2d(&tm.act_st24, mystage + 8192, f0 + 192, m0 + wg * 64);
                    tma_store_commit();
                    TS(2, 5);
                    tma_store_wait<0>();
                    TS(2, 6);
                    mbar_arrive_cluster(bars + 8 * BD4B, 0);
                    mbar_arrive_cluster(bars + 8 * BD4B, 1);
                    TS(2, 7);
                    flag_signal_relaxed(F_A + mt);
                    TS(2, 8);
                }
            }
        }
        TS(0, 12);
        {
            const int m5 = (p * 2 + (j >> 2)) * 128, n0 = (j & 3) * 160;
            const int nkb = rank == 0 ? 14 : 13;
            float accA[64], accB[16];
            uint32_t st = 0, ph = 0, prev = 0;
            const int cbase = n0 + (int)rank * 80;
            for (int i = 0; i < nkb; i++) {
                mbar_wait(bars + 8 * (B5F + st), ph);
                if (i == 0) TS(0, 13);
                const uint32_t buf = base + st * P5_STAGE;
                wgmma_fence();
#pragma unroll
                for (int k = 0; k < 4; k++) {
                    uint64_t da = make_desc(buf + wg * 8192 + k * 32, 16, 1024, 1);
                    wgmma_ss_n128_t1(accA, da, make_desc(buf + 16384 + k * 2048, 8192, 1024, 1), (i | k) != 0);
                    wgmma_ss_n32_t1(accB, da, make_desc(buf + 32768 + k * 1024, 4096, 512, 2), (i | k) != 0);
                }
                wgmma_commit();
                if (i > 0) {
                    wgmma_wait<1>();
                    if (tid == 0) mbar_arrive(bars + 8 * (B5E + prev));
                }
                prev = st;
                if (++st == 5) { st = 0; ph ^= 1; }
            }
            uint4 xv[5];
            float2 gbv[10];
#pragma unroll
            for (int it = 0; it < 5; it++) {
                const int idx = it * 256 + (int)threadIdx.x;
                const int row = idx / 10, ch = idx - row * 10;
                xv[it] = __ldcg(reinterpret_cast<const uint4*>(g_x1 + (size_t)(m5 + row) * D_MODEL + cbase + ch * 8));
            }
#pragma unroll
            for (int jj = 0; jj < 10; jj++) gbv[jj] = __ldcg(reinterpret_cast<const float2*>(g_mod + 5 * D_MODEL + cbase + jj * 8 + (lane & 3) * 2));
            wgmma_wait<0>();
            fence_regs(accA); fence_regs(accB);
            float acc[80];
#pragma unroll
            for (int i = 0; i < 64; i++) acc[i] = accA[i];
#pragma unroll
            for (int i = 0; i < 16; i++) acc[64 + i] = accB[i];
            TS(0, 14);
            constexpr uint32_t XBUF = 5 * P5_STAGE;
            mbar_wait(bars + 8 * BD4B, 0);
            TS(3, 0);
            {
                const uint32_t dst = mapa(base + XBUF, rank ^ 1) + wg * 20480 + tid * 16;
                const uint32_t rbar = mapa(bars + 8 * BX, rank ^ 1);
                if (rank == 0) {
#pragma unroll
                    for (int i = 0; i < 10; i++)
                        asm volatile("st.async.shared::cluster.mbarrier::complete_tx::bytes.v4.f32 [%0], {%1, %2, %3, %4}, [%5];" ::"r"(dst + i * 2048),
                                     "f"(acc[40 + 4 * i]), "f"(acc[40 + 4 * i + 1]), "f"(acc[40 + 4 * i + 2]), "f"(acc[40 + 4 * i + 3]), "r"(rbar) : "memory");
                } else {
#pragma unroll
                    for (int i = 0; i < 10; i++)
                        asm volatile("st.async.shared::cluster.mbarrier::complete_tx::bytes.v4.f32 [%0], {%1, %2, %3, %4}, [%5];" ::"r"(dst + i * 2048),
                                     "f"(acc[4 * i]), "f"(acc[4 * i + 1]), "f"(acc[4 * i + 2]), "f"(acc[4 * i + 3]), "r"(rbar) : "memory");
                }
            }
            TS(3, 1);
            mbar_wait(bars + 8 * BX, 0);
            TS(3, 2);
            {
                bar_sync(5, 256);
                const uint32_t tile = base;
                TS(3, 3);
#pragma unroll
                for (int jj = 0; jj < 10; jj += 2) {
                    float4 o0, o1;
                    asm volatile("ld.shared.v4.f32 {%0, %1, %2, %3}, [%4];" : "=f"(o0.x), "=f"(o0.y), "=f"(o0.z), "=f"(o0.w) : "r"(base + XBUF + wg * 20480 + tid * 16 + jj * 2048));
                    asm volatile("ld.shared.v4.f32 {%0, %1, %2, %3}, [%4];" : "=f"(o1.x), "=f"(o1.y), "=f"(o1.z), "=f"(o1.w) : "r"(base + XBUF + wg * 20480 + tid * 16 + (jj + 1) * 2048));
                    const float2 g0 = gbv[jj], g1 = gbv[jj + 1];
                    float a[8];
#pragma unroll
                    for (int ee = 0; ee < 8; ee++) a[ee] = rank == 0 ? acc[4 * jj + ee] : acc[40 + 4 * jj + ee];
                    const int mi = lane >> 3;
                    const int row = wg * 64 + warp * 16 + (mi & 1) * 8 + (lane & 7);
                    const uint32_t addr = tile + row * 176 + (jj + (mi >> 1)) * 16;
                    stmatrix_x4(addr, pack_bf16(g0.x * bf16_round(a[0] + o0.x), g0.y * bf16_round(a[1] + o0.y)),
                                pack_bf16(g0.x * bf16_round(a[2] + o0.z), g0.y * bf16_round(a[3] + o0.w)),
                                pack_bf16(g1.x * bf16_round(a[4] + o1.x), g1.y * bf16_round(a[5] + o1.y)),
                                pack_bf16(g1.x * bf16_round(a[6] + o1.z), g1.y * bf16_round(a[7] + o1.w)));
                }
                TS(3, 4);
                bar_sync(5, 256);
                TS(3, 5);
#pragma unroll
                for (int it = 0; it < 5; it++) {
                    const int idx = it * 256 + (int)threadIdx.x;
                    const int row = idx / 10, ch = idx - row * 10;
                    uint4 tv;
                    asm volatile("ld.shared.v4.b32 {%0, %1, %2, %3}, [%4];" : "=r"(tv.x), "=r"(tv.y), "=r"(tv.z), "=r"(tv.w) : "r"(tile + row * 176 + ch * 16));
                    uint4 r;
                    r.x = pack_bf16(bf16lo(xv[it].x) + bf16lo(tv.x), bf16hi(xv[it].x) + bf16hi(tv.x));
                    r.y = pack_bf16(bf16lo(xv[it].y) + bf16lo(tv.y), bf16hi(xv[it].y) + bf16hi(tv.y));
                    r.z = pack_bf16(bf16lo(xv[it].z) + bf16lo(tv.z), bf16hi(xv[it].z) + bf16hi(tv.z));
                    r.w = pack_bf16(bf16lo(xv[it].w) + bf16lo(tv.w), bf16hi(xv[it].w) + bf16hi(tv.w));
                    *reinterpret_cast<uint4*>(out + (size_t)(m5 + row) * D_MODEL + cbase + ch * 8) = r;
                }
            }
            TS(0, 15);
            if (threadIdx.x == 0) {
                const unsigned old = atomicAdd(&g_exit, 1u);
                if (old == (epoch + 1) * 128u - 1u) {
                    asm volatile("st.volatile.global.u32 [%0], %1;" ::"l"(&g_epoch), "r"(epoch + 1) : "memory");
                }
            }
            asm volatile("barrier.cluster.arrive.relaxed.aligned;\n barrier.cluster.wait.aligned;" ::: "memory");
        }
    }
}

typedef CUresult (*PFN_encodeTiled)(CUtensorMap*, CUtensorMapDataType, cuuint32_t, void*, const cuuint64_t*, const cuuint64_t*,
                                    const cuuint32_t*, const cuuint32_t*, CUtensorMapInterleave, CUtensorMapSwizzle,
                                    CUtensorMapL2promotion, CUtensorMapFloatOOBfill);

static PFN_encodeTiled get_encode() {
    static PFN_encodeTiled fn = nullptr;
    if (!fn) {
        void* p = nullptr;
        cudaDriverEntryPointQueryResult qr;
        cudaGetDriverEntryPoint("cuTensorMapEncodeTiled", &p, cudaEnableDefault, &qr);
        fn = (PFN_encodeTiled)p;
    }
    return fn;
}

static CUtensorMap make_map(const void* ptr, uint64_t rows, uint64_t cols, uint32_t box_rows, uint32_t box_cols, CUtensorMapSwizzle swz) {
    CUtensorMap m;
    cuuint64_t dims[2] = {cols, rows};
    cuuint64_t strides[1] = {cols * 2};
    cuuint32_t box[2] = {box_cols, box_rows};
    cuuint32_t es[2] = {1, 1};
    get_encode()(&m, CU_TENSOR_MAP_DATA_TYPE_BFLOAT16, 2, const_cast<void*>(ptr), dims, strides, box, es, CU_TENSOR_MAP_INTERLEAVE_NONE,
                 swz, CU_TENSOR_MAP_L2_PROMOTION_L2_256B, CU_TENSOR_MAP_FLOAT_OOB_FILL_NONE);
    return m;
}

extern "C" void kernel_launch(void* const* d_in, const int* in_sizes, int n_in, void* d_out, int out_size) {
    (void)in_sizes; (void)n_in; (void)out_size;
    const __nv_bfloat16* x = (const __nv_bfloat16*)d_in[0];
    const __nv_bfloat16* kc = (const __nv_bfloat16*)d_in[1];
    const __nv_bfloat16* vc = (const __nv_bfloat16*)d_in[2];
    const __nv_bfloat16* wq = (const __nv_bfloat16*)d_in[3];
    const __nv_bfloat16* wo = (const __nv_bfloat16*)d_in[4];
    const __nv_bfloat16* wg = (const __nv_bfloat16*)d_in[6];
    const __nv_bfloat16* wu = (const __nv_bfloat16*)d_in[7];
    const __nv_bfloat16* wd = (const __nv_bfloat16*)d_in[8];
    const __nv_bfloat16* c = (const __nv_bfloat16*)d_in[9];
    const __nv_bfloat16* wmod = (const __nv_bfloat16*)d_in[10];
    __nv_bfloat16* out = (__nv_bfloat16*)d_out;

    static bool init = false;
    static void *p_h, *p_o, *p_x1, *p_h2, *p_act, *p_part;
    if (!init) {
        cudaFuncSetAttribute(mega_kernel, cudaFuncAttributeMaxDynamicSharedMemorySize, SM_TOTAL);
        cudaGetSymbolAddress(&p_h, g_h);
        cudaGetSymbolAddress(&p_o, g_o);
        cudaGetSymbolAddress(&p_x1, g_x1);
        cudaGetSymbolAddress(&p_h2, g_h2);
        cudaGetSymbolAddress(&p_act, g_act);
        cudaGetSymbolAddress(&p_part, g_part);
        init = true;
    }
    const CUtensorMapSwizzle S128 = CU_TENSOR_MAP_SWIZZLE_128B, S64 = CU_TENSOR_MAP_SWIZZLE_64B;
    Maps tm;
    tm.h = make_map(p_h, S_LEN, D_MODEL, 128, 64, S128);
    tm.wq = make_map(wq, D_MODEL, N_HEADS * D_HEAD, 64, 64, S128);
    tm.k = make_map(kc, N_HEADS * S_KV, D_HEAD, 128, 64, S128);
    tm.v = make_map(vc, N_HEADS * S_KV, D_HEAD, 128, 64, S128);
    tm.o_st = make_map(p_o, S_LEN, N_HEADS * D_HEAD, 64, 64, S128);
    tm.o_a = make_map(p_o, S_LEN, N_HEADS * D_HEAD, 128, 64, S128);
    tm.wo = make_map(wo, N_HEADS * D_HEAD, D_MODEL, 64, 64, S128);
    tm.part_st = make_map(p_part, 4 * S_LEN, D_MODEL, 64, 64, S128);
    tm.h2 = make_map(p_h2, S_LEN, D_MODEL, 128, 64, S128);
    tm.g128 = make_map(wg, D_MODEL, D_FF, 64, 64, S128);
    tm.u128 = make_map(wu, D_MODEL, D_FF, 64, 64, S128);
    tm.g64 = make_map(wg, D_MODEL, D_FF, 64, 32, S64);
    tm.u64 = make_map(wu, D_MODEL, D_FF, 64, 32, S64);
    tm.act_st64 = make_map(p_act, S_LEN, D_FF, 64, 64, S128);
    tm.act_st24 = make_map(p_act, S_LEN, D_FF, 64, 24, CU_TENSOR_MAP_SWIZZLE_NONE);
    tm.act_a = make_map(p_act, S_LEN, D_FF, 128, 64, S128);
    tm.wd = make_map(wd, D_FF, D_MODEL, 64, 64, S128);
    tm.wd32 = make_map(wd, D_FF, D_MODEL, 64, 32, S64);

    cudaLaunchConfig_t cfg = {};
    cfg.gridDim = dim3(128);
    cfg.blockDim = dim3(384);
    cfg.dynamicSmemBytes = SM_TOTAL;
    cfg.stream = cudaStreamPerThread;
    cfg.attrs = nullptr;
    cfg.numAttrs = 0;
    cudaLaunchKernelEx(&cfg, mega_kernel, tm, x, c, wmod, out, (const void*)wo, (const void*)wg, (const void*)wu, (const void*)wd);
}
```

```cpp
#include <cuda_runtime.h>
#include <cuda_bf16.h>
#include <cuda.h>
#include <stdint.h>

__device__ __forceinline__ uint32_t smem_u32(const void* p) { return (uint32_t)__cvta_generic_to_shared(p); }

__device__ __forceinline__ void mbar_init(uint32_t bar, uint32_t count) {
    asm volatile("mbarrier.init.shared::cta.b64 [%0], %1;" ::"r"(bar), "r"(count) : "memory");
}
__device__ __forceinline__ void mbar_expect_tx(uint32_t bar, uint32_t bytes) {
    asm volatile("mbarrier.arrive.expect_tx.shared::cta.b64 _, [%0], %1;" ::"r"(bar), "r"(bytes) : "memory");
}
__device__ __forceinline__ void mbar_arrive(uint32_t bar) {
    asm volatile("mbarrier.arrive.shared::cta.b64 _, [%0];" ::"r"(bar) : "memory");
}
__device__ __forceinline__ void mbar_arrive_cluster(uint32_t bar, uint32_t cta) {
    asm volatile(
        "{\n.reg .b32 ra;\n"
        "mapa.shared::cluster.u32 ra, %0, %1;\n"
        "mbarrier.arrive.shared::cluster.b64 _, [ra];\n}\n" ::"r"(bar), "r"(cta)
        : "memory");
}
__device__ __forceinline__ bool mbar_try_wait(uint32_t bar, uint32_t parity) {
    uint32_t ok;
    asm volatile(
        "{\n.reg .pred p;\n"
        "mbarrier.try_wait.parity.shared::cta.b64 p, [%1], %2;\n"
        "selp.u32 %0, 1, 0, p;\n}\n"
        : "=r"(ok)
        : "r"(bar), "r"(parity)
        : "memory");
    return ok != 0;
}
__device__ __forceinline__ bool mbar_try_wait_cluster(uint32_t bar, uint32_t parity) {
    uint32_t ok;
    asm volatile(
        "{\n.reg .pred p;\n"
        "mbarrier.try_wait.parity.shared::cta.b64 p, [%1], %2;\n"
        "selp.u32 %0, 1, 0, p;\n}\n"
        : "=r"(ok)
        : "r"(bar), "r"(parity)
        : "memory");
    return ok != 0;
}
__device__ volatile int g_abort = 0;
__device__ __forceinline__ void mbar_wait(uint32_t bar, uint32_t parity) {
    asm volatile(
        "{\n.reg .pred p;\n.reg .u32 n;\n"
        "mov.u32 n, 0;\n"
        "WAIT_LOOP:\n"
        "mbarrier.try_wait.parity.shared::cta.b64 p, [%0], %1;\n"
        "@p bra WAIT_DONE;\n"
        "add.u32 n, n, 1;\n"
        "setp.lt.u32 p, n, 16777216;\n"
        "@p bra WAIT_LOOP;\n"
        "WAIT_DONE:\n}\n" ::"r"(bar), "r"(parity) : "memory");
}
__device__ __forceinline__ void mbar_wait_cluster(uint32_t bar, uint32_t parity) { mbar_wait(bar, parity); }
__device__ __forceinline__ void fence_mbar_init() { asm volatile("fence.mbarrier_init.release.cluster;" ::: "memory"); }
__device__ __forceinline__ void fence_proxy_async() { asm volatile("fence.proxy.async.shared::cta;" ::: "memory"); }
__device__ __forceinline__ void fence_proxy_async_all() { asm volatile("fence.proxy.async;" ::: "memory"); }
__device__ __forceinline__ void cluster_arrive() { asm volatile("barrier.cluster.arrive.release.aligned;" ::: "memory"); }
__device__ __forceinline__ void cluster_wait() { asm volatile("barrier.cluster.wait.acquire.aligned;" ::: "memory"); }
__device__ __forceinline__ void cluster_sync() { cluster_arrive(); cluster_wait(); }
__device__ __forceinline__ uint32_t cluster_ctarank() {
    uint32_t r;
    asm volatile("mov.u32 %0, %%cluster_ctarank;" : "=r"(r));
    return r;
}
__device__ __forceinline__ void bar_sync(int id, int n) { asm volatile("bar.sync %0, %1;" ::"r"(id), "r"(n) : "memory"); }
__device__ __forceinline__ void bar_arrive(int id, int n) { asm volatile("bar.arrive %0, %1;" ::"r"(id), "r"(n) : "memory"); }
__device__ __forceinline__ void pdl_wait() { asm volatile("griddepcontrol.wait;" ::: "memory"); }
__device__ __forceinline__ void pdl_launch() { asm volatile("griddepcontrol.launch_dependents;" ::: "memory"); }

__device__ __forceinline__ void tma_prefetch_desc(const CUtensorMap* m) {
    asm volatile("prefetch.tensormap [%0];" ::"l"(m) : "memory");
}
__device__ __forceinline__ void tma_load_2d(uint32_t dst, const CUtensorMap* m, int c0, int c1, uint32_t bar) {
    asm volatile(
        "cp.async.bulk.tensor.2d.shared::cluster.global.mbarrier::complete_tx::bytes [%0], [%1, {%3, %4}], [%2];"
        ::"r"(dst), "l"(m), "r"(bar), "r"(c0), "r"(c1)
        : "memory");
}
__device__ __forceinline__ void tma_load_2d_mc(uint32_t dst, const CUtensorMap* m, int c0, int c1, uint32_t bar, uint16_t mask) {
    asm volatile(
        "cp.async.bulk.tensor.2d.shared::cluster.global.mbarrier::complete_tx::bytes.multicast::cluster [%0], [%1, {%3, %4}], [%2], %5;"
        ::"r"(dst), "l"(m), "r"(bar), "r"(c0), "r"(c1), "h"(mask)
        : "memory");
}
__device__ __forceinline__ void tma_store_2d(const CUtensorMap* m, uint32_t src, int c0, int c1) {
    asm volatile("cp.async.bulk.tensor.2d.global.shared::cta.bulk_group [%0, {%2, %3}], [%1];"
                 ::"l"(m), "r"(src), "r"(c0), "r"(c1)
                 : "memory");
}
__device__ __forceinline__ void tma_store_commit() { asm volatile("cp.async.bulk.commit_group;" ::: "memory"); }
template <int N> __device__ __forceinline__ void tma_store_wait_read() {
    asm volatile("cp.async.bulk.wait_group.read %0;" ::"n"(N) : "memory");
}
template <int N> __device__ __forceinline__ void tma_store_wait() {
    asm volatile("cp.async.bulk.wait_group %0;" ::"n"(N) : "memory");
}

__device__ __forceinline__ void wgmma_fence() { asm volatile("wgmma.fence.sync.aligned;" ::: "memory"); }
__device__ __forceinline__ void wgmma_commit() { asm volatile("wgmma.commit_group.sync.aligned;" ::: "memory"); }
template <int N> __device__ __forceinline__ void wgmma_wait() {
    asm volatile("wgmma.wait_group.sync.aligned %0;" ::"n"(N) : "memory");
}
template <int R> __device__ __forceinline__ void reg_alloc() { asm volatile("setmaxnreg.inc.sync.aligned.u32 %0;" ::"n"(R)); }
template <int R> __device__ __forceinline__ void reg_dealloc() { asm volatile("setmaxnreg.dec.sync.aligned.u32 %0;" ::"n"(R)); }

template <int N> __device__ __forceinline__ void fence_regs(float (&r)[N]) {
#pragma unroll
    for (int i = 0; i < N; i++) asm volatile("" : "+f"(r[i])::"memory");
}
template <int N> __device__ __forceinline__ void fence_regs_u(uint32_t (&r)[N][4]) {
#pragma unroll
    for (int i = 0; i < N; i++) {
#pragma unroll
        for (int j = 0; j < 4; j++) asm volatile("" : "+r"(r[i][j])::"memory");
    }
}

__device__ __forceinline__ uint64_t make_desc(uint32_t addr, uint32_t lbo_bytes, uint32_t sbo_bytes, uint32_t swz) {
    return (uint64_t)((addr & 0x3FFFF) >> 4) | ((uint64_t)(lbo_bytes >> 4) << 16) | ((uint64_t)(sbo_bytes >> 4) << 32) |
           ((uint64_t)swz << 62);
}

__device__ __forceinline__ uint32_t pack_bf16(float lo, float hi) {
    uint32_t r;
    asm("cvt.rn.bf16x2.f32 %0, %1, %2;" : "=r"(r) : "f"(hi), "f"(lo));
    return r;
}
__device__ __forceinline__ float bf16_round(float x) { return __bfloat162float(__float2bfloat16_rn(x)); }
__device__ __forceinline__ float bf16lo(uint32_t v) { return __uint_as_float(v << 16); }
__device__ __forceinline__ float bf16hi(uint32_t v) { return __uint_as_float(v & 0xffff0000u); }
__device__ __forceinline__ float ex2(float x) {
    float y;
    asm("ex2.approx.ftz.f32 %0, %1;" : "=f"(y) : "f"(x));
    return y;
}
__device__ __forceinline__ void stmatrix_x4(uint32_t addr, uint32_t r0, uint32_t r1, uint32_t r2, uint32_t r3) {
    asm volatile("stmatrix.sync.aligned.m8n8.x4.shared.b16 [%0], {%1, %2, %3, %4};" ::"r"(addr), "r"(r0), "r"(r1), "r"(r2), "r"(r3)
                 : "memory");
}
__device__ __forceinline__ uint32_t mapa(uint32_t addr, uint32_t cta) {
    uint32_t r;
    asm volatile("mapa.shared::cluster.u32 %0, %1, %2;" : "=r"(r) : "r"(addr), "r"(cta));
    return r;
}
__device__ __forceinline__ void st_cluster_v2(uint32_t addr, float a, float b) {
    asm volatile("st.shared::cluster.v2.f32 [%0], {%1, %2};" ::"r"(addr), "f"(a), "f"(b) : "memory");
}
__device__ __forceinline__ void wgmma_ss_n256_t1(float (&d)[128], uint64_t descA, uint64_t descB, int scaleD) {
    asm volatile("{\n.reg .pred p;\n"
        "setp.ne.b32 p, %130, 0;\n"
        "wgmma.mma_async.sync.aligned.m64n256k16.f32.bf16.bf16 "
        "{%0, %1, %2, %3, %4, %5, %6, %7, %8, %9, %10, %11, %12, %13, %14, %15, "
        "%16, %17, %18, %19, %20, %21, %22, %23, %24, %25, %26, %27, %28, %29, %30, %31, "
        "%32, %33, %34, %35, %36, %37, %38, %39, %40, %41, %42, %43, %44, %45, %46, %47, "
        "%48, %49, %50, %51, %52, %53, %54, %55, %56, %57, %58, %59, %60, %61, %62, %63, "
        "%64, %65, %66, %67, %68, %69, %70, %71, %72, %73, %74, %75, %76, %77, %78, %79, "
        "%80, %81, %82, %83, %84, %85, %86, %87, %88, %89, %90, %91, %92, %93, %94, %95, "
        "%96, %97, %98, %99, %100, %101, %102, %103, %104, %105, %106, %107, %108, %109, %110, %111, "
        "%112, %113, %114, %115, %116, %117, %118, %119, %120, %121, %122, %123, %124, %125, %126, %127}, "
        "%128, %129, p, 1, 1, 0, 1;\n}\n"
        :
          "+f"(d[0]), "+f"(d[1]), "+f"(d[2]), "+f"(d[3]), "+f"(d[4]), "+f"(d[5]), "+f"(d[6]), "+f"(d[7]),
          "+f"(d[8]), "+f"(d[9]), "+f"(d[10]), "+f"(d[11]), "+f"(d[12]), "+f"(d[13]), "+f"(d[14]), "+f"(d[15]),
          "+f"(d[16]), "+f"(d[17]), "+f"(d[18]), "+f"(d[19]), "+f"(d[20]), "+f"(d[21]), "+f"(d[22]), "+f"(d[23]),
          "+f"(d[24]), "+f"(d[25]), "+f"(d[26]), "+f"(d[27]), "+f"(d[28]), "+f"(d[29]), "+f"(d[30]), "+f"(d[31]),
          "+f"(d[32]), "+f"(d[33]), "+f"(d[34]), "+f"(d[35]), "+f"(d[36]), "+f"(d[37]), "+f"(d[38]), "+f"(d[39]),
          "+f"(d[40]), "+f"(d[41]), "+f"(d[42]), "+f"(d[43]), "+f"(d[44]), "+f"(d[45]), "+f"(d[46]), "+f"(d[47]),
          "+f"(d[48]), "+f"(d[49]), "+f"(d[50]), "+f"(d[51]), "+f"(d[52]), "+f"(d[53]), "+f"(d[54]), "+f"(d[55]),
          "+f"(d[56]), "+f"(d[57]), "+f"(d[58]), "+f"(d[59]), "+f"(d[60]), "+f"(d[61]), "+f"(d[62]), "+f"(d[63]),
          "+f"(d[64]), "+f"(d[65]), "+f"(d[66]), "+f"(d[67]), "+f"(d[68]), "+f"(d[69]), "+f"(d[70]), "+f"(d[71]),
          "+f"(d[72]), "+f"(d[73]), "+f"(d[74]), "+f"(d[75]), "+f"(d[76]), "+f"(d[77]), "+f"(d[78]), "+f"(d[79]),
          "+f"(d[80]), "+f"(d[81]), "+f"(d[82]), "+f"(d[83]), "+f"(d[84]), "+f"(d[85]), "+f"(d[86]), "+f"(d[87]),
          "+f"(d[88]), "+f"(d[89]), "+f"(d[90]), "+f"(d[91]), "+f"(d[92]), "+f"(d[93]), "+f"(d[94]), "+f"(d[95]),
          "+f"(d[96]), "+f"(d[97]), "+f"(d[98]), "+f"(d[99]), "+f"(d[100]), "+f"(d[101]), "+f"(d[102]), "+f"(d[103]),
          "+f"(d[104]), "+f"(d[105]), "+f"(d[106]), "+f"(d[107]), "+f"(d[108]), "+f"(d[109]), "+f"(d[110]), "+f"(d[111]),
          "+f"(d[112]), "+f"(d[113]), "+f"(d[114]), "+f"(d[115]), "+f"(d[116]), "+f"(d[117]), "+f"(d[118]), "+f"(d[119]),
          "+f"(d[120]), "+f"(d[121]), "+f"(d[122]), "+f"(d[123]), "+f"(d[124]), "+f"(d[125]), "+f"(d[126]), "+f"(d[127])
        : "l"(descA), "l"(descB), "r"(scaleD));
}

__device__ __forceinline__ void wgmma_rs_n128_t0(float (&d)[64], const uint32_t (&a)[4], uint64_t descB, int scaleD) {
    asm volatile("{\n.reg .pred p;\n"
        "setp.ne.b32 p, %69, 0;\n"
        "wgmma.mma_async.sync.aligned.m64n128k16.f32.bf16.bf16 "
        "{%0, %1, %2, %3, %4, %5, %6, %7, %8, %9, %10, %11, %12, %13, %14, %15, "
        "%16, %17, %18, %19, %20, %21, %22, %23, %24, %25, %26, %27, %28, %29, %30, %31, "
        "%32, %33, %34, %35, %36, %37, %38, %39, %40, %41, %42, %43, %44, %45, %46, %47, "
        "%48, %49, %50, %51, %52, %53, %54, %55, %56, %57, %58, %59, %60, %61, %62, %63}, "
        "{%64, %65, %66, %67}, %68, p, 1, 1, 0;\n}\n"
        :
          "+f"(d[0]), "+f"(d[1]), "+f"(d[2]), "+f"(d[3]), "+f"(d[4]), "+f"(d[5]), "+f"(d[6]), "+f"(d[7]),
          "+f"(d[8]), "+f"(d[9]), "+f"(d[10]), "+f"(d[11]), "+f"(d[12]), "+f"(d[13]), "+f"(d[14]), "+f"(d[15]),
          "+f"(d[16]), "+f"(d[17]), "+f"(d[18]), "+f"(d[19]), "+f"(d[20]), "+f"(d[21]), "+f"(d[22]), "+f"(d[23]),
          "+f"(d[24]), "+f"(d[25]), "+f"(d[26]), "+f"(d[27]), "+f"(d[28]), "+f"(d[29]), "+f"(d[30]), "+f"(d[31]),
          "+f"(d[32]), "+f"(d[33]), "+f"(d[34]), "+f"(d[35]), "+f"(d[36]), "+f"(d[37]), "+f"(d[38]), "+f"(d[39]),
          "+f"(d[40]), "+f"(d[41]), "+f"(d[42]), "+f"(d[43]), "+f"(d[44]), "+f"(d[45]), "+f"(d[46]), "+f"(d[47]),
          "+f"(d[48]), "+f"(d[49]), "+f"(d[50]), "+f"(d[51]), "+f"(d[52]), "+f"(d[53]), "+f"(d[54]), "+f"(d[55]),
          "+f"(d[56]), "+f"(d[57]), "+f"(d[58]), "+f"(d[59]), "+f"(d[60]), "+f"(d[61]), "+f"(d[62]), "+f"(d[63])
        : "r"(a[0]), "r"(a[1]), "r"(a[2]), "r"(a[3]), "l"(descB), "r"(scaleD));
}

__device__ __forceinline__ void wgmma_rs_n128_t0_z(float (&d)[64], const uint32_t (&a)[4], uint64_t descB) {
    asm volatile("{\n.reg .pred p;\n"
        "setp.ne.b32 p, 0, 0;\n"
        "wgmma.mma_async.sync.aligned.m64n128k16.f32.bf16.bf16 "
        "{%0, %1, %2, %3, %4, %5, %6, %7, %8, %9, %10, %11, %12, %13, %14, %15, "
        "%16, %17, %18, %19, %20, %21, %22, %23, %24, %25, %26, %27, %28, %29, %30, %31, "
        "%32, %33, %34, %35, %36, %37, %38, %39, %40, %41, %42, %43, %44, %45, %46, %47, "
        "%48, %49, %50, %51, %52, %53, %54, %55, %56, %57, %58, %59, %60, %61, %62, %63}, "
        "{%64, %65, %66, %67}, %68, p, 1, 1, 0;\n}\n"
        :
          "=f"(d[0]), "=f"(d[1]), "=f"(d[2]), "=f"(d[3]), "=f"(d[4]), "=f"(d[5]), "=f"(d[6]), "=f"(d[7]),
          "=f"(d[8]), "=f"(d[9]), "=f"(d[10]), "=f"(d[11]), "=f"(d[12]), "=f"(d[13]), "=f"(d[14]), "=f"(d[15]),
          "=f"(d[16]), "=f"(d[17]), "=f"(d[18]), "=f"(d[19]), "=f"(d[20]), "=f"(d[21]), "=f"(d[22]), "=f"(d[23]),
          "=f"(d[24]), "=f"(d[25]), "=f"(d[26]), "=f"(d[27]), "=f"(d[28]), "=f"(d[29]), "=f"(d[30]), "=f"(d[31]),
          "=f"(d[32]), "=f"(d[33]), "=f"(d[34]), "=f"(d[35]), "=f"(d[36]), "=f"(d[37]), "=f"(d[38]), "=f"(d[39]),
          "=f"(d[40]), "=f"(d[41]), "=f"(d[42]), "=f"(d[43]), "=f"(d[44]), "=f"(d[45]), "=f"(d[46]), "=f"(d[47]),
          "=f"(d[48]), "=f"(d[49]), "=f"(d[50]), "=f"(d[51]), "=f"(d[52]), "=f"(d[53]), "=f"(d[54]), "=f"(d[55]),
          "=f"(d[56]), "=f"(d[57]), "=f"(d[58]), "=f"(d[59]), "=f"(d[60]), "=f"(d[61]), "=f"(d[62]), "=f"(d[63])
        : "r"(a[0]), "r"(a[1]), "r"(a[2]), "r"(a[3]), "l"(descB));
}

__device__ __forceinline__ void wgmma_rs_n128_t1(float (&d)[64], const uint32_t (&a)[4], uint64_t descB, int scaleD) {
    asm volatile("{\n.reg .pred p;\n"
        "setp.ne.b32 p, %69, 0;\n"
        "wgmma.mma_async.sync.aligned.m64n128k16.f32.bf16.bf16 "
        "{%0, %1, %2, %3, %4, %5, %6, %7, %8, %9, %10, %11, %12, %13, %14, %15, "
        "%16, %17, %18, %19, %20, %21, %22, %23, %24, %25, %26, %27, %28, %29, %30, %31, "
        "%32, %33, %34, %35, %36, %37, %38, %39, %40, %41, %42, %43, %44, %45, %46, %47, "
        "%48, %49, %50, %51, %52, %53, %54, %55, %56, %57, %58, %59, %60, %61, %62, %63}, "
        "{%64, %65, %66, %67}, %68, p, 1, 1, 1;\n}\n"
        :
          "+f"(d[0]), "+f"(d[1]), "+f"(d[2]), "+f"(d[3]), "+f"(d[4]), "+f"(d[5]), "+f"(d[6]), "+f"(d[7]),
          "+f"(d[8]), "+f"(d[9]), "+f"(d[10]), "+f"(d[11]), "+f"(d[12]), "+f"(d[13]), "+f"(d[14]), "+f"(d[15]),
          "+f"(d[16]), "+f"(d[17]), "+f"(d[18]), "+f"(d[19]), "+f"(d[20]), "+f"(d[21]), "+f"(d[22]), "+f"(d[23]),
          "+f"(d[24]), "+f"(d[25]), "+f"(d[26]), "+f"(d[27]), "+f"(d[28]), "+f"(d[29]), "+f"(d[30]), "+f"(d[31]),
          "+f"(d[32]), "+f"(d[33]), "+f"(d[34]), "+f"(d[35]), "+f"(d[36]), "+f"(d[37]), "+f"(d[38]), "+f"(d[39]),
          "+f"(d[40]), "+f"(d[41]), "+f"(d[42]), "+f"(d[43]), "+f"(d[44]), "+f"(d[45]), "+f"(d[46]), "+f"(d[47]),
          "+f"(d[48]), "+f"(d[49]), "+f"(d[50]), "+f"(d[51]), "+f"(d[52]), "+f"(d[53]), "+f"(d[54]), "+f"(d[55]),
          "+f"(d[56]), "+f"(d[57]), "+f"(d[58]), "+f"(d[59]), "+f"(d[60]), "+f"(d[61]), "+f"(d[62]), "+f"(d[63])
        : "r"(a[0]), "r"(a[1]), "r"(a[2]), "r"(a[3]), "l"(descB), "r"(scaleD));
}

__device__ __forceinline__ void wgmma_ss_n184_t1(float (&d)[92], uint64_t descA, uint64_t descB, int scaleD) {
    asm volatile("{\n.reg .pred p;\n"
        "setp.ne.b32 p, %94, 0;\n"
        "wgmma.mma_async.sync.aligned.m64n184k16.f32.bf16.bf16 "
        "{%0, %1, %2, %3, %4, %5, %6, %7, %8, %9, %10, %11, %12, %13, %14, %15, "
        "%16, %17, %18, %19, %20, %21, %22, %23, %24, %25, %26, %27, %28, %29, %30, %31, "
        "%32, %33, %34, %35, %36, %37, %38, %39, %40, %41, %42, %43, %44, %45, %46, %47, "
        "%48, %49, %50, %51, %52, %53, %54, %55, %56, %57, %58, %59, %60, %61, %62, %63, "
        "%64, %65, %66, %67, %68, %69, %70, %71, %72, %73, %74, %75, %76, %77, %78, %79, "
        "%80, %81, %82, %83, %84, %85, %86, %87, %88, %89, %90, %91}, "
        "%92, %93, p, 1, 1, 0, 1;\n}\n"
        :
          "+f"(d[0]), "+f"(d[1]), "+f"(d[2]), "+f"(d[3]), "+f"(d[4]), "+f"(d[5]), "+f"(d[6]), "+f"(d[7]),
          "+f"(d[8]), "+f"(d[9]), "+f"(d[10]), "+f"(d[11]), "+f"(d[12]), "+f"(d[13]), "+f"(d[14]), "+f"(d[15]),
          "+f"(d[16]), "+f"(d[17]), "+f"(d[18]), "+f"(d[19]), "+f"(d[20]), "+f"(d[21]), "+f"(d[22]), "+f"(d[23]),
          "+f"(d[24]), "+f"(d[25]), "+f"(d[26]), "+f"(d[27]), "+f"(d[28]), "+f"(d[29]), "+f"(d[30]), "+f"(d[31]),
          "+f"(d[32]), "+f"(d[33]), "+f"(d[34]), "+f"(d[35]), "+f"(d[36]), "+f"(d[37]), "+f"(d[38]), "+f"(d[39]),
          "+f"(d[40]), "+f"(d[41]), "+f"(d[42]), "+f"(d[43]), "+f"(d[44]), "+f"(d[45]), "+f"(d[46]), "+f"(d[47]),
          "+f"(d[48]), "+f"(d[49]), "+f"(d[50]), "+f"(d[51]), "+f"(d[52]), "+f"(d[53]), "+f"(d[54]), "+f"(d[55]),
          "+f"(d[56]), "+f"(d[57]), "+f"(d[58]), "+f"(d[59]), "+f"(d[60]), "+f"(d[61]), "+f"(d[62]), "+f"(d[63]),
          "+f"(d[64]), "+f"(d[65]), "+f"(d[66]), "+f"(d[67]), "+f"(d[68]), "+f"(d[69]), "+f"(d[70]), "+f"(d[71]),
          "+f"(d[72]), "+f"(d[73]), "+f"(d[74]), "+f"(d[75]), "+f"(d[76]), "+f"(d[77]), "+f"(d[78]), "+f"(d[79]),
          "+f"(d[80]), "+f"(d[81]), "+f"(d[82]), "+f"(d[83]), "+f"(d[84]), "+f"(d[85]), "+f"(d[86]), "+f"(d[87]),
          "+f"(d[88]), "+f"(d[89]), "+f"(d[90]), "+f"(d[91])
        : "l"(descA), "l"(descB), "r"(scaleD));
}

__device__ __forceinline__ void wgmma_ss_n192_t1(float (&d)[96], uint64_t descA, uint64_t descB, int scaleD) {
    asm volatile("{\n.reg .pred p;\n"
        "setp.ne.b32 p, %98, 0;\n"
        "wgmma.mma_async.sync.aligned.m64n192k16.f32.bf16.bf16 "
        "{%0, %1, %2, %3, %4, %5, %6, %7, %8, %9, %10, %11, %12, %13, %14, %15, "
        "%16, %17, %18, %19, %20, %21, %22, %23, %24, %25, %26, %27, %28, %29, %30, %31, "
        "%32, %33, %34, %35, %36, %37, %38, %39, %40, %41, %42, %43, %44, %45, %46, %47, "
        "%48, %49, %50, %51, %52, %53, %54, %55, %56, %57, %58, %59, %60, %61, %62, %63, "
        "%64, %65, %66, %67, %68, %69, %70, %71, %72, %73, %74, %75, %76, %77, %78, %79, "
        "%80, %81, %82, %83, %84, %85, %86, %87, %88, %89, %90, %91, %92, %93, %94, %95}, "
        "%96, %97, p, 1, 1, 0, 1;\n}\n"
        :
          "+f"(d[0]), "+f"(d[1]), "+f"(d[2]), "+f"(d[3]), "+f"(d[4]), "+f"(d[5]), "+f"(d[6]), "+f"(d[7]),
          "+f"(d[8]), "+f"(d[9]), "+f"(d[10]), "+f"(d[11]), "+f"(d[12]), "+f"(d[13]), "+f"(d[14]), "+f"(d[15]),
          "+f"(d[16]), "+f"(d[17]), "+f"(d[18]), "+f"(d[19]), "+f"(d[20]), "+f"(d[21]), "+f"(d[22]), "+f"(d[23]),
          "+f"(d[24]), "+f"(d[25]), "+f"(d[26]), "+f"(d[27]), "+f"(d[28]), "+f"(d[29]), "+f"(d[30]), "+f"(d[31]),
          "+f"(d[32]), "+f"(d[33]), "+f"(d[34]), "+f"(d[35]), "+f"(d[36]), "+f"(d[37]), "+f"(d[38]), "+f"(d[39]),
          "+f"(d[40]), "+f"(d[41]), "+f"(d[42]), "+f"(d[43]), "+f"(d[44]), "+f"(d[45]), "+f"(d[46]), "+f"(d[47]),
          "+f"(d[48]), "+f"(d[49]), "+f"(d[50]), "+f"(d[51]), "+f"(d[52]), "+f"(d[53]), "+f"(d[54]), "+f"(d[55]),
          "+f"(d[56]), "+f"(d[57]), "+f"(d[58]), "+f"(d[59]), "+f"(d[60]), "+f"(d[61]), "+f"(d[62]), "+f"(d[63]),
          "+f"(d[64]), "+f"(d[65]), "+f"(d[66]), "+f"(d[67]), "+f"(d[68]), "+f"(d[69]), "+f"(d[70]), "+f"(d[71]),
          "+f"(d[72]), "+f"(d[73]), "+f"(d[74]), "+f"(d[75]), "+f"(d[76]), "+f"(d[77]), "+f"(d[78]), "+f"(d[79]),
          "+f"(d[80]), "+f"(d[81]), "+f"(d[82]), "+f"(d[83]), "+f"(d[84]), "+f"(d[85]), "+f"(d[86]), "+f"(d[87]),
          "+f"(d[88]), "+f"(d[89]), "+f"(d[90]), "+f"(d[91]), "+f"(d[92]), "+f"(d[93]), "+f"(d[94]), "+f"(d[95])
        : "l"(descA), "l"(descB), "r"(scaleD));
}

__device__ __forceinline__ void wgmma_ss_n128_t1(float (&d)[64], uint64_t descA, uint64_t descB, int scaleD) {
    asm volatile("{\n.reg .pred p;\n"
        "setp.ne.b32 p, %66, 0;\n"
        "wgmma.mma_async.sync.aligned.m64n128k16.f32.bf16.bf16 "
        "{%0, %1, %2, %3, %4, %5, %6, %7, %8, %9, %10, %11, %12, %13, %14, %15, "
        "%16, %17, %18, %19, %20, %21, %22, %23, %24, %25, %26, %27, %28, %29, %30, %31, "
        "%32, %33, %34, %35, %36, %37, %38, %39, %40, %41, %42, %43, %44, %45, %46, %47, "
        "%48, %49, %50, %51, %52, %53, %54, %55, %56, %57, %58, %59, %60, %61, %62, %63}, "
        "%64, %65, p, 1, 1, 0, 1;\n}\n"
        :
          "+f"(d[0]), "+f"(d[1]), "+f"(d[2]), "+f"(d[3]), "+f"(d[4]), "+f"(d[5]), "+f"(d[6]), "+f"(d[7]),
          "+f"(d[8]), "+f"(d[9]), "+f"(d[10]), "+f"(d[11]), "+f"(d[12]), "+f"(d[13]), "+f"(d[14]), "+f"(d[15]),
          "+f"(d[16]), "+f"(d[17]), "+f"(d[18]), "+f"(d[19]), "+f"(d[20]), "+f"(d[21]), "+f"(d[22]), "+f"(d[23]),
          "+f"(d[24]), "+f"(d[25]), "+f"(d[26]), "+f"(d[27]), "+f"(d[28]), "+f"(d[29]), "+f"(d[30]), "+f"(d[31]),
          "+f"(d[32]), "+f"(d[33]), "+f"(d[34]), "+f"(d[35]), "+f"(d[36]), "+f"(d[37]), "+f"(d[38]), "+f"(d[39]),
          "+f"(d[40]), "+f"(d[41]), "+f"(d[42]), "+f"(d[43]), "+f"(d[44]), "+f"(d[45]), "+f"(d[46]), "+f"(d[47]),
          "+f"(d[48]), "+f"(d[49]), "+f"(d[50]), "+f"(d[51]), "+f"(d[52]), "+f"(d[53]), "+f"(d[54]), "+f"(d[55]),
          "+f"(d[56]), "+f"(d[57]), "+f"(d[58]), "+f"(d[59]), "+f"(d[60]), "+f"(d[61]), "+f"(d[62]), "+f"(d[63])
        : "l"(descA), "l"(descB), "r"(scaleD));
}

__device__ __forceinline__ void wgmma_ss_n32_t1(float (&d)[16], uint64_t descA, uint64_t descB, int scaleD) {
    asm volatile("{\n.reg .pred p;\n"
        "setp.ne.b32 p, %18, 0;\n"
        "wgmma.mma_async.sync.aligned.m64n32k16.f32.bf16.bf16 "
        "{%0, %1, %2, %3, %4, %5, %6, %7, %8, %9, %10, %11, %12, %13, %14, %15}, "
        "%16, %17, p, 1, 1, 0, 1;\n}\n"
        :
          "+f"(d[0]), "+f"(d[1]), "+f"(d[2]), "+f"(d[3]), "+f"(d[4]), "+f"(d[5]), "+f"(d[6]), "+f"(d[7]),
          "+f"(d[8]), "+f"(d[9]), "+f"(d[10]), "+f"(d[11]), "+f"(d[12]), "+f"(d[13]), "+f"(d[14]), "+f"(d[15])
        : "l"(descA), "l"(descB), "r"(scaleD));
}

constexpr int S_LEN = 2048;
constexpr int D_MODEL = 640;
constexpr int N_HEADS = 32;
constexpr int D_HEAD = 128;
constexpr int S_KV = 2048;
constexpr int WIN = 512;
constexpr int D_FF = 1728;
constexpr float LN_EPS = 1e-5f;

#define TS(kid, slot)

__device__ float g_mod[6 * D_MODEL];
__device__ __align__(1024) __nv_bfloat16 g_h[S_LEN * D_MODEL];
__device__ __align__(1024) __nv_bfloat16 g_o[S_LEN * N_HEADS * D_HEAD];
__device__ __align__(1024) __nv_bfloat16 g_part[4 * S_LEN * D_MODEL];
__device__ __align__(1024) __nv_bfloat16 g_x1[S_LEN * D_MODEL];
__device__ __align__(1024) __nv_bfloat16 g_h2[S_LEN * D_MODEL];
__device__ __align__(1024) __nv_bfloat16 g_act[S_LEN * D_FF];

constexpr int F_MODAB = 0, F_MODALL = 1, F_H = 2, F_P = 18, F_H2 = 34, F_A = 50, F_O = 66, F_A1 = 130, F_COUNT = 146;
__device__ unsigned g_flags[F_COUNT * 32];
__device__ unsigned g_epoch;
__device__ unsigned g_exit;

__device__ __forceinline__ void flag_signal(int f) {
    asm volatile("red.release.gpu.global.add.u32 [%0], 1;" ::"l"(g_flags + f * 32) : "memory");
}
__device__ __forceinline__ void flag_signal_relaxed(int f) {
    asm volatile("red.relaxed.gpu.global.add.u32 [%0], 1;" ::"l"(g_flags + f * 32) : "memory");
}
__device__ __forceinline__ void flag_wait(int f, unsigned target) {
    unsigned n = 0;
    while (true) {
        unsigned v;
        asm volatile("ld.acquire.gpu.global.u32 %0, [%1];" : "=r"(v) : "l"(g_flags + f * 32) : "memory");
        if ((int)(v - target) >= 0) break;
        if ((++n & 0xfffu) == 0) {
            if (n > (1u << 24)) g_abort = 1;
            if (g_abort) break;
        }
    }
}

struct Maps {
    CUtensorMap h, wq, k, v, o_st, o_a, wo, part_st, h2, g128, u128, g64, u64, act_st64, act_st24, act_a, wd, wd32;
};

constexpr int SM_DATA = 229376;
constexpr int SM_STAGING = 196608;
constexpr int SM_TOTAL = SM_DATA + 1024 + 512;
constexpr int B1F = 0, B1E = 6, B2F = 12, B2E = 16, B4F = 20, B4E = 24, B5F = 28, B5E = 33, BD1 = 38, BD2 = 39, BD4 = 40, BD1A = 41, BX = 42, BD4B = 43;
constexpr int P1_STAGE = 32768, P2_STAGE = 57344, P4_STAGE = 49152, P5_STAGE = 36864;

__device__ __forceinline__ float rcp_approx(float x) { float y; asm("rcp.approx.ftz.f32 %0, %1;" : "=f"(y) : "f"(x)); return y; }
__device__ __forceinline__ float silu_mul(float g, float u) { return g * rcp_approx(1.f + ex2(-1.4426950408889634f * g)) * u; }
__device__ __forceinline__ uint2 ldcg_u2(const void* p) { return __ldcg(reinterpret_cast<const uint2*>(p)); }

__device__ __forceinline__ void ln_rows_impl(uint2 a0, uint2 a1, uint2 a2, uint2 a3, uint2 a4, uint2 b0, uint2 b1, uint2 b2, uint2 b3, uint2 b4,
                                          const float* __restrict__ shift, const float* __restrict__ scale1p,
                                          __nv_bfloat16* __restrict__ dst, int lane) {
    const uint2 xr[2][5] = {{a0, a1, a2, a3, a4}, {b0, b1, b2, b3, b4}};
    float4 sh[5], sc[5];
#pragma unroll
    for (int i = 0; i < 5; i++) {
        sh[i] = __ldcg(reinterpret_cast<const float4*>(shift + (lane + 32 * i) * 4));
        sc[i] = __ldcg(reinterpret_cast<const float4*>(scale1p + (lane + 32 * i) * 4));
    }
    float mean[2], rstd[2];
#pragma unroll
    for (int rr = 0; rr < 2; rr++) {
        float s = 0.f;
#pragma unroll
        for (int i = 0; i < 5; i++) s += (bf16lo(xr[rr][i].x) + bf16hi(xr[rr][i].x)) + (bf16lo(xr[rr][i].y) + bf16hi(xr[rr][i].y));
#pragma unroll
        for (int o = 16; o > 0; o >>= 1) s += __shfl_xor_sync(0xffffffffu, s, o);
        mean[rr] = s * (1.f / D_MODEL);
    }
#pragma unroll
    for (int rr = 0; rr < 2; rr++) {
        float q = 0.f;
#pragma unroll
        for (int i = 0; i < 5; i++) {
            const float d0 = bf16lo(xr[rr][i].x) - mean[rr], d1 = bf16hi(xr[rr][i].x) - mean[rr];
            const float d2 = bf16lo(xr[rr][i].y) - mean[rr], d3 = bf16hi(xr[rr][i].y) - mean[rr];
            q += (d0 * d0 + d1 * d1) + (d2 * d2 + d3 * d3);
        }
#pragma unroll
        for (int o = 16; o > 0; o >>= 1) q += __shfl_xor_sync(0xffffffffu, q, o);
        rstd[rr] = rsqrtf(q * (1.f / D_MODEL) + LN_EPS);
    }
#pragma unroll
    for (int rr = 0; rr < 2; rr++) {
#pragma unroll
        for (int i = 0; i < 5; i++) {
            uint2 u;
            u.x = pack_bf16((bf16lo(xr[rr][i].x) - mean[rr]) * rstd[rr] * sc[i].x + sh[i].x, (bf16hi(xr[rr][i].x) - mean[rr]) * rstd[rr] * sc[i].y + sh[i].y);
            u.y = pack_bf16((bf16lo(xr[rr][i].y) - mean[rr]) * rstd[rr] * sc[i].z + sh[i].z, (bf16hi(xr[rr][i].y) - mean[rr]) * rstd[rr] * sc[i].w + sh[i].w);
            *reinterpret_cast<uint2*>(dst + (size_t)rr * D_MODEL + (lane + 32 * i) * 4) = u;
        }
    }
}

__device__ __forceinline__ void ln_rows(const uint2 (&xr)[2][5], const float* shift, const float* scale1p, __nv_bfloat16* dst, int lane) {
    ln_rows_impl(xr[0][0], xr[0][1], xr[0][2], xr[0][3], xr[0][4], xr[1][0], xr[1][1], xr[1][2], xr[1][3], xr[1][4], shift, scale1p, dst, lane);
}

__global__ void __cluster_dims__(2, 1, 1) __launch_bounds__(384, 1)
mega_kernel(const __grid_constant__ Maps tm, const __nv_bfloat16* __restrict__ x, const __nv_bfloat16* __restrict__ cvec,
            const __nv_bfloat16* __restrict__ w_mod, __nv_bfloat16* __restrict__ out, const void* wo_p, const void* wg_p,
            const void* wu_p, const void* wd_p) {
    extern __shared__ uint8_t smem_raw[];
    const uint32_t base = (smem_u32(smem_raw) + 1023u) & ~1023u;
    const uint32_t bars = base + SM_DATA;
    const uint32_t rank = cluster_ctarank();
    const int cid = blockIdx.x >> 1;
    const int p = cid & 7, j = cid >> 3;
    const int mt = p * 2 + (int)rank;
    const int m0 = mt * 128;
    const int wg = threadIdx.x >> 7;
    unsigned epoch;
    asm volatile("ld.volatile.global.u32 %0, [%1];" : "=r"(epoch) : "l"(&g_epoch));

    uint2 xr[2][5];
    uint4 w[10];
    unsigned short cr[10];
    if (wg < 2) {
        const int cw = threadIdx.x >> 5, lane = threadIdx.x & 31;
        const int mb = blockIdx.x < 120 ? blockIdx.x : 0;
#pragma unroll
        for (int i = 0; i < 10; i++) cr[i] = __ldg(reinterpret_cast<const unsigned short*>(cvec) + cw * 80 + i * 8 + (lane >> 2));
#pragma unroll
        for (int i = 0; i < 10; i++)
            w[i] = __ldg(reinterpret_cast<const uint4*>(w_mod + (size_t)(cw * 80 + i * 8 + (lane >> 2)) * (6 * D_MODEL) + mb * 32 + (lane & 3) * 8));
#pragma unroll
        for (int rr = 0; rr < 2; rr++)
#pragma unroll
            for (int i = 0; i < 5; i++)
                xr[rr][i] = __ldg(reinterpret_cast<const uint2*>(x + (size_t)(m0 + j * 16 + cw * 2 + rr) * D_MODEL + (lane + 32 * i) * 4));
    }

    if (threadIdx.x == 0) {
        for (int i = 0; i < 6; i++) { mbar_init(bars + 8 * (B1F + i), 1); mbar_init(bars + 8 * (B1E + i), 4); }
        for (int i = 0; i < 4; i++) { mbar_init(bars + 8 * (B2F + i), 1); mbar_init(bars + 8 * (B2E + i), 4); }
        for (int i = 0; i < 4; i++) { mbar_init(bars + 8 * (B4F + i), 1); mbar_init(bars + 8 * (B4E + i), 4); }
        for (int i = 0; i < 5; i++) { mbar_init(bars + 8 * (B5F + i), 1); mbar_init(bars + 8 * (B5E + i), 2); }
        mbar_init(bars + 8 * BD1, 4); mbar_init(bars + 8 * BD2, 4); mbar_init(bars + 8 * BD4, 4); mbar_init(bars + 8 * BD1A, 4);
        mbar_init(bars + 8 * BX, 1); mbar_init(bars + 8 * BD4B, 4);
        mbar_expect_tx(bars + 8 * BX, 40960);
        fence_mbar_init();
    }
    __syncthreads();
    cluster_sync();

    if (wg == 2) {
        reg_dealloc<40>();
        if (threadIdx.x == 256) {
            {
                uint32_t st = 0, ph = 1;
                bool first = true;
#pragma unroll 1
                for (int hp = 0; hp < 2; hp++) {
                    const int head0 = j * 4 + hp * 2;
                    if (first) {
#pragma unroll 1
                        for (int s = 1; s < 6; s++) {
                            if (s == 3) continue;
                            const int kb = s < 3 ? s - 1 : s - 2;
                            mbar_expect_tx(bars + 8 * (B1F + s), P1_STAGE);
#pragma unroll 1
                            for (int c = 0; c < 2; c++) {
                                const int chunk = 2 * (int)rank + c;
                                tma_load_2d_mc(base + s * P1_STAGE + chunk * 8192, &tm.wq, head0 * 128 + chunk * 64, kb * 64, bars + 8 * (B1F + s), 3);
                            }
                        }
                        flag_wait(F_H + mt, (epoch + 1) * 8);
                        fence_proxy_async_all();
#pragma unroll 1
                        for (int s = 0; s < 6; s += 3) {
                            mbar_expect_tx(bars + 8 * (B1F + s), P1_STAGE);
                            tma_load_2d(base + s * P1_STAGE, &tm.h, (s / 3 * 2) * 64, m0, bars + 8 * (B1F + s));
                            tma_load_2d(base + s * P1_STAGE + 16384, &tm.h, (s / 3 * 2 + 1) * 64, m0, bars + 8 * (B1F + s));
                        }
                        ph = 0;
                    }
#pragma unroll 1
                    for (int kk2 = first ? 2 : 0; kk2 < 5; kk2++) {
                        mbar_wait(bars + 8 * (B1E + st), ph);
                        mbar_expect_tx(bars + 8 * (B1F + st), P1_STAGE);
                        tma_load_2d(base + st * P1_STAGE, &tm.h, (2 * kk2) * 64, m0, bars + 8 * (B1F + st));
                        tma_load_2d(base + st * P1_STAGE + 16384, &tm.h, (2 * kk2 + 1) * 64, m0, bars + 8 * (B1F + st));
                        if (++st == 6) { st = 0; ph ^= 1; }
#pragma unroll 1
                        for (int u = 0; u < 2; u++) {
                            mbar_wait(bars + 8 * (B1E + st), ph);
                            mbar_expect_tx(bars + 8 * (B1F + st), P1_STAGE);
                            const int kb = 2 * kk2 + u;
#pragma unroll 1
                            for (int c = 0; c < 2; c++) {
                                const int chunk = 2 * (int)rank + c;
                                tma_load_2d_mc(base + st * P1_STAGE + chunk * 8192, &tm.wq, head0 * 128 + chunk * 64, kb * 64, bars + 8 * (B1F + st), 3);
                            }
                            if (++st == 6) { st = 0; ph ^= 1; }
                        }
                    }
                    first = false;
#pragma unroll 1
                    for (int t = 0; t <= 8; t++) {
                        if (t < 8) {
                            mbar_wait(bars + 8 * (B1E + st), ph);
                            mbar_expect_tx(bars + 8 * (B1F + st), P1_STAGE);
                            const int row = (head0 + (t >> 2)) * S_KV + (S_KV - WIN) + (t & 3) * 128;
                            tma_load_2d_mc(base + st * P1_STAGE + rank * 16384, &tm.k, rank * 64, row, bars + 8 * (B1F + st), 3);
                            if (++st == 6) { st = 0; ph ^= 1; }
                        }
                        if (t > 0) {
                            mbar_wait(bars + 8 * (B1E + st), ph);
                            mbar_expect_tx(bars + 8 * (B1F + st), P1_STAGE);
                            const int tv = t - 1;
                            const int row = (head0 + (tv >> 2)) * S_KV + (S_KV - WIN) + (tv & 3) * 128;
                            tma_load_2d_mc(base + st * P1_STAGE + rank * 16384, &tm.v, rank * 64, row, bars + 8 * (B1F + st), 3);
                            if (++st == 6) { st = 0; ph ^= 1; }
                        }
                    }
                }
            }
            {
                const int kq = j >> 1, n0 = (j & 1) * 320;
                uint32_t st = 0, ph = 1;
#pragma unroll 1
                for (int i = 0; i < 16; i++) {
                    if (i == 0) mbar_wait(bars + 8 * BD1A, 0);
                    if (i == 3) mbar_wait(bars + 8 * BD1, 0);
                    if (i == 8) { flag_wait(F_O + mt * 4 + kq, (epoch + 1) * 4); fence_proxy_async_all(); }
                    mbar_wait(bars + 8 * (B2E + st), ph);
                    mbar_expect_tx(bars + 8 * (B2F + st), P2_STAGE);
                    const uint32_t dst = base + st * P2_STAGE;
                    const int k0 = kq * 1024 + ((i + (j & 1) * 8) & 15) * 64;
                    tma_load_2d(dst, &tm.o_a, k0, m0, bars + 8 * (B2F + st));
#pragma unroll 1
                    for (int c = 0; c < 5; c++)
                        if (((c + i) & 1) == (int)rank) tma_load_2d_mc(dst + 16384 + c * 8192, &tm.wo, n0 + c * 64, k0, bars + 8 * (B2F + st), 3);
                    if (++st == 4) { st = 0; ph ^= 1; }
                }
            }
            {
                const int f0 = j * 216;
                const CUtensorMap* t128 = rank == 0 ? &tm.g128 : &tm.u128;
                const CUtensorMap* t64 = rank == 0 ? &tm.g64 : &tm.u64;
                mbar_wait(bars + 8 * BD2, 0);
#pragma unroll 1
                for (int i = 0; i < 4; i++) {
                    mbar_expect_tx(bars + 8 * (B4F + i), 16384 + 32768);
                    const uint32_t dst = base + i * P4_STAGE;
                    tma_load_2d_mc(dst + 16384 + rank * 16384, t128, f0, i * 64, bars + 8 * (B4F + i), 3);
                    tma_load_2d_mc(dst + 16384 + rank * 16384 + 8192, t128, f0 + 64, i * 64, bars + 8 * (B4F + i), 3);
                }
                flag_wait(F_H2 + mt, (epoch + 1) * 8);
                fence_proxy_async_all();
#pragma unroll 1
                for (int i = 0; i < 4; i++) tma_load_2d(base + i * P4_STAGE, &tm.h2, i * 64, m0, bars + 8 * (B4F + i));
                uint32_t st = 0, ph = 0;
#pragma unroll 1
                for (int i = 4; i < 20; i++) {
                    const int kb = i < 10 ? i : i - 10;
                    mbar_wait(bars + 8 * (B4E + st), ph);
                    const uint32_t dst = base + st * P4_STAGE;
                    if (i < 10) {
                        mbar_expect_tx(bars + 8 * (B4F + st), 16384 + 32768);
                        tma_load_2d(dst, &tm.h2, kb * 64, m0, bars + 8 * (B4F + st));
                        tma_load_2d_mc(dst + 16384 + rank * 16384, t128, f0, kb * 64, bars + 8 * (B4F + st), 3);
                        tma_load_2d_mc(dst + 16384 + rank * 16384 + 8192, t128, f0 + 64, kb * 64, bars + 8 * (B4F + st), 3);
                    } else {
                        mbar_expect_tx(bars + 8 * (B4F + st), 16384 + 24576);
                        tma_load_2d(dst, &tm.h2, kb * 64, m0, bars + 8 * (B4F + st));
#pragma unroll 1
                        for (int c = 0; c < 3; c++)
                            tma_load_2d_mc(dst + 16384 + rank * 12288 + c * 4096, t64, f0 + 128 + c * 32, kb * 64, bars + 8 * (B4F + st), 3);
                    }
                    if (++st == 4) { st = 0; ph ^= 1; }
                }
            }
            {
                const int mt5 = p * 2 + (j >> 2), n0 = (j & 3) * 160;
                const int nkb = rank == 0 ? 14 : 13;
                const unsigned long long ord = rank == 0
                    ? (0ull | 1ull << 5 | 4ull << 10 | 7ull << 15 | 11ull << 20 | 2ull << 25 | 3ull << 30 | 5ull << 35 | 6ull << 40 | 8ull << 45 | 9ull << 50 | 10ull << 55)
                    : (14ull | 17ull << 5 | 21ull << 10 | 24ull << 15 | 15ull << 20 | 16ull << 25 | 18ull << 30 | 19ull << 35 | 20ull << 40 | 22ull << 45 | 23ull << 50 | 25ull << 55);
                const int nearly = rank == 0 ? 5 : 4;
                mbar_wait(bars + 8 * BD4, 0);
                uint32_t st = 0, ph = 1;
#pragma unroll 1
                for (int i = 0; i < nkb; i++) {
                    const int kb = i < 12 ? (int)((ord >> (5 * i)) & 31) : (rank == 0 ? i : 26);
                    if (i == 0) { flag_wait(F_A1 + mt5, (epoch + 1) * 16); fence_proxy_async_all(); }
                    if (i == nearly) { flag_wait(F_A + mt5, (epoch + 1) * 16); fence_proxy_async_all(); }
                    mbar_wait(bars + 8 * (B5E + st), ph);
                    mbar_expect_tx(bars + 8 * (B5F + st), P5_STAGE);
                    const uint32_t dst = base + st * P5_STAGE;
                    const int k0 = kb * 64;
                    tma_load_2d(dst + 16384, &tm.wd, n0, k0, bars + 8 * (B5F + st));
                    tma_load_2d(dst + 16384 + 8192, &tm.wd, n0 + 64, k0, bars + 8 * (B5F + st));
                    tma_load_2d(dst + 16384 + 16384, &tm.wd32, n0 + 128, k0, bars + 8 * (B5F + st));
                    tma_load_2d(dst, &tm.act_a, k0, mt5 * 128, bars + 8 * (B5F + st));
                    if (++st == 5) { st = 0; ph ^= 1; }
                }
            }
        }
        else if (threadIdx.x == 288) {
            mbar_wait(bars + 8 * B1F, 0);
            const char* pw[4] = {(const char*)wo_p, (const char*)wg_p, (const char*)wu_p, (const char*)wd_p};
#pragma unroll 1
            for (int t = 0; t < 4; t++) {
                const uint32_t bytes = t == 0 ? 40960u : 17280u;
                asm volatile("cp.async.bulk.prefetch.L2.global [%0], %1;" ::"l"(pw[t] + (size_t)blockIdx.x * bytes), "r"(bytes) : "memory");
            }
        }
        __syncwarp();
        asm volatile("barrier.cluster.arrive.relaxed.aligned; // producer\n barrier.cluster.wait.aligned;" ::: "memory");
    } else {
        reg_alloc<232>();
        const int tid = threadIdx.x & 127;
        const int warp = tid >> 5, lane = tid & 31;
        const int cw = threadIdx.x >> 5;
        const uint32_t mystage = base + SM_STAGING + wg * 16384;
        auto arrive_both = [&](uint32_t bar) {
            if (tid == 0) mbar_arrive_cluster(bar, 0);
            if (tid == 32) mbar_arrive_cluster(bar, 1);
        };
        TS(0, 0);
        {
            if (blockIdx.x < 120) {
                float* red = reinterpret_cast<float*>(smem_raw + (base - smem_u32(smem_raw)) + SM_STAGING);
                float acc[8];
#pragma unroll
                for (int i = 0; i < 8; i++) acc[i] = 0.f;
#pragma unroll
                for (int i = 0; i < 10; i++) {
                    const float s = bf16_round(silu_mul(__uint_as_float((uint32_t)cr[i] << 16), 1.f));
                    acc[0] += s * bf16lo(w[i].x); acc[1] += s * bf16hi(w[i].x);
                    acc[2] += s * bf16lo(w[i].y); acc[3] += s * bf16hi(w[i].y);
                    acc[4] += s * bf16lo(w[i].z); acc[5] += s * bf16hi(w[i].z);
                    acc[6] += s * bf16lo(w[i].w); acc[7] += s * bf16hi(w[i].w);
                }
#pragma unroll
                for (int i = 0; i < 8; i++) {
                    acc[i] += __shfl_xor_sync(0xffffffffu, acc[i], 4);
                    acc[i] += __shfl_xor_sync(0xffffffffu, acc[i], 8);
                    acc[i] += __shfl_xor_sync(0xffffffffu, acc[i], 16);
                }
                if (lane < 4) {
#pragma unroll
                    for (int i = 0; i < 8; i++) red[cw * 32 + lane * 8 + i] = acc[i];
                }
                TS(6, 0);
                bar_sync(5, 256);
                TS(6, 1);
                if (threadIdx.x < 32) {
                    float t = 0.f;
#pragma unroll
                    for (int i = 0; i < 8; i++) t += red[i * 32 + threadIdx.x];
                    t = bf16_round(t);
                    const int chunk = blockIdx.x / 20;
                    if (chunk == 1 || chunk == 4) t = bf16_round(1.f + t);
                    g_mod[blockIdx.x * 32 + threadIdx.x] = t;
                    __syncwarp();
                    TS(6, 2);
                    if (threadIdx.x == 0) flag_signal(blockIdx.x < 40 ? F_MODAB : F_MODALL);
                    TS(6, 3);
                }
            }
            if (threadIdx.x == 0) flag_wait(F_MODAB, (epoch + 1) * 40);
            bar_sync(5, 256);
            TS(0, 1);
            ln_rows(xr, g_mod, g_mod + D_MODEL, g_h + (size_t)(m0 + j * 16 + cw * 2) * D_MODEL, lane);
            TS(6, 4);
            bar_sync(5, 256);
            TS(6, 5);
            if (threadIdx.x == 0) flag_signal(F_H + mt);
        }
        TS(0, 2);
        {
            const float cscale = 0.08838834764831845f * 1.4426950408889634f;
            uint32_t st = 0, ph = 0;
            auto wait_full = [&]() -> uint32_t {
                mbar_wait(bars + 8 * (B1F + st), ph);
                return base + st * P1_STAGE;
            };
            auto release = [&](uint32_t s) { arrive_both(bars + 8 * (B1E + s)); };
            auto advance = [&]() { if (++st == 6) { st = 0; ph ^= 1; } };
            auto turn_wait = [&]() { bar_sync(3 + wg, 256); };
            auto turn_pass = [&]() { bar_arrive(3 + (wg ^ 1), 256); };
            if (wg == 1) bar_arrive(3, 256);

            for (int hp = 0; hp < 2; hp++) {
                const int head0 = j * 4 + hp * 2;
                uint32_t q[8][4];
                {
                    float acc[128];
#pragma unroll
                    for (int i = 0; i < 128; i++) acc[i] = 0.f;
                    for (int kk2 = 0; kk2 < 5; kk2++) {
                        const uint32_t hbuf = wait_full();
                        if (kk2 == 0 && hp == 0) TS(0, 3);
                        const uint32_t sth = st;
                        advance();
#pragma unroll
                        for (int u = 0; u < 2; u++) {
                            const uint32_t wbuf = wait_full();
                            const uint32_t stw = st;
                            advance();
                            wgmma_fence();
#pragma unroll
                            for (int k = 0; k < 4; k++) {
                                uint64_t da = make_desc(hbuf + u * 16384 + wg * 8192 + k * 32, 16, 1024, 1);
                                uint64_t db = make_desc(wbuf + k * 2048, 8192, 1024, 1);
                                wgmma_ss_n256_t1(acc, da, db, 1);
                            }
                            wgmma_commit();
                            wgmma_wait<0>();
                            release(stw);
                        }
                        release(sth);
                    }
                    fence_regs(acc);
                    if (tid == 0) tma_store_wait_read<0>();
                    bar_sync(1 + wg, 128);
#pragma unroll
                    for (int i = 0; i < 8; i++) {
                        q[i][0] = pack_bf16(acc[8 * i + 0], acc[8 * i + 1]);
                        q[i][1] = pack_bf16(acc[8 * i + 2], acc[8 * i + 3]);
                        q[i][2] = pack_bf16(acc[8 * i + 4], acc[8 * i + 5]);
                        q[i][3] = pack_bf16(acc[8 * i + 6], acc[8 * i + 7]);
                        uint32_t b0 = pack_bf16(acc[64 + 8 * i + 0], acc[64 + 8 * i + 1]);
                        uint32_t b1 = pack_bf16(acc[64 + 8 * i + 2], acc[64 + 8 * i + 3]);
                        uint32_t b2 = pack_bf16(acc[64 + 8 * i + 4], acc[64 + 8 * i + 5]);
                        uint32_t b3 = pack_bf16(acc[64 + 8 * i + 6], acc[64 + 8 * i + 7]);
                        asm volatile("st.shared.v4.b32 [%0], {%1, %2, %3, %4};" ::"r"(mystage + (i * 128 + tid) * 16), "r"(b0), "r"(b1),
                                     "r"(b2), "r"(b3) : "memory");
                    }
                }
                float o[64], s[64], e[64];
                uint32_t pp[8][4];
                float mm0, mm1, l0, l1, a0, a1, lo0, lo1;
#pragma unroll
                for (int i = 0; i < 64; i++) { o[i] = 0.f; }

                auto issue_s = [&]() -> uint32_t {
                    const uint32_t kbuf = wait_full();
                    const uint32_t stk = st;
                    advance();
                    wgmma_fence();
#pragma unroll
                    for (int k = 0; k < 8; k++) {
                        uint64_t db = make_desc(kbuf + (k >> 2) * 16384 + (k & 3) * 32, 16, 1024, 1);
                        if (k == 0) wgmma_rs_n128_t0_z(s, q[k], db);
                        else wgmma_rs_n128_t0(s, q[k], db, 1);
                    }
                    wgmma_commit();
                    return stk;
                };
                auto issue_pv = [&](bool fresh) -> uint32_t {
                    const uint32_t vbuf = wait_full();
                    const uint32_t stv = st;
                    advance();
                    wgmma_fence();
#pragma unroll
                    for (int k = 0; k < 8; k++) {
                        uint64_t db = make_desc(vbuf + k * 2048, 16384, 1024, 1);
                        wgmma_rs_n128_t1(o, pp[k], db, (!fresh) || k != 0);
                    }
                    wgmma_commit();
                    return stv;
                };
                auto softmax = [&](bool first) {
                    float mx0 = fmaxf(s[0], s[1]), mx1 = fmaxf(s[2], s[3]);
#pragma unroll
                    for (int jj = 1; jj < 16; jj++) {
                        mx0 = fmaxf(mx0, fmaxf(s[4 * jj], s[4 * jj + 1]));
                        mx1 = fmaxf(mx1, fmaxf(s[4 * jj + 2], s[4 * jj + 3]));
                    }
                    mx0 = fmaxf(mx0, __shfl_xor_sync(0xffffffffu, mx0, 1));
                    mx0 = fmaxf(mx0, __shfl_xor_sync(0xffffffffu, mx0, 2));
                    mx1 = fmaxf(mx1, __shfl_xor_sync(0xffffffffu, mx1, 1));
                    mx1 = fmaxf(mx1, __shfl_xor_sync(0xffffffffu, mx1, 2));
                    if (first) {
                        lo0 = l0; lo1 = l1;
                        mm0 = mx0; mm1 = mx1; l0 = 0.f; l1 = 0.f; a0 = 0.f; a1 = 0.f;
                    } else {
                        float mn0 = fmaxf(mm0, mx0), mn1 = fmaxf(mm1, mx1);
                        a0 = ex2((mm0 - mn0) * cscale); a1 = ex2((mm1 - mn1) * cscale);
                        mm0 = mn0; mm1 = mn1;
                    }
                    const float mc0 = mm0 * cscale, mc1 = mm1 * cscale;
                    float r0 = 0.f, r1 = 0.f;
#pragma unroll
                    for (int jj = 0; jj < 16; jj++) {
                        e[4 * jj] = ex2(fmaf(s[4 * jj], cscale, -mc0));
                        e[4 * jj + 1] = ex2(fmaf(s[4 * jj + 1], cscale, -mc0));
                        e[4 * jj + 2] = ex2(fmaf(s[4 * jj + 2], cscale, -mc1));
                        e[4 * jj + 3] = ex2(fmaf(s[4 * jj + 3], cscale, -mc1));
                        r0 += e[4 * jj] + e[4 * jj + 1];
                        r1 += e[4 * jj + 2] + e[4 * jj + 3];
                    }
                    l0 = l0 * a0 + r0; l1 = l1 * a1 + r1;
                };
                auto convert_p = [&]() {
#pragma unroll
                    for (int i = 0; i < 8; i++) {
                        pp[i][0] = pack_bf16(e[8 * i + 0], e[8 * i + 1]);
                        pp[i][1] = pack_bf16(e[8 * i + 2], e[8 * i + 3]);
                        pp[i][2] = pack_bf16(e[8 * i + 4], e[8 * i + 5]);
                        pp[i][3] = pack_bf16(e[8 * i + 6], e[8 * i + 7]);
                    }
                };
                auto store_o = [&](float ls0, float ls1, int head, bool last) {
                    float s0 = ls0 + __shfl_xor_sync(0xffffffffu, ls0, 1); s0 += __shfl_xor_sync(0xffffffffu, s0, 2);
                    float s1 = ls1 + __shfl_xor_sync(0xffffffffu, ls1, 1); s1 += __shfl_xor_sync(0xffffffffu, s1, 2);
                    const float i0 = 1.f / s0, i1 = 1.f / s1;
                    if (tid == 0) {
                        tma_store_wait<0>();
                        if (last) {
                            mbar_arrive_cluster(bars + 8 * BD1A, 0);
                            mbar_arrive_cluster(bars + 8 * BD1A, 1);
                        }
                    }
                    bar_sync(1 + wg, 128);
#pragma unroll
                    for (int jj = 0; jj < 16; jj += 2) {
                        const int mi = lane >> 3;
                        const int row = warp * 16 + (mi & 1) * 8 + (lane & 7);
                        const int grp = jj + (mi >> 1);
                        const uint32_t addr = mystage + (grp >> 3) * 8192 + row * 128 + (((grp & 7) ^ (row & 7)) << 4);
                        stmatrix_x4(addr, pack_bf16(o[4 * jj] * i0, o[4 * jj + 1] * i0), pack_bf16(o[4 * jj + 2] * i1, o[4 * jj + 3] * i1),
                                    pack_bf16(o[4 * jj + 4] * i0, o[4 * jj + 5] * i0), pack_bf16(o[4 * jj + 6] * i1, o[4 * jj + 7] * i1));
                    }
                    fence_proxy_async();
                    bar_sync(1 + wg, 128);
                    if (tid == 0) {
                        tma_store_2d(&tm.o_st, mystage, head * 128, m0 + wg * 64);
                        tma_store_2d(&tm.o_st, mystage + 8192, head * 128 + 64, m0 + wg * 64);
                        tma_store_commit();
                        if (last) {
                            tma_store_wait<0>();
                            mbar_arrive_cluster(bars + 8 * BD1, 0);
                            mbar_arrive_cluster(bars + 8 * BD1, 1);
                            flag_signal_relaxed(F_O + mt * 4 + (j >> 1));
                        }
                    }
                };

                l0 = 0.f; l1 = 0.f;
                {
                    turn_wait();
                    uint32_t stk = issue_s();
                    turn_pass();
                    wgmma_wait<0>();
                    fence_regs(s);
                    release(stk);
                    softmax(true);
                    convert_p();
                }
#pragma unroll 1
                for (int t = 1; t < 8; t++) {
                    const bool first = (t == 4);
                    if (t == 4) {
#pragma unroll
                        for (int i = 0; i < 8; i++) {
                            asm volatile("ld.shared.v4.b32 {%0, %1, %2, %3}, [%4];" : "=r"(q[i][0]), "=r"(q[i][1]), "=r"(q[i][2]), "=r"(q[i][3])
                                         : "r"(mystage + (i * 128 + tid) * 16) : "memory");
                        }
                    }
                    turn_wait();
                    uint32_t stk = issue_s();
                    uint32_t stv = issue_pv(t == 1 || t == 5);
                    turn_pass();
                    wgmma_wait<1>();
                    fence_regs(s);
                    release(stk);
                    softmax(first);
                    asm volatile("{\n.reg .pred p;\nsetp.lt.f32 p, %0, 0fBF800000;\n@p st.shared.f32 [%1], %0;\n}\n" ::"f"(l0 + l1), "r"(mystage) : "memory");
                    wgmma_wait<0>();
                    fence_regs(o);
                    release(stv);
                    if (first) {
                        store_o(lo0, lo1, head0, false);
                    } else {
#pragma unroll
                        for (int jj = 0; jj < 16; jj++) {
                            o[4 * jj] *= a0; o[4 * jj + 1] *= a0; o[4 * jj + 2] *= a1; o[4 * jj + 3] *= a1;
                        }
                    }
                    convert_p();
                }
                {
                    turn_wait();
                    uint32_t stv = issue_pv(false);
                    turn_pass();
                    wgmma_wait<0>();
                    fence_regs(o);
                    release(stv);
                    store_o(l0, l1, head0 + 1, hp == 1);
                }
            }
        }
        TS(0, 4);
        {
            const int kq = j >> 1, n0 = (j & 1) * 320;
            float acc0[96], acc1[64];
            uint32_t st = 0, ph = 0, prev = 0;
            for (int i = 0; i < 16; i++) {
                mbar_wait(bars + 8 * (B2F + st), ph);
                if (i == 0) TS(0, 5);
                const uint32_t buf = base + st * P2_STAGE;
                wgmma_fence();
#pragma unroll
                for (int k = 0; k < 4; k++) {
                    uint64_t da = make_desc(buf + wg * 8192 + k * 32, 16, 1024, 1);
                    wgmma_ss_n192_t1(acc0, da, make_desc(buf + 16384 + k * 2048, 8192, 1024, 1), (i | k) != 0);
                    wgmma_ss_n128_t1(acc1, da, make_desc(buf + 16384 + 3 * 8192 + k * 2048, 8192, 1024, 1), (i | k) != 0);
                }
                wgmma_commit();
                if (i > 0) { wgmma_wait<1>(); arrive_both(bars + 8 * (B2E + prev)); }
                prev = st;
                if (++st == 4) { st = 0; ph ^= 1; }
            }
            wgmma_wait<0>();
            fence_regs(acc0); fence_regs(acc1);
            TS(0, 6);
            bar_sync(5, 256);
            TS(4, 0);
            const uint32_t stg = base + wg * 40960;
            const int mi = lane >> 3;
            const int row = warp * 16 + (mi & 1) * 8 + (lane & 7);
#pragma unroll
            for (int jj = 0; jj < 24; jj += 2) {
                const int grp = jj + (mi >> 1);
                stmatrix_x4(stg + (grp >> 3) * 8192 + row * 128 + (((grp & 7) ^ (row & 7)) << 4),
                            pack_bf16(acc0[4 * jj], acc0[4 * jj + 1]), pack_bf16(acc0[4 * jj + 2], acc0[4 * jj + 3]),
                            pack_bf16(acc0[4 * jj + 4], acc0[4 * jj + 5]), pack_bf16(acc0[4 * jj + 6], acc0[4 * jj + 7]));
            }
#pragma unroll
            for (int jj = 0; jj < 16; jj += 2) {
                const int grp = jj + (mi >> 1);
                stmatrix_x4(stg + (3 + (grp >> 3)) * 8192 + row * 128 + (((grp & 7) ^ (row & 7)) << 4),
                            pack_bf16(acc1[4 * jj], acc1[4 * jj + 1]), pack_bf16(acc1[4 * jj + 2], acc1[4 * jj + 3]),
                            pack_bf16(acc1[4 * jj + 4], acc1[4 * jj + 5]), pack_bf16(acc1[4 * jj + 6], acc1[4 * jj + 7]));
            }
            TS(4, 1);
            fence_proxy_async();
            bar_sync(1 + wg, 128);
            TS(4, 2);
            if (tid == 0) {
#pragma unroll
                for (int c = 0; c < 5; c++) tma_store_2d(&tm.part_st, stg + c * 8192, n0 + c * 64, kq * S_LEN + m0 + wg * 64);
                tma_store_commit();
                TS(4, 3);
                tma_store_wait<0>();
                TS(4, 4);
                mbar_arrive_cluster(bars + 8 * BD2, 0);
                mbar_arrive_cluster(bars + 8 * BD2, 1);
                flag_signal_relaxed(F_P + mt);
            }
        }
        TS(0, 7);
        {
            uint2 xr[2][5];
#pragma unroll
            for (int rr = 0; rr < 2; rr++)
#pragma unroll
                for (int i = 0; i < 5; i++)
                    xr[rr][i] = __ldg(reinterpret_cast<const uint2*>(x + (size_t)(m0 + j * 16 + cw * 2 + rr) * D_MODEL + (lane + 32 * i) * 4));
            if (threadIdx.x == 0) { flag_wait(F_MODALL, (epoch + 1) * 80); flag_wait(F_P + mt, (epoch + 1) * 16); }
            bar_sync(5, 256);
            TS(0, 8);
            uint2 pr[2][4][5];
            float4 gv[5];
#pragma unroll
            for (int rr = 0; rr < 2; rr++)
#pragma unroll
                for (int s = 0; s < 4; s++)
#pragma unroll
                    for (int i = 0; i < 5; i++)
                        pr[rr][s][i] = ldcg_u2(g_part + ((size_t)s * S_LEN + m0 + j * 16 + cw * 2 + rr) * D_MODEL + (lane + 32 * i) * 4);
#pragma unroll
            for (int i = 0; i < 5; i++) gv[i] = __ldcg(reinterpret_cast<const float4*>(g_mod + 2 * D_MODEL + (lane + 32 * i) * 4));
#pragma unroll
            for (int rr = 0; rr < 2; rr++) {
#pragma unroll
                for (int i = 0; i < 5; i++) {
                    float a0 = (bf16lo(pr[rr][0][i].x) + bf16lo(pr[rr][1][i].x)) + (bf16lo(pr[rr][2][i].x) + bf16lo(pr[rr][3][i].x));
                    float a1 = (bf16hi(pr[rr][0][i].x) + bf16hi(pr[rr][1][i].x)) + (bf16hi(pr[rr][2][i].x) + bf16hi(pr[rr][3][i].x));
                    float a2 = (bf16lo(pr[rr][0][i].y) + bf16lo(pr[rr][1][i].y)) + (bf16lo(pr[rr][2][i].y) + bf16lo(pr[rr][3][i].y));
                    float a3 = (bf16hi(pr[rr][0][i].y) + bf16hi(pr[rr][1][i].y)) + (bf16hi(pr[rr][2][i].y) + bf16hi(pr[rr][3][i].y));
                    xr[rr][i].x = pack_bf16(bf16lo(xr[rr][i].x) + gv[i].x * a0, bf16hi(xr[rr][i].x) + gv[i].y * a1);
                    xr[rr][i].y = pack_bf16(bf16lo(xr[rr][i].y) + gv[i].z * a2, bf16hi(xr[rr][i].y) + gv[i].w * a3);
                    *reinterpret_cast<uint2*>(g_x1 + (size_t)(m0 + j * 16 + cw * 2 + rr) * D_MODEL + (lane + 32 * i) * 4) = xr[rr][i];
                }
            }
            TS(5, 0);
            ln_rows(xr, g_mod + 3 * D_MODEL, g_mod + 4 * D_MODEL, g_h2 + (size_t)(m0 + j * 16 + cw * 2) * D_MODEL, lane);
            TS(5, 1);
            bar_sync(5, 256);
            TS(5, 2);
            if (threadIdx.x == 0) flag_signal(F_H2 + mt);
        }
        TS(0, 9);
        {
            const int f0 = j * 216;
            uint32_t st = 0, ph = 0, prev = 0;
            {
                float acc[128];
                if (wg == 1) bar_sync(6, 256);
                for (int i = 0; i < 10; i++) {
                    mbar_wait(bars + 8 * (B4F + st), ph);
                    if (i == 0) TS(0, 10);
                    const uint32_t buf = base + st * P4_STAGE;
                    wgmma_fence();
#pragma unroll
                    for (int k = 0; k < 4; k++) {
                        uint64_t da = make_desc(buf + wg * 8192 + k * 32, 16, 1024, 1);
                        uint64_t db = make_desc(buf + 16384 + k * 2048, 8192, 1024, 1);
                        wgmma_ss_n256_t1(acc, da, db, (i | k) != 0);
                    }
                    wgmma_commit();
                    if (i == 1 && wg == 0) bar_arrive(6, 256);
                    if (i > 0) { wgmma_wait<1>(); arrive_both(bars + 8 * (B4E + prev)); }
                    prev = st;
                    if (++st == 4) { st = 0; ph ^= 1; }
                }
                wgmma_wait<0>();
                arrive_both(bars + 8 * (B4E + prev));
                fence_regs(acc);
                TS(2, 0);
#pragma unroll
                for (int jj = 0; jj < 16; jj += 2) {
                    const int mi = lane >> 3;
                    const int row = warp * 16 + (mi & 1) * 8 + (lane & 7);
                    const int grp = jj + (mi >> 1);
                    const uint32_t addr = mystage + (grp >> 3) * 8192 + row * 128 + (((grp & 7) ^ (row & 7)) << 4);
                    stmatrix_x4(addr, pack_bf16(silu_mul(acc[4 * jj], acc[64 + 4 * jj]), silu_mul(acc[4 * jj + 1], acc[64 + 4 * jj + 1])),
                                pack_bf16(silu_mul(acc[4 * jj + 2], acc[64 + 4 * jj + 2]), silu_mul(acc[4 * jj + 3], acc[64 + 4 * jj + 3])),
                                pack_bf16(silu_mul(acc[4 * jj + 4], acc[64 + 4 * jj + 4]), silu_mul(acc[4 * jj + 5], acc[64 + 4 * jj + 5])),
                                pack_bf16(silu_mul(acc[4 * jj + 6], acc[64 + 4 * jj + 6]), silu_mul(acc[4 * jj + 7], acc[64 + 4 * jj + 7])));
                }
                fence_proxy_async();
                bar_sync(1 + wg, 128);
                TS(2, 1);
                if (tid == 0) {
                    tma_store_2d(&tm.act_st64, mystage, f0, m0 + wg * 64);
                    tma_store_2d(&tm.act_st64, mystage + 8192, f0 + 64, m0 + wg * 64);
                    tma_store_commit();
                }
                TS(2, 2);
            }
            {
                float acc[92];
                for (int i = 0; i < 10; i++) {
                    mbar_wait(bars + 8 * (B4F + st), ph);
                    const uint32_t buf = base + st * P4_STAGE;
                    wgmma_fence();
#pragma unroll
                    for (int k = 0; k < 4; k++) {
                        uint64_t da = make_desc(buf + wg * 8192 + k * 32, 16, 1024, 1);
                        uint64_t db = make_desc(buf + 16384 + k * 1024, 4096, 512, 2);
                        wgmma_ss_n184_t1(acc, da, db, (i | k) != 0);
                    }
                    wgmma_commit();
                    if (i == 3 && tid == 0) { tma_store_wait<0>(); flag_signal_relaxed(F_A1 + mt); }
                    if (i > 0) { wgmma_wait<1>(); arrive_both(bars + 8 * (B4E + prev)); }
                    prev = st;
                    if (++st == 4) { st = 0; ph ^= 1; }
                }
                wgmma_wait<0>();
                arrive_both(bars + 8 * BD4);
                fence_regs(acc);
                TS(0, 11);
                bar_sync(1 + wg, 128);
                TS(2, 3);
#pragma unroll
                for (int jj = 0; jj < 8; jj += 2) {
                    const int mi = lane >> 3;
                    const int row = warp * 16 + (mi & 1) * 8 + (lane & 7);
                    const int grp = jj + (mi >> 1);
                    const uint32_t addr = mystage + row * 128 + ((grp ^ (row & 7)) << 4);
                    stmatrix_x4(addr, pack_bf16(silu_mul(acc[4 * jj], acc[48 + 4 * jj]), silu_mul(acc[4 * jj + 1], acc[48 + 4 * jj + 1])),
                                pack_bf16(silu_mul(acc[4 * jj + 2], acc[48 + 4 * jj + 2]), silu_mul(acc[4 * jj + 3], acc[48 + 4 * jj + 3])),
                                pack_bf16(silu_mul(acc[4 * jj + 4], acc[48 + 4 * jj + 4]), silu_mul(acc[4 * jj + 5], acc[48 + 4 * jj + 5])),
                                pack_bf16(silu_mul(acc[4 * jj + 6], acc[48 + 4 * jj + 6]), silu_mul(acc[4 * jj + 7], acc[48 + 4 * jj + 7])));
                }
                {
                    const int mi = lane >> 3;
                    const int row = warp * 16 + (mi & 1) * 8 + (lane & 7);
                    const uint32_t addr = mystage + 8192 + row * 48 + (mi >> 1) * 16;
                    stmatrix_x4(addr, pack_bf16(silu_mul(acc[32], acc[80]), silu_mul(acc[33], acc[81])),
                                pack_bf16(silu_mul(acc[34], acc[82]), silu_mul(acc[35], acc[83])),
                                pack_bf16(silu_mul(acc[36], acc[84]), silu_mul(acc[37], acc[85])),
                                pack_bf16(silu_mul(acc[38], acc[86]), silu_mul(acc[39], acc[87])));
                    const uint32_t addr2 = mystage + 8192 + (warp * 16 + ((lane >> 3) & 1) * 8 + (lane & 7)) * 48 + 32;
                    asm volatile("stmatrix.sync.aligned.m8n8.x2.shared.b16 [%0], {%1, %2};" ::"r"(addr2),
                                 "r"(pack_bf16(silu_mul(acc[40], acc[88]), silu_mul(acc[41], acc[89]))),
                                 "r"(pack_bf16(silu_mul(acc[42], acc[90]), silu_mul(acc[43], acc[91]))) : "memory");
                }
                fence_proxy_async();
                bar_sync(1 + wg, 128);
                TS(2, 4);
                if (tid == 0) {
                    tma_store_2d(&tm.act_st64, mystage, f0 + 128, m0 + wg * 64);
                    tma_store_2d(&tm.act_st24, mystage + 8192, f0 + 192, m0 + wg * 64);
                    tma_store_commit();
                    TS(2, 5);
                    tma_store_wait<0>();
                    TS(2, 6);
                    mbar_arrive_cluster(bars + 8 * BD4B, 0);
                    mbar_arrive_cluster(bars + 8 * BD4B, 1);
                    TS(2, 7);
                    flag_signal_relaxed(F_A + mt);
                    TS(2, 8);
                }
            }
        }
        TS(0, 12);
        {
            const int m5 = (p * 2 + (j >> 2)) * 128, n0 = (j & 3) * 160;
            const int nkb = rank == 0 ? 14 : 13;
            float accA[64], accB[16];
            uint32_t st = 0, ph = 0, prev = 0;
            const int cbase = n0 + (int)rank * 80;
            for (int i = 0; i < nkb; i++) {
                mbar_wait(bars + 8 * (B5F + st), ph);
                if (i == 0) TS(0, 13);
                const uint32_t buf = base + st * P5_STAGE;
                wgmma_fence();
#pragma unroll
                for (int k = 0; k < 4; k++) {
                    uint64_t da = make_desc(buf + wg * 8192 + k * 32, 16, 1024, 1);
                    wgmma_ss_n128_t1(accA, da, make_desc(buf + 16384 + k * 2048, 8192, 1024, 1), (i | k) != 0);
                    wgmma_ss_n32_t1(accB, da, make_desc(buf + 32768 + k * 1024, 4096, 512, 2), (i | k) != 0);
                }
                wgmma_commit();
                if (i > 0) {
                    wgmma_wait<1>();
                    if (tid == 0) mbar_arrive(bars + 8 * (B5E + prev));
                }
                prev = st;
                if (++st == 5) { st = 0; ph ^= 1; }
            }
            uint4 xv[5];
            float2 gbv[10];
#pragma unroll
            for (int it = 0; it < 5; it++) {
                const int idx = it * 256 + (int)threadIdx.x;
                const int row = idx / 10, ch = idx - row * 10;
                xv[it] = __ldcg(reinterpret_cast<const uint4*>(g_x1 + (size_t)(m5 + row) * D_MODEL + cbase + ch * 8));
            }
#pragma unroll
            for (int jj = 0; jj < 10; jj++) gbv[jj] = __ldcg(reinterpret_cast<const float2*>(g_mod + 5 * D_MODEL + cbase + jj * 8 + (lane & 3) * 2));
            wgmma_wait<0>();
            fence_regs(accA); fence_regs(accB);
            float acc[80];
#pragma unroll
            for (int i = 0; i < 64; i++) acc[i] = accA[i];
#pragma unroll
            for (int i = 0; i < 16; i++) acc[64 + i] = accB[i];
            TS(0, 14);
            constexpr uint32_t XBUF = 5 * P5_STAGE;
            mbar_wait(bars + 8 * BD4B, 0);
            TS(3, 0);
            {
                const uint32_t dst = mapa(base + XBUF, rank ^ 1) + wg * 20480 + tid * 16;
                const uint32_t rbar = mapa(bars + 8 * BX, rank ^ 1);
                if (rank == 0) {
#pragma unroll
                    for (int i = 0; i < 10; i++)
                        asm volatile("st.async.shared::cluster.mbarrier::complete_tx::bytes.v4.f32 [%0], {%1, %2, %3, %4}, [%5];" ::"r"(dst + i * 2048),
                                     "f"(acc[40 + 4 * i]), "f"(acc[40 + 4 * i + 1]), "f"(acc[40 + 4 * i + 2]), "f"(acc[40 + 4 * i + 3]), "r"(rbar) : "memory");
                } else {
#pragma unroll
                    for (int i = 0; i < 10; i++)
                        asm volatile("st.async.shared::cluster.mbarrier::complete_tx::bytes.v4.f32 [%0], {%1, %2, %3, %4}, [%5];" ::"r"(dst + i * 2048),
                                     "f"(acc[4 * i]), "f"(acc[4 * i + 1]), "f"(acc[4 * i + 2]), "f"(acc[4 * i + 3]), "r"(rbar) : "memory");
                }
            }
            TS(3, 1);
            mbar_wait(bars + 8 * BX, 0);
            TS(3, 2);
            {
                bar_sync(5, 256);
                const uint32_t tile = base;
                TS(3, 3);
#pragma unroll
                for (int jj = 0; jj < 10; jj += 2) {
                    float4 o0, o1;
                    asm volatile("ld.shared.v4.f32 {%0, %1, %2, %3}, [%4];" : "=f"(o0.x), "=f"(o0.y), "=f"(o0.z), "=f"(o0.w) : "r"(base + XBUF + wg * 20480 + tid * 16 + jj * 2048));
                    asm volatile("ld.shared.v4.f32 {%0, %1, %2, %3}, [%4];" : "=f"(o1.x), "=f"(o1.y), "=f"(o1.z), "=f"(o1.w) : "r"(base + XBUF + wg * 20480 + tid * 16 + (jj + 1) * 2048));
                    const float2 g0 = gbv[jj], g1 = gbv[jj + 1];
                    float a[8];
#pragma unroll
                    for (int ee = 0; ee < 8; ee++) a[ee] = rank == 0 ? acc[4 * jj + ee] : acc[40 + 4 * jj + ee];
                    const int mi = lane >> 3;
                    const int row = wg * 64 + warp * 16 + (mi & 1) * 8 + (lane & 7);
                    const uint32_t addr = tile + row * 176 + (jj + (mi >> 1)) * 16;
                    stmatrix_x4(addr, pack_bf16(g0.x * bf16_round(a[0] + o0.x), g0.y * bf16_round(a[1] + o0.y)),
                                pack_bf16(g0.x * bf16_round(a[2] + o0.z), g0.y * bf16_round(a[3] + o0.w)),
                                pack_bf16(g1.x * bf16_round(a[4] + o1.x), g1.y * bf16_round(a[5] + o1.y)),
                                pack_bf16(g1.x * bf16_round(a[6] + o1.z), g1.y * bf16_round(a[7] + o1.w)));
                }
                TS(3, 4);
                bar_sync(5, 256);
                TS(3, 5);
#pragma unroll
                for (int it = 0; it < 5; it++) {
                    const int idx = it * 256 + (int)threadIdx.x;
                    const int row = idx / 10, ch = idx - row * 10;
                    uint4 tv;
                    asm volatile("ld.shared.v4.b32 {%0, %1, %2, %3}, [%4];" : "=r"(tv.x), "=r"(tv.y), "=r"(tv.z), "=r"(tv.w) : "r"(tile + row * 176 + ch * 16));
                    uint4 r;
                    r.x = pack_bf16(bf16lo(xv[it].x) + bf16lo(tv.x), bf16hi(xv[it].x) + bf16hi(tv.x));
                    r.y = pack_bf16(bf16lo(xv[it].y) + bf16lo(tv.y), bf16hi(xv[it].y) + bf16hi(tv.y));
                    r.z = pack_bf16(bf16lo(xv[it].z) + bf16lo(tv.z), bf16hi(xv[it].z) + bf16hi(tv.z));
                    r.w = pack_bf16(bf16lo(xv[it].w) + bf16lo(tv.w), bf16hi(xv[it].w) + bf16hi(tv.w));
                    *reinterpret_cast<uint4*>(out + (size_t)(m5 + row) * D_MODEL + cbase + ch * 8) = r;
                }
            }
            TS(0, 15);
            if (threadIdx.x == 0) {
                const unsigned old = atomicAdd(&g_exit, 1u);
                if (old == (epoch + 1) * 128u - 1u) {
                    asm volatile("st.volatile.global.u32 [%0], %1;" ::"l"(&g_epoch), "r"(epoch + 1) : "memory");
                }
            }
            asm volatile("barrier.cluster.arrive.relaxed.aligned;\n barrier.cluster.wait.aligned;" ::: "memory");
        }
    }
}

typedef CUresult (*PFN_encodeTiled)(CUtensorMap*, CUtensorMapDataType, cuuint32_t, void*, const cuuint64_t*, const cuuint64_t*,
                                    const cuuint32_t*, const cuuint32_t*, CUtensorMapInterleave, CUtensorMapSwizzle,
                                    CUtensorMapL2promotion, CUtensorMapFloatOOBfill);

static PFN_encodeTiled get_encode() {
    static PFN_encodeTiled fn = nullptr;
    if (!fn) {
        void* p = nullptr;
        cudaDriverEntryPointQueryResult qr;
        cudaGetDriverEntryPoint("cuTensorMapEncodeTiled", &p, cudaEnableDefault, &qr);
        fn = (PFN_encodeTiled)p;
    }
    return fn;
}

static CUtensorMap make_map(const void* ptr, uint64_t rows, uint64_t cols, uint32_t box_rows, uint32_t box_cols, CUtensorMapSwizzle swz) {
    CUtensorMap m;
    cuuint64_t dims[2] = {cols, rows};
    cuuint64_t strides[1] = {cols * 2};
    cuuint32_t box[2] = {box_cols, box_rows};
    cuuint32_t es[2] = {1, 1};
    get_encode()(&m, CU_TENSOR_MAP_DATA_TYPE_BFLOAT16, 2, const_cast<void*>(ptr), dims, strides, box, es, CU_TENSOR_MAP_INTERLEAVE_NONE,
                 swz, CU_TENSOR_MAP_L2_PROMOTION_L2_256B, CU_TENSOR_MAP_FLOAT_OOB_FILL_NONE);
    return m;
}

extern "C" void kernel_launch(void* const* d_in, const int* in_sizes, int n_in, void* d_out, int out_size) {
    (void)in_sizes; (void)n_in; (void)out_size;
    const __nv_bfloat16* x = (const __nv_bfloat16*)d_in[0];
    const __nv_bfloat16* kc = (const __nv_bfloat16*)d_in[1];
    const __nv_bfloat16* vc = (const __nv_bfloat16*)d_in[2];
    const __nv_bfloat16* wq = (const __nv_bfloat16*)d_in[3];
    const __nv_bfloat16* wo = (const __nv_bfloat16*)d_in[4];
    const __nv_bfloat16* wg = (const __nv_bfloat16*)d_in[6];
    const __nv_bfloat16* wu = (const __nv_bfloat16*)d_in[7];
    const __nv_bfloat16* wd = (const __nv_bfloat16*)d_in[8];
    const __nv_bfloat16* c = (const __nv_bfloat16*)d_in[9];
    const __nv_bfloat16* wmod = (const __nv_bfloat16*)d_in[10];
    __nv_bfloat16* out = (__nv_bfloat16*)d_out;

    static bool init = false;
    static void *p_h, *p_o, *p_x1, *p_h2, *p_act, *p_part;
    if (!init) {
        cudaFuncSetAttribute(mega_kernel, cudaFuncAttributeMaxDynamicSharedMemorySize, SM_TOTAL);
        cudaGetSymbolAddress(&p_h, g_h);
        cudaGetSymbolAddress(&p_o, g_o);
        cudaGetSymbolAddress(&p_x1, g_x1);
        cudaGetSymbolAddress(&p_h2, g_h2);
        cudaGetSymbolAddress(&p_act, g_act);
        cudaGetSymbolAddress(&p_part, g_part);
        init = true;
    }
    const CUtensorMapSwizzle S128 = CU_TENSOR_MAP_SWIZZLE_128B, S64 = CU_TENSOR_MAP_SWIZZLE_64B;
    Maps tm;
    tm.h = make_map(p_h, S_LEN, D_MODEL, 128, 64, S128);
    tm.wq = make_map(wq, D_MODEL, N_HEADS * D_HEAD, 64, 64, S128);
    tm.k = make_map(kc, N_HEADS * S_KV, D_HEAD, 128, 64, S128);
    tm.v = make_map(vc, N_HEADS * S_KV, D_HEAD, 128, 64, S128);
    tm.o_st = make_map(p_o, S_LEN, N_HEADS * D_HEAD, 64, 64, S128);
    tm.o_a = make_map(p_o, S_LEN, N_HEADS * D_HEAD, 128, 64, S128);
    tm.wo = make_map(wo, N_HEADS * D_HEAD, D_MODEL, 64, 64, S128);
    tm.part_st = make_map(p_part, 4 * S_LEN, D_MODEL, 64, 64, S128);
    tm.h2 = make_map(p_h2, S_LEN, D_MODEL, 128, 64, S128);
    tm.g128 = make_map(wg, D_MODEL, D_FF, 64, 64, S128);
    tm.u128 = make_map(wu, D_MODEL, D_FF, 64, 64, S128);
    tm.g64 = make_map(wg, D_MODEL, D_FF, 64, 32, S64);
    tm.u64 = make_map(wu, D_MODEL, D_FF, 64, 32, S64);
    tm.act_st64 = make_map(p_act, S_LEN, D_FF, 64, 64, S128);
    tm.act_st24 = make_map(p_act, S_LEN, D_FF, 64, 24, CU_TENSOR_MAP_SWIZZLE_NONE);
    tm.act_a = make_map(p_act, S_LEN, D_FF, 128, 64, S128);
    tm.wd = make_map(wd, D_FF, D_MODEL, 64, 64, S128);
    tm.wd32 = make_map(wd, D_FF, D_MODEL, 64, 32, S64);

    cudaLaunchConfig_t cfg = {};
    cfg.gridDim = dim3(128);
    cfg.blockDim = dim3(384);
    cfg.dynamicSmemBytes = SM_TOTAL;
    cfg.stream = cudaStreamPerThread;
    cfg.attrs = nullptr;
    cfg.numAttrs = 0;
    cudaLaunchKernelEx(&cfg, mega_kernel, tm, x, c, wmod, out, (const void*)wo, (const void*)wg, (const void*)wu, (const void*)wd);
}
```

```cpp
#include <cuda_runtime.h>
#include <cuda_bf16.h>
#include <cuda.h>
#include <stdint.h>

__device__ __forceinline__ uint32_t smem_u32(const void* p) { return (uint32_t)__cvta_generic_to_shared(p); }

__device__ __forceinline__ void mbar_init(uint32_t bar, uint32_t count) {
    asm volatile("mbarrier.init.shared::cta.b64 [%0], %1;" ::"r"(bar), "r"(count) : "memory");
}
__device__ __forceinline__ void mbar_expect_tx(uint32_t bar, uint32_t bytes) {
    asm volatile("mbarrier.arrive.expect_tx.shared::cta.b64 _, [%0], %1;" ::"r"(bar), "r"(bytes) : "memory");
}
__device__ __forceinline__ void mbar_arrive(uint32_t bar) {
    asm volatile("mbarrier.arrive.shared::cta.b64 _, [%0];" ::"r"(bar) : "memory");
}
__device__ __forceinline__ void mbar_arrive_cluster(uint32_t bar, uint32_t cta) {
    asm volatile(
        "{\n.reg .b32 ra;\n"
        "mapa.shared::cluster.u32 ra, %0, %1;\n"
        "mbarrier.arrive.shared::cluster.b64 _, [ra];\n}\n" ::"r"(bar), "r"(cta)
        : "memory");
}
__device__ __forceinline__ bool mbar_try_wait(uint32_t bar, uint32_t parity) {
    uint32_t ok;
    asm volatile(
        "{\n.reg .pred p;\n"
        "mbarrier.try_wait.parity.shared::cta.b64 p, [%1], %2;\n"
        "selp.u32 %0, 1, 0, p;\n}\n"
        : "=r"(ok)
        : "r"(bar), "r"(parity)
        : "memory");
    return ok != 0;
}
__device__ __forceinline__ bool mbar_try_wait_cluster(uint32_t bar, uint32_t parity) {
    uint32_t ok;
    asm volatile(
        "{\n.reg .pred p;\n"
        "mbarrier.try_wait.parity.shared::cta.b64 p, [%1], %2;\n"
        "selp.u32 %0, 1, 0, p;\n}\n"
        : "=r"(ok)
        : "r"(bar), "r"(parity)
        : "memory");
    return ok != 0;
}
__device__ volatile int g_abort = 0;
__device__ __forceinline__ void mbar_wait(uint32_t bar, uint32_t parity) {
    asm volatile(
        "{\n.reg .pred p;\n.reg .u32 n;\n"
        "mov.u32 n, 0;\n"
        "WAIT_LOOP:\n"
        "mbarrier.try_wait.parity.shared::cta.b64 p, [%0], %1;\n"
        "@p bra WAIT_DONE;\n"
        "add.u32 n, n, 1;\n"
        "setp.lt.u32 p, n, 16777216;\n"
        "@p bra WAIT_LOOP;\n"
        "WAIT_DONE:\n}\n" ::"r"(bar), "r"(parity) : "memory");
}
__device__ __forceinline__ void mbar_wait_cluster(uint32_t bar, uint32_t parity) { mbar_wait(bar, parity); }
__device__ __forceinline__ void fence_mbar_init() { asm volatile("fence.mbarrier_init.release.cluster;" ::: "memory"); }
__device__ __forceinline__ void fence_proxy_async() { asm volatile("fence.proxy.async.shared::cta;" ::: "memory"); }
__device__ __forceinline__ void fence_proxy_async_all() { asm volatile("fence.proxy.async;" ::: "memory"); }
__device__ __forceinline__ void cluster_arrive() { asm volatile("barrier.cluster.arrive.release.aligned;" ::: "memory"); }
__device__ __forceinline__ void cluster_wait() { asm volatile("barrier.cluster.wait.acquire.aligned;" ::: "memory"); }
__device__ __forceinline__ void cluster_sync() { cluster_arrive(); cluster_wait(); }
__device__ __forceinline__ uint32_t cluster_ctarank() {
    uint32_t r;
    asm volatile("mov.u32 %0, %%cluster_ctarank;" : "=r"(r));
    return r;
}
__device__ __forceinline__ void bar_sync(int id, int n) { asm volatile("bar.sync %0, %1;" ::"r"(id), "r"(n) : "memory"); }
__device__ __forceinline__ void bar_arrive(int id, int n) { asm volatile("bar.arrive %0, %1;" ::"r"(id), "r"(n) : "memory"); }
__device__ __forceinline__ void pdl_wait() { asm volatile("griddepcontrol.wait;" ::: "memory"); }
__device__ __forceinline__ void pdl_launch() { asm volatile("griddepcontrol.launch_dependents;" ::: "memory"); }

__device__ __forceinline__ void tma_prefetch_desc(const CUtensorMap* m) {
    asm volatile("prefetch.tensormap [%0];" ::"l"(m) : "memory");
}
__device__ __forceinline__ void tma_load_2d(uint32_t dst, const CUtensorMap* m, int c0, int c1, uint32_t bar) {
    asm volatile(
        "cp.async.bulk.tensor.2d.shared::cluster.global.mbarrier::complete_tx::bytes [%0], [%1, {%3, %4}], [%2];"
        ::"r"(dst), "l"(m), "r"(bar), "r"(c0), "r"(c1)
        : "memory");
}
__device__ __forceinline__ void tma_load_2d_mc(uint32_t dst, const CUtensorMap* m, int c0, int c1, uint32_t bar, uint16_t mask) {
    asm volatile(
        "cp.async.bulk.tensor.2d.shared::cluster.global.mbarrier::complete_tx::bytes.multicast::cluster [%0], [%1, {%3, %4}], [%2], %5;"
        ::"r"(dst), "l"(m), "r"(bar), "r"(c0), "r"(c1), "h"(mask)
        : "memory");
}
__device__ __forceinline__ void tma_store_2d(const CUtensorMap* m, uint32_t src, int c0, int c1) {
    asm volatile("cp.async.bulk.tensor.2d.global.shared::cta.bulk_group [%0, {%2, %3}], [%1];"
                 ::"l"(m), "r"(src), "r"(c0), "r"(c1)
                 : "memory");
}
__device__ __forceinline__ void tma_store_commit() { asm volatile("cp.async.bulk.commit_group;" ::: "memory"); }
template <int N> __device__ __forceinline__ void tma_store_wait_read() {
    asm volatile("cp.async.bulk.wait_group.read %0;" ::"n"(N) : "memory");
}
template <int N> __device__ __forceinline__ void tma_store_wait() {
    asm volatile("cp.async.bulk.wait_group %0;" ::"n"(N) : "memory");
}

__device__ __forceinline__ void wgmma_fence() { asm volatile("wgmma.fence.sync.aligned;" ::: "memory"); }
__device__ __forceinline__ void wgmma_commit() { asm volatile("wgmma.commit_group.sync.aligned;" ::: "memory"); }
template <int N> __device__ __forceinline__ void wgmma_wait() {
    asm volatile("wgmma.wait_group.sync.aligned %0;" ::"n"(N) : "memory");
}
template <int R> __device__ __forceinline__ void reg_alloc() { asm volatile("setmaxnreg.inc.sync.aligned.u32 %0;" ::"n"(R)); }
template <int R> __device__ __forceinline__ void reg_dealloc() { asm volatile("setmaxnreg.dec.sync.aligned.u32 %0;" ::"n"(R)); }

template <int N> __device__ __forceinline__ void fence_regs(float (&r)[N]) {
#pragma unroll
    for (int i = 0; i < N; i++) asm volatile("" : "+f"(r[i])::"memory");
}
template <int N> __device__ __forceinline__ void fence_regs_u(uint32_t (&r)[N][4]) {
#pragma unroll
    for (int i = 0; i < N; i++) {
#pragma unroll
        for (int j = 0; j < 4; j++) asm volatile("" : "+r"(r[i][j])::"memory");
    }
}

__device__ __forceinline__ uint64_t make_desc(uint32_t addr, uint32_t lbo_bytes, uint32_t sbo_bytes, uint32_t swz) {
    return (uint64_t)((addr & 0x3FFFF) >> 4) | ((uint64_t)(lbo_bytes >> 4) << 16) | ((uint64_t)(sbo_bytes >> 4) << 32) |
           ((uint64_t)swz << 62);
}

__device__ __forceinline__ uint32_t pack_bf16(float lo, float hi) {
    uint32_t r;
    asm("cvt.rn.bf16x2.f32 %0, %1, %2;" : "=r"(r) : "f"(hi), "f"(lo));
    return r;
}
__device__ __forceinline__ float bf16_round(float x) { return __bfloat162float(__float2bfloat16_rn(x)); }
__device__ __forceinline__ float bf16lo(uint32_t v) { return __uint_as_float(v << 16); }
__device__ __forceinline__ float bf16hi(uint32_t v) { return __uint_as_float(v & 0xffff0000u); }
__device__ __forceinline__ float ex2(float x) {
    float y;
    asm("ex2.approx.ftz.f32 %0, %1;" : "=f"(y) : "f"(x));
    return y;
}
__device__ __forceinline__ void stmatrix_x4(uint32_t addr, uint32_t r0, uint32_t r1, uint32_t r2, uint32_t r3) {
    asm volatile("stmatrix.sync.aligned.m8n8.x4.shared.b16 [%0], {%1, %2, %3, %4};" ::"r"(addr), "r"(r0), "r"(r1), "r"(r2), "r"(r3)
                 : "memory");
}
__device__ __forceinline__ uint32_t mapa(uint32_t addr, uint32_t cta) {
    uint32_t r;
    asm volatile("mapa.shared::cluster.u32 %0, %1, %2;" : "=r"(r) : "r"(addr), "r"(cta));
    return r;
}
__device__ __forceinline__ void st_cluster_v2(uint32_t addr, float a, float b) {
    asm volatile("st.shared::cluster.v2.f32 [%0], {%1, %2};" ::"r"(addr), "f"(a), "f"(b) : "memory");
}
__device__ __forceinline__ void wgmma_ss_n256_t1(float (&d)[128], uint64_t descA, uint64_t descB, int scaleD) {
    asm volatile("{\n.reg .pred p;\n"
        "setp.ne.b32 p, %130, 0;\n"
        "wgmma.mma_async.sync.aligned.m64n256k16.f32.bf16.bf16 "
        "{%0, %1, %2, %3, %4, %5, %6, %7, %8, %9, %10, %11, %12, %13, %14, %15, "
        "%16, %17, %18, %19, %20, %21, %22, %23, %24, %25, %26, %27, %28, %29, %30, %31, "
        "%32, %33, %34, %35, %36, %37, %38, %39, %40, %41, %42, %43, %44, %45, %46, %47, "
        "%48, %49, %50, %51, %52, %53, %54, %55, %56, %57, %58, %59, %60, %61, %62, %63, "
        "%64, %65, %66, %67, %68, %69, %70, %71, %72, %73, %74, %75, %76, %77, %78, %79, "
        "%80, %81, %82, %83, %84, %85, %86, %87, %88, %89, %90, %91, %92, %93, %94, %95, "
        "%96, %97, %98, %99, %100, %101, %102, %103, %104, %105, %106, %107, %108, %109, %110, %111, "
        "%112, %113, %114, %115, %116, %117, %118, %119, %120, %121, %122, %123, %124, %125, %126, %127}, "
        "%128, %129, p, 1, 1, 0, 1;\n}\n"
        :
          "+f"(d[0]), "+f"(d[1]), "+f"(d[2]), "+f"(d[3]), "+f"(d[4]), "+f"(d[5]), "+f"(d[6]), "+f"(d[7]),
          "+f"(d[8]), "+f"(d[9]), "+f"(d[10]), "+f"(d[11]), "+f"(d[12]), "+f"(d[13]), "+f"(d[14]), "+f"(d[15]),
          "+f"(d[16]), "+f"(d[17]), "+f"(d[18]), "+f"(d[19]), "+f"(d[20]), "+f"(d[21]), "+f"(d[22]), "+f"(d[23]),
          "+f"(d[24]), "+f"(d[25]), "+f"(d[26]), "+f"(d[27]), "+f"(d[28]), "+f"(d[29]), "+f"(d[30]), "+f"(d[31]),
          "+f"(d[32]), "+f"(d[33]), "+f"(d[34]), "+f"(d[35]), "+f"(d[36]), "+f"(d[37]), "+f"(d[38]), "+f"(d[39]),
          "+f"(d[40]), "+f"(d[41]), "+f"(d[42]), "+f"(d[43]), "+f"(d[44]), "+f"(d[45]), "+f"(d[46]), "+f"(d[47]),
          "+f"(d[48]), "+f"(d[49]), "+f"(d[50]), "+f"(d[51]), "+f"(d[52]), "+f"(d[53]), "+f"(d[54]), "+f"(d[55]),
          "+f"(d[56]), "+f"(d[57]), "+f"(d[58]), "+f"(d[59]), "+f"(d[60]), "+f"(d[61]), "+f"(d[62]), "+f"(d[63]),
          "+f"(d[64]), "+f"(d[65]), "+f"(d[66]), "+f"(d[67]), "+f"(d[68]), "+f"(d[69]), "+f"(d[70]), "+f"(d[71]),
          "+f"(d[72]), "+f"(d[73]), "+f"(d[74]), "+f"(d[75]), "+f"(d[76]), "+f"(d[77]), "+f"(d[78]), "+f"(d[79]),
          "+f"(d[80]), "+f"(d[81]), "+f"(d[82]), "+f"(d[83]), "+f"(d[84]), "+f"(d[85]), "+f"(d[86]), "+f"(d[87]),
          "+f"(d[88]), "+f"(d[89]), "+f"(d[90]), "+f"(d[91]), "+f"(d[92]), "+f"(d[93]), "+f"(d[94]), "+f"(d[95]),
          "+f"(d[96]), "+f"(d[97]), "+f"(d[98]), "+f"(d[99]), "+f"(d[100]), "+f"(d[101]), "+f"(d[102]), "+f"(d[103]),
          "+f"(d[104]), "+f"(d[105]), "+f"(d[106]), "+f"(d[107]), "+f"(d[108]), "+f"(d[109]), "+f"(d[110]), "+f"(d[111]),
          "+f"(d[112]), "+f"(d[113]), "+f"(d[114]), "+f"(d[115]), "+f"(d[116]), "+f"(d[117]), "+f"(d[118]), "+f"(d[119]),
          "+f"(d[120]), "+f"(d[121]), "+f"(d[122]), "+f"(d[123]), "+f"(d[124]), "+f"(d[125]), "+f"(d[126]), "+f"(d[127])
        : "l"(descA), "l"(descB), "r"(scaleD));
}

__device__ __forceinline__ void wgmma_rs_n128_t0(float (&d)[64], const uint32_t (&a)[4], uint64_t descB, int scaleD) {
    asm volatile("{\n.reg .pred p;\n"
        "setp.ne.b32 p, %69, 0;\n"
        "wgmma.mma_async.sync.aligned.m64n128k16.f32.bf16.bf16 "
        "{%0, %1, %2, %3, %4, %5, %6, %7, %8, %9, %10, %11, %12, %13, %14, %15, "
        "%16, %17, %18, %19, %20, %21, %22, %23, %24, %25, %26, %27, %28, %29, %30, %31, "
        "%32, %33, %34, %35, %36, %37, %38, %39, %40, %41, %42, %43, %44, %45, %46, %47, "
        "%48, %49, %50, %51, %52, %53, %54, %55, %56, %57, %58, %59, %60, %61, %62, %63}, "
        "{%64, %65, %66, %67}, %68, p, 1, 1, 0;\n}\n"
        :
          "+f"(d[0]), "+f"(d[1]), "+f"(d[2]), "+f"(d[3]), "+f"(d[4]), "+f"(d[5]), "+f"(d[6]), "+f"(d[7]),
          "+f"(d[8]), "+f"(d[9]), "+f"(d[10]), "+f"(d[11]), "+f"(d[12]), "+f"(d[13]), "+f"(d[14]), "+f"(d[15]),
          "+f"(d[16]), "+f"(d[17]), "+f"(d[18]), "+f"(d[19]), "+f"(d[20]), "+f"(d[21]), "+f"(d[22]), "+f"(d[23]),
          "+f"(d[24]), "+f"(d[25]), "+f"(d[26]), "+f"(d[27]), "+f"(d[28]), "+f"(d[29]), "+f"(d[30]), "+f"(d[31]),
          "+f"(d[32]), "+f"(d[33]), "+f"(d[34]), "+f"(d[35]), "+f"(d[36]), "+f"(d[37]), "+f"(d[38]), "+f"(d[39]),
          "+f"(d[40]), "+f"(d[41]), "+f"(d[42]), "+f"(d[43]), "+f"(d[44]), "+f"(d[45]), "+f"(d[46]), "+f"(d[47]),
          "+f"(d[48]), "+f"(d[49]), "+f"(d[50]), "+f"(d[51]), "+f"(d[52]), "+f"(d[53]), "+f"(d[54]), "+f"(d[55]),
          "+f"(d[56]), "+f"(d[57]), "+f"(d[58]), "+f"(d[59]), "+f"(d[60]), "+f"(d[61]), "+f"(d[62]), "+f"(d[63])
        : "r"(a[0]), "r"(a[1]), "r"(a[2]), "r"(a[3]), "l"(descB), "r"(scaleD));
}

__device__ __forceinline__ void wgmma_rs_n128_t0_z(float (&d)[64], const uint32_t (&a)[4], uint64_t descB) {
    asm volatile("{\n.reg .pred p;\n"
        "setp.ne.b32 p, 0, 0;\n"
        "wgmma.mma_async.sync.aligned.m64n128k16.f32.bf16.bf16 "
        "{%0, %1, %2, %3, %4, %5, %6, %7, %8, %9, %10, %11, %12, %13, %14, %15, "
        "%16, %17, %18, %19, %20, %21, %22, %23, %24, %25, %26, %27, %28, %29, %30, %31, "
        "%32, %33, %34, %35, %36, %37, %38, %39, %40, %41, %42, %43, %44, %45, %46, %47, "
        "%48, %49, %50, %51, %52, %53, %54, %55, %56, %57, %58, %59, %60, %61, %62, %63}, "
        "{%64, %65, %66, %67}, %68, p, 1, 1, 0;\n}\n"
        :
          "=f"(d[0]), "=f"(d[1]), "=f"(d[2]), "=f"(d[3]), "=f"(d[4]), "=f"(d[5]), "=f"(d[6]), "=f"(d[7]),
          "=f"(d[8]), "=f"(d[9]), "=f"(d[10]), "=f"(d[11]), "=f"(d[12]), "=f"(d[13]), "=f"(d[14]), "=f"(d[15]),
          "=f"(d[16]), "=f"(d[17]), "=f"(d[18]), "=f"(d[19]), "=f"(d[20]), "=f"(d[21]), "=f"(d[22]), "=f"(d[23]),
          "=f"(d[24]), "=f"(d[25]), "=f"(d[26]), "=f"(d[27]), "=f"(d[28]), "=f"(d[29]), "=f"(d[30]), "=f"(d[31]),
          "=f"(d[32]), "=f"(d[33]), "=f"(d[34]), "=f"(d[35]), "=f"(d[36]), "=f"(d[37]), "=f"(d[38]), "=f"(d[39]),
          "=f"(d[40]), "=f"(d[41]), "=f"(d[42]), "=f"(d[43]), "=f"(d[44]), "=f"(d[45]), "=f"(d[46]), "=f"(d[47]),
          "=f"(d[48]), "=f"(d[49]), "=f"(d[50]), "=f"(d[51]), "=f"(d[52]), "=f"(d[53]), "=f"(d[54]), "=f"(d[55]),
          "=f"(d[56]), "=f"(d[57]), "=f"(d[58]), "=f"(d[59]), "=f"(d[60]), "=f"(d[61]), "=f"(d[62]), "=f"(d[63])
        : "r"(a[0]), "r"(a[1]), "r"(a[2]), "r"(a[3]), "l"(descB));
}

__device__ __forceinline__ void wgmma_rs_n128_t1(float (&d)[64], const uint32_t (&a)[4], uint64_t descB, int scaleD) {
    asm volatile("{\n.reg .pred p;\n"
        "setp.ne.b32 p, %69, 0;\n"
        "wgmma.mma_async.sync.aligned.m64n128k16.f32.bf16.bf16 "
        "{%0, %1, %2, %3, %4, %5, %6, %7, %8, %9, %10, %11, %12, %13, %14, %15, "
        "%16, %17, %18, %19, %20, %21, %22, %23, %24, %25, %26, %27, %28, %29, %30, %31, "
        "%32, %33, %34, %35, %36, %37, %38, %39, %40, %41, %42, %43, %44, %45, %46, %47, "
        "%48, %49, %50, %51, %52, %53, %54, %55, %56, %57, %58, %59, %60, %61, %62, %63}, "
        "{%64, %65, %66, %67}, %68, p, 1, 1, 1;\n}\n"
        :
          "+f"(d[0]), "+f"(d[1]), "+f"(d[2]), "+f"(d[3]), "+f"(d[4]), "+f"(d[5]), "+f"(d[6]), "+f"(d[7]),
          "+f"(d[8]), "+f"(d[9]), "+f"(d[10]), "+f"(d[11]), "+f"(d[12]), "+f"(d[13]), "+f"(d[14]), "+f"(d[15]),
          "+f"(d[16]), "+f"(d[17]), "+f"(d[18]), "+f"(d[19]), "+f"(d[20]), "+f"(d[21]), "+f"(d[22]), "+f"(d[23]),
          "+f"(d[24]), "+f"(d[25]), "+f"(d[26]), "+f"(d[27]), "+f"(d[28]), "+f"(d[29]), "+f"(d[30]), "+f"(d[31]),
          "+f"(d[32]), "+f"(d[33]), "+f"(d[34]), "+f"(d[35]), "+f"(d[36]), "+f"(d[37]), "+f"(d[38]), "+f"(d[39]),
          "+f"(d[40]), "+f"(d[41]), "+f"(d[42]), "+f"(d[43]), "+f"(d[44]), "+f"(d[45]), "+f"(d[46]), "+f"(d[47]),
          "+f"(d[48]), "+f"(d[49]), "+f"(d[50]), "+f"(d[51]), "+f"(d[52]), "+f"(d[53]), "+f"(d[54]), "+f"(d[55]),
          "+f"(d[56]), "+f"(d[57]), "+f"(d[58]), "+f"(d[59]), "+f"(d[60]), "+f"(d[61]), "+f"(d[62]), "+f"(d[63])
        : "r"(a[0]), "r"(a[1]), "r"(a[2]), "r"(a[3]), "l"(descB), "r"(scaleD));
}

__device__ __forceinline__ void wgmma_ss_n184_t1(float (&d)[92], uint64_t descA, uint64_t descB, int scaleD) {
    asm volatile("{\n.reg .pred p;\n"
        "setp.ne.b32 p, %94, 0;\n"
        "wgmma.mma_async.sync.aligned.m64n184k16.f32.bf16.bf16 "
        "{%0, %1, %2, %3, %4, %5, %6, %7, %8, %9, %10, %11, %12, %13, %14, %15, "
        "%16, %17, %18, %19, %20, %21, %22, %23, %24, %25, %26, %27, %28, %29, %30, %31, "
        "%32, %33, %34, %35, %36, %37, %38, %39, %40, %41, %42, %43, %44, %45, %46, %47, "
        "%48, %49, %50, %51, %52, %53, %54, %55, %56, %57, %58, %59, %60, %61, %62, %63, "
        "%64, %65, %66, %67, %68, %69, %70, %71, %72, %73, %74, %75, %76, %77, %78, %79, "
        "%80, %81, %82, %83, %84, %85, %86, %87, %88, %89, %90, %91}, "
        "%92, %93, p, 1, 1, 0, 1;\n}\n"
        :
          "+f"(d[0]), "+f"(d[1]), "+f"(d[2]), "+f"(d[3]), "+f"(d[4]), "+f"(d[5]), "+f"(d[6]), "+f"(d[7]),
          "+f"(d[8]), "+f"(d[9]), "+f"(d[10]), "+f"(d[11]), "+f"(d[12]), "+f"(d[13]), "+f"(d[14]), "+f"(d[15]),
          "+f"(d[16]), "+f"(d[17]), "+f"(d[18]), "+f"(d[19]), "+f"(d[20]), "+f"(d[21]), "+f"(d[22]), "+f"(d[23]),
          "+f"(d[24]), "+f"(d[25]), "+f"(d[26]), "+f"(d[27]), "+f"(d[28]), "+f"(d[29]), "+f"(d[30]), "+f"(d[31]),
          "+f"(d[32]), "+f"(d[33]), "+f"(d[34]), "+f"(d[35]), "+f"(d[36]), "+f"(d[37]), "+f"(d[38]), "+f"(d[39]),
          "+f"(d[40]), "+f"(d[41]), "+f"(d[42]), "+f"(d[43]), "+f"(d[44]), "+f"(d[45]), "+f"(d[46]), "+f"(d[47]),
          "+f"(d[48]), "+f"(d[49]), "+f"(d[50]), "+f"(d[51]), "+f"(d[52]), "+f"(d[53]), "+f"(d[54]), "+f"(d[55]),
          "+f"(d[56]), "+f"(d[57]), "+f"(d[58]), "+f"(d[59]), "+f"(d[60]), "+f"(d[61]), "+f"(d[62]), "+f"(d[63]),
          "+f"(d[64]), "+f"(d[65]), "+f"(d[66]), "+f"(d[67]), "+f"(d[68]), "+f"(d[69]), "+f"(d[70]), "+f"(d[71]),
          "+f"(d[72]), "+f"(d[73]), "+f"(d[74]), "+f"(d[75]), "+f"(d[76]), "+f"(d[77]), "+f"(d[78]), "+f"(d[79]),
          "+f"(d[80]), "+f"(d[81]), "+f"(d[82]), "+f"(d[83]), "+f"(d[84]), "+f"(d[85]), "+f"(d[86]), "+f"(d[87]),
          "+f"(d[88]), "+f"(d[89]), "+f"(d[90]), "+f"(d[91])
        : "l"(descA), "l"(descB), "r"(scaleD));
}

__device__ __forceinline__ void wgmma_ss_n192_t1(float (&d)[96], uint64_t descA, uint64_t descB, int scaleD) {
    asm volatile("{\n.reg .pred p;\n"
        "setp.ne.b32 p, %98, 0;\n"
        "wgmma.mma_async.sync.aligned.m64n192k16.f32.bf16.bf16 "
        "{%0, %1, %2, %3, %4, %5, %6, %7, %8, %9, %10, %11, %12, %13, %14, %15, "
        "%16, %17, %18, %19, %20, %21, %22, %23, %24, %25, %26, %27, %28, %29, %30, %31, "
        "%32, %33, %34, %35, %36, %37, %38, %39, %40, %41, %42, %43, %44, %45, %46, %47, "
        "%48, %49, %50, %51, %52, %53, %54, %55, %56, %57, %58, %59, %60, %61, %62, %63, "
        "%64, %65, %66, %67, %68, %69, %70, %71, %72, %73, %74, %75, %76, %77, %78, %79, "
        "%80, %81, %82, %83, %84, %85, %86, %87, %88, %89, %90, %91, %92, %93, %94, %95}, "
        "%96, %97, p, 1, 1, 0, 1;\n}\n"
        :
          "+f"(d[0]), "+f"(d[1]), "+f"(d[2]), "+f"(d[3]), "+f"(d[4]), "+f"(d[5]), "+f"(d[6]), "+f"(d[7]),
          "+f"(d[8]), "+f"(d[9]), "+f"(d[10]), "+f"(d[11]), "+f"(d[12]), "+f"(d[13]), "+f"(d[14]), "+f"(d[15]),
          "+f"(d[16]), "+f"(d[17]), "+f"(d[18]), "+f"(d[19]), "+f"(d[20]), "+f"(d[21]), "+f"(d[22]), "+f"(d[23]),
          "+f"(d[24]), "+f"(d[25]), "+f"(d[26]), "+f"(d[27]), "+f"(d[28]), "+f"(d[29]), "+f"(d[30]), "+f"(d[31]),
          "+f"(d[32]), "+f"(d[33]), "+f"(d[34]), "+f"(d[35]), "+f"(d[36]), "+f"(d[37]), "+f"(d[38]), "+f"(d[39]),
          "+f"(d[40]), "+f"(d[41]), "+f"(d[42]), "+f"(d[43]), "+f"(d[44]), "+f"(d[45]), "+f"(d[46]), "+f"(d[47]),
          "+f"(d[48]), "+f"(d[49]), "+f"(d[50]), "+f"(d[51]), "+f"(d[52]), "+f"(d[53]), "+f"(d[54]), "+f"(d[55]),
          "+f"(d[56]), "+f"(d[57]), "+f"(d[58]), "+f"(d[59]), "+f"(d[60]), "+f"(d[61]), "+f"(d[62]), "+f"(d[63]),
          "+f"(d[64]), "+f"(d[65]), "+f"(d[66]), "+f"(d[67]), "+f"(d[68]), "+f"(d[69]), "+f"(d[70]), "+f"(d[71]),
          "+f"(d[72]), "+f"(d[73]), "+f"(d[74]), "+f"(d[75]), "+f"(d[76]), "+f"(d[77]), "+f"(d[78]), "+f"(d[79]),
          "+f"(d[80]), "+f"(d[81]), "+f"(d[82]), "+f"(d[83]), "+f"(d[84]), "+f"(d[85]), "+f"(d[86]), "+f"(d[87]),
          "+f"(d[88]), "+f"(d[89]), "+f"(d[90]), "+f"(d[91]), "+f"(d[92]), "+f"(d[93]), "+f"(d[94]), "+f"(d[95])
        : "l"(descA), "l"(descB), "r"(scaleD));
}

__device__ __forceinline__ void wgmma_ss_n128_t1(float (&d)[64], uint64_t descA, uint64_t descB, int scaleD) {
    asm volatile("{\n.reg .pred p;\n"
        "setp.ne.b32 p, %66, 0;\n"
        "wgmma.mma_async.sync.aligned.m64n128k16.f32.bf16.bf16 "
        "{%0, %1, %2, %3, %4, %5, %6, %7, %8, %9, %10, %11, %12, %13, %14, %15, "
        "%16, %17, %18, %19, %20, %21, %22, %23, %24, %25, %26, %27, %28, %29, %30, %31, "
        "%32, %33, %34, %35, %36, %37, %38, %39, %40, %41, %42, %43, %44, %45, %46, %47, "
        "%48, %49, %50, %51, %52, %53, %54, %55, %56, %57, %58, %59, %60, %61, %62, %63}, "
        "%64, %65, p, 1, 1, 0, 1;\n}\n"
        :
          "+f"(d[0]), "+f"(d[1]), "+f"(d[2]), "+f"(d[3]), "+f"(d[4]), "+f"(d[5]), "+f"(d[6]), "+f"(d[7]),
          "+f"(d[8]), "+f"(d[9]), "+f"(d[10]), "+f"(d[11]), "+f"(d[12]), "+f"(d[13]), "+f"(d[14]), "+f"(d[15]),
          "+f"(d[16]), "+f"(d[17]), "+f"(d[18]), "+f"(d[19]), "+f"(d[20]), "+f"(d[21]), "+f"(d[22]), "+f"(d[23]),
          "+f"(d[24]), "+f"(d[25]), "+f"(d[26]), "+f"(d[27]), "+f"(d[28]), "+f"(d[29]), "+f"(d[30]), "+f"(d[31]),
          "+f"(d[32]), "+f"(d[33]), "+f"(d[34]), "+f"(d[35]), "+f"(d[36]), "+f"(d[37]), "+f"(d[38]), "+f"(d[39]),
          "+f"(d[40]), "+f"(d[41]), "+f"(d[42]), "+f"(d[43]), "+f"(d[44]), "+f"(d[45]), "+f"(d[46]), "+f"(d[47]),
          "+f"(d[48]), "+f"(d[49]), "+f"(d[50]), "+f"(d[51]), "+f"(d[52]), "+f"(d[53]), "+f"(d[54]), "+f"(d[55]),
          "+f"(d[56]), "+f"(d[57]), "+f"(d[58]), "+f"(d[59]), "+f"(d[60]), "+f"(d[61]), "+f"(d[62]), "+f"(d[63])
        : "l"(descA), "l"(descB), "r"(scaleD));
}

__device__ __forceinline__ void wgmma_ss_n32_t1(float (&d)[16], uint64_t descA, uint64_t descB, int scaleD) {
    asm volatile("{\n.reg .pred p;\n"
        "setp.ne.b32 p, %18, 0;\n"
        "wgmma.mma_async.sync.aligned.m64n32k16.f32.bf16.bf16 "
        "{%0, %1, %2, %3, %4, %5, %6, %7, %8, %9, %10, %11, %12, %13, %14, %15}, "
        "%16, %17, p, 1, 1, 0, 1;\n}\n"
        :
          "+f"(d[0]), "+f"(d[1]), "+f"(d[2]), "+f"(d[3]), "+f"(d[4]), "+f"(d[5]), "+f"(d[6]), "+f"(d[7]),
          "+f"(d[8]), "+f"(d[9]), "+f"(d[10]), "+f"(d[11]), "+f"(d[12]), "+f"(d[13]), "+f"(d[14]), "+f"(d[15])
        : "l"(descA), "l"(descB), "r"(scaleD));
}

constexpr int S_LEN = 2048;
constexpr int D_MODEL = 640;
constexpr int N_HEADS = 32;
constexpr int D_HEAD = 128;
constexpr int S_KV = 2048;
constexpr int WIN = 512;
constexpr int D_FF = 1728;
constexpr float LN_EPS = 1e-5f;

#define TS(kid, slot)

__device__ float g_mod[6 * D_MODEL];
__device__ __align__(1024) __nv_bfloat16 g_h[S_LEN * D_MODEL];
__device__ __align__(1024) __nv_bfloat16 g_o[S_LEN * N_HEADS * D_HEAD];
__device__ __align__(1024) __nv_bfloat16 g_part[4 * S_LEN * D_MODEL];
__device__ __align__(1024) __nv_bfloat16 g_x1[S_LEN * D_MODEL];
__device__ __align__(1024) __nv_bfloat16 g_h2[S_LEN * D_MODEL];
__device__ __align__(1024) __nv_bfloat16 g_act[S_LEN * D_FF];

constexpr int F_MODAB = 0, F_MODALL = 1, F_H = 2, F_P = 18, F_H2 = 34, F_A = 50, F_O = 66, F_A1 = 130, F_COUNT = 146;
__device__ unsigned g_flags[F_COUNT * 32];
__device__ unsigned g_epoch;
__device__ unsigned g_exit;

__device__ __forceinline__ void flag_signal(int f) {
    asm volatile("red.release.gpu.global.add.u32 [%0], 1;" ::"l"(g_flags + f * 32) : "memory");
}
__device__ __forceinline__ void flag_signal_relaxed(int f) {
    asm volatile("fence.proxy.async;" ::: "memory");
    asm volatile("red.release.gpu.global.add.u32 [%0], 1;" ::"l"(g_flags + f * 32) : "memory");
}
__device__ __forceinline__ void flag_wait(int f, unsigned target) {
    unsigned n = 0;
    while (true) {
        unsigned v;
        asm volatile("ld.acquire.gpu.global.u32 %0, [%1];" : "=r"(v) : "l"(g_flags + f * 32) : "memory");
        if ((int)(v - target) >= 0) break;
        if ((++n & 0xfffu) == 0) {
            if (n > (1u << 24)) g_abort = 1;
            if (g_abort) break;
        }
    }
}

struct Maps {
    CUtensorMap h, wq, k, v, o_st, o_a, wo, part_st, h2, g128, u128, g64, u64, act_st64, act_st24, act_a, wd, wd32;
};

constexpr int SM_DATA = 229376;
constexpr int SM_STAGING = 196608;
constexpr int SM_TOTAL = SM_DATA + 1024 + 512;
constexpr int B1F = 0, B1E = 6, B2F = 12, B2E = 16, B4F = 20, B4E = 24, B5F = 28, B5E = 33, BD1 = 38, BD2 = 39, BD4 = 40, BD1A = 41, BX = 42, BD4B = 43, BHS = 44, BHF = 46;
constexpr int P1_STAGE = 32768, P2_STAGE = 57344, P4_STAGE = 49152, P5_STAGE = 36864;

__device__ __forceinline__ float rcp_approx(float x) { float y; asm("rcp.approx.ftz.f32 %0, %1;" : "=f"(y) : "f"(x)); return y; }
__device__ __forceinline__ float silu_mul(float g, float u) { return g * rcp_approx(1.f + ex2(-1.4426950408889634f * g)) * u; }
__device__ __forceinline__ uint2 ldcg_u2(const void* p) { return __ldcg(reinterpret_cast<const uint2*>(p)); }

__device__ __forceinline__ void ln_rows_impl(uint2 a0, uint2 a1, uint2 a2, uint2 a3, uint2 a4, uint2 b0, uint2 b1, uint2 b2, uint2 b3, uint2 b4,
                                          const float* __restrict__ shift, const float* __restrict__ scale1p,
                                          __nv_bfloat16* __restrict__ dst, int lane) {
    const uint2 xr[2][5] = {{a0, a1, a2, a3, a4}, {b0, b1, b2, b3, b4}};
    float4 sh[5], sc[5];
#pragma unroll
    for (int i = 0; i < 5; i++) {
        sh[i] = __ldcg(reinterpret_cast<const float4*>(shift + (lane + 32 * i) * 4));
        sc[i] = __ldcg(reinterpret_cast<const float4*>(scale1p + (lane + 32 * i) * 4));
    }
    float mean[2], rstd[2];
#pragma unroll
    for (int rr = 0; rr < 2; rr++) {
        float s = 0.f;
#pragma unroll
        for (int i = 0; i < 5; i++) s += (bf16lo(xr[rr][i].x) + bf16hi(xr[rr][i].x)) + (bf16lo(xr[rr][i].y) + bf16hi(xr[rr][i].y));
#pragma unroll
        for (int o = 16; o > 0; o >>= 1) s += __shfl_xor_sync(0xffffffffu, s, o);
        mean[rr] = s * (1.f / D_MODEL);
    }
#pragma unroll
    for (int rr = 0; rr < 2; rr++) {
        float q = 0.f;
#pragma unroll
        for (int i = 0; i < 5; i++) {
            const float d0 = bf16lo(xr[rr][i].x) - mean[rr], d1 = bf16hi(xr[rr][i].x) - mean[rr];
            const float d2 = bf16lo(xr[rr][i].y) - mean[rr], d3 = bf16hi(xr[rr][i].y) - mean[rr];
            q += (d0 * d0 + d1 * d1) + (d2 * d2 + d3 * d3);
        }
#pragma unroll
        for (int o = 16; o > 0; o >>= 1) q += __shfl_xor_sync(0xffffffffu, q, o);
        rstd[rr] = rsqrtf(q * (1.f / D_MODEL) + LN_EPS);
    }
#pragma unroll
    for (int rr = 0; rr < 2; rr++) {
#pragma unroll
        for (int i = 0; i < 5; i++) {
            uint2 u;
            u.x = pack_bf16((bf16lo(xr[rr][i].x) - mean[rr]) * rstd[rr] * sc[i].x + sh[i].x, (bf16hi(xr[rr][i].x) - mean[rr]) * rstd[rr] * sc[i].y + sh[i].y);
            u.y = pack_bf16((bf16lo(xr[rr][i].y) - mean[rr]) * rstd[rr] * sc[i].z + sh[i].z, (bf16hi(xr[rr][i].y) - mean[rr]) * rstd[rr] * sc[i].w + sh[i].w);
            *reinterpret_cast<uint2*>(dst + (size_t)rr * D_MODEL + (lane + 32 * i) * 4) = u;
        }
    }
}

__device__ __forceinline__ void ln_rows(const uint2 (&xr)[2][5], const float* shift, const float* scale1p, __nv_bfloat16* dst, int lane) {
    ln_rows_impl(xr[0][0], xr[0][1], xr[0][2], xr[0][3], xr[0][4], xr[1][0], xr[1][1], xr[1][2], xr[1][3], xr[1][4], shift, scale1p, dst, lane);
}

__global__ void __cluster_dims__(2, 1, 1) __launch_bounds__(384, 1)
mega_kernel(const __grid_constant__ Maps tm, const __nv_bfloat16* __restrict__ x, const __nv_bfloat16* __restrict__ cvec,
            const __nv_bfloat16* __restrict__ w_mod, __nv_bfloat16* __restrict__ out, const void* wo_p, const void* wg_p,
            const void* wu_p, const void* wd_p) {
    extern __shared__ uint8_t smem_raw[];
    const uint32_t base = (smem_u32(smem_raw) + 1023u) & ~1023u;
    const uint32_t bars = base + SM_DATA;
    const uint32_t rank = cluster_ctarank();
    const int cid = blockIdx.x >> 1;
    const int p = cid & 7, j = cid >> 3;
    const int mt = p * 2 + (int)rank;
    const int m0 = mt * 128;
    const int wg = threadIdx.x >> 7;
    unsigned epoch;
    asm volatile("ld.volatile.global.u32 %0, [%1];" : "=r"(epoch) : "l"(&g_epoch));

    uint2 xr[2][5];
    uint4 w[10];
    unsigned short cr[10];
    if (wg < 2) {
        const int cw = threadIdx.x >> 5, lane = threadIdx.x & 31;
        const int mb = blockIdx.x < 120 ? blockIdx.x : 0;
#pragma unroll
        for (int i = 0; i < 10; i++) cr[i] = __ldg(reinterpret_cast<const unsigned short*>(cvec) + cw * 80 + i * 8 + (lane >> 2));
#pragma unroll
        for (int i = 0; i < 10; i++)
            w[i] = __ldg(reinterpret_cast<const uint4*>(w_mod + (size_t)(cw * 80 + i * 8 + (lane >> 2)) * (6 * D_MODEL) + mb * 32 + (lane & 3) * 8));
#pragma unroll
        for (int rr = 0; rr < 2; rr++)
#pragma unroll
            for (int i = 0; i < 5; i++)
                xr[rr][i] = __ldg(reinterpret_cast<const uint2*>(x + (size_t)(m0 + j * 16 + cw * 2 + rr) * D_MODEL + (lane + 32 * i) * 4));
    }

    if (threadIdx.x == 0) {
        for (int i = 0; i < 6; i++) { mbar_init(bars + 8 * (B1F + i), 1); mbar_init(bars + 8 * (B1E + i), 4); }
        for (int i = 0; i < 4; i++) { mbar_init(bars + 8 * (B2F + i), 1); mbar_init(bars + 8 * (B2E + i), 4); }
        for (int i = 0; i < 4; i++) { mbar_init(bars + 8 * (B4F + i), 1); mbar_init(bars + 8 * (B4E + i), 4); }
        for (int i = 0; i < 5; i++) { mbar_init(bars + 8 * (B5F + i), 1); mbar_init(bars + 8 * (B5E + i), 2); }
        mbar_init(bars + 8 * BD1, 4); mbar_init(bars + 8 * BD2, 4); mbar_init(bars + 8 * BD4, 4); mbar_init(bars + 8 * BD1A, 8);
        for (int i = 0; i < 2; i++) { mbar_init(bars + 8 * (BHS + i), 1); mbar_init(bars + 8 * (BHF + i), 1); }
        mbar_init(bars + 8 * BX, 1); mbar_init(bars + 8 * BD4B, 4);
        mbar_expect_tx(bars + 8 * BX, 40960);
        fence_mbar_init();
    }
    __syncthreads();
    cluster_sync();

    if (wg == 2) {
        reg_dealloc<40>();
        if (threadIdx.x == 256) {
            {
                uint32_t st = 0, ph = 1;
                bool first = true;
#pragma unroll 1
                for (int hp = 0; hp < 2; hp++) {
                    const int head0 = j * 4 + hp * 2;
                    if (first) {
#pragma unroll 1
                        for (int s = 1; s < 6; s++) {
                            if (s == 3) continue;
                            const int kb = s < 3 ? s - 1 : s - 2;
                            mbar_expect_tx(bars + 8 * (B1F + s), P1_STAGE);
#pragma unroll 1
                            for (int c = 0; c < 2; c++) {
                                const int chunk = 2 * (int)rank + c;
                                tma_load_2d_mc(base + s * P1_STAGE + chunk * 8192, &tm.wq, head0 * 128 + chunk * 64, kb * 64, bars + 8 * (B1F + s), 3);
                            }
                        }
                        flag_wait(F_H + mt, (epoch + 1) * 8);
                        fence_proxy_async_all();
#pragma unroll 1
                        for (int s = 0; s < 6; s += 3) {
                            mbar_expect_tx(bars + 8 * (B1F + s), P1_STAGE);
                            tma_load_2d(base + s * P1_STAGE, &tm.h, (s / 3 * 2) * 64, m0, bars + 8 * (B1F + s));
                            tma_load_2d(base + s * P1_STAGE + 16384, &tm.h, (s / 3 * 2 + 1) * 64, m0, bars + 8 * (B1F + s));
                        }
                        ph = 0;
                    }
#pragma unroll 1
                    for (int kk2 = first ? 2 : 0; kk2 < 5; kk2++) {
                        mbar_wait(bars + 8 * (B1E + st), ph);
                        mbar_expect_tx(bars + 8 * (B1F + st), P1_STAGE);
                        tma_load_2d(base + st * P1_STAGE, &tm.h, (2 * kk2) * 64, m0, bars + 8 * (B1F + st));
                        tma_load_2d(base + st * P1_STAGE + 16384, &tm.h, (2 * kk2 + 1) * 64, m0, bars + 8 * (B1F + st));
                        if (++st == 6) { st = 0; ph ^= 1; }
#pragma unroll 1
                        for (int u = 0; u < 2; u++) {
                            mbar_wait(bars + 8 * (B1E + st), ph);
                            mbar_expect_tx(bars + 8 * (B1F + st), P1_STAGE);
                            const int kb = 2 * kk2 + u;
#pragma unroll 1
                            for (int c = 0; c < 2; c++) {
                                const int chunk = 2 * (int)rank + c;
                                tma_load_2d_mc(base + st * P1_STAGE + chunk * 8192, &tm.wq, head0 * 128 + chunk * 64, kb * 64, bars + 8 * (B1F + st), 3);
                            }
                            if (++st == 6) { st = 0; ph ^= 1; }
                        }
                    }
                    first = false;
#pragma unroll 1
                    for (int t = 0; t <= 8; t++) {
                        if (t < 8) {
                            mbar_wait(bars + 8 * (B1E + st), ph);
                            mbar_expect_tx(bars + 8 * (B1F + st), P1_STAGE);
                            const int row = (head0 + (t >> 2)) * S_KV + (S_KV - WIN) + (t & 3) * 128;
                            tma_load_2d_mc(base + st * P1_STAGE + rank * 16384, &tm.k, rank * 64, row, bars + 8 * (B1F + st), 3);
                            if (++st == 6) { st = 0; ph ^= 1; }
                        }
                        if (t > 0) {
                            mbar_wait(bars + 8 * (B1E + st), ph);
                            mbar_expect_tx(bars + 8 * (B1F + st), P1_STAGE);
                            const int tv = t - 1;
                            const int row = (head0 + (tv >> 2)) * S_KV + (S_KV - WIN) + (tv & 3) * 128;
                            tma_load_2d_mc(base + st * P1_STAGE + rank * 16384, &tm.v, rank * 64, row, bars + 8 * (B1F + st), 3);
                            if (++st == 6) { st = 0; ph ^= 1; }
                        }
                    }
                }
            }
            {
                const int kq = j >> 1, n0 = (j & 1) * 320;
                uint32_t st = 0, ph = 1;
#pragma unroll 1
                for (int i = 0; i < 16; i++) {
                    if (i == 0) mbar_wait(bars + 8 * BD1A, 0);
                    if (i == 3) mbar_wait(bars + 8 * BD1, 0);
                    if (i == 8) { flag_wait(F_O + mt * 4 + kq, (epoch + 1) * 4); fence_proxy_async_all(); }
                    mbar_wait(bars + 8 * (B2E + st), ph);
                    mbar_expect_tx(bars + 8 * (B2F + st), P2_STAGE);
                    const uint32_t dst = base + st * P2_STAGE;
                    const int k0 = kq * 1024 + ((i + (j & 1) * 8) & 15) * 64;
                    tma_load_2d(dst, &tm.o_a, k0, m0, bars + 8 * (B2F + st));
#pragma unroll 1
                    for (int c = 0; c < 5; c++)
                        if (((c + i) & 1) == (int)rank) tma_load_2d_mc(dst + 16384 + c * 8192, &tm.wo, n0 + c * 64, k0, bars + 8 * (B2F + st), 3);
                    if (++st == 4) { st = 0; ph ^= 1; }
                }
            }
            {
                const int f0 = j * 216;
                const CUtensorMap* t128 = rank == 0 ? &tm.g128 : &tm.u128;
                const CUtensorMap* t64 = rank == 0 ? &tm.g64 : &tm.u64;
                mbar_wait(bars + 8 * BD2, 0);
#pragma unroll 1
                for (int i = 0; i < 4; i++) {
                    mbar_expect_tx(bars + 8 * (B4F + i), 16384 + 32768);
                    const uint32_t dst = base + i * P4_STAGE;
                    tma_load_2d_mc(dst + 16384 + rank * 16384, t128, f0, i * 64, bars + 8 * (B4F + i), 3);
                    tma_load_2d_mc(dst + 16384 + rank * 16384 + 8192, t128, f0 + 64, i * 64, bars + 8 * (B4F + i), 3);
                }
                flag_wait(F_H2 + mt, (epoch + 1) * 8);
                fence_proxy_async_all();
#pragma unroll 1
                for (int i = 0; i < 4; i++) tma_load_2d(base + i * P4_STAGE, &tm.h2, i * 64, m0, bars + 8 * (B4F + i));
                uint32_t st = 0, ph = 0;
#pragma unroll 1
                for (int i = 4; i < 20; i++) {
                    const int kb = i < 10 ? i : i - 10;
                    mbar_wait(bars + 8 * (B4E + st), ph);
                    const uint32_t dst = base + st * P4_STAGE;
                    if (i < 10) {
                        mbar_expect_tx(bars + 8 * (B4F + st), 16384 + 32768);
                        tma_load_2d(dst, &tm.h2, kb * 64, m0, bars + 8 * (B4F + st));
                        tma_load_2d_mc(dst + 16384 + rank * 16384, t128, f0, kb * 64, bars + 8 * (B4F + st), 3);
                        tma_load_2d_mc(dst + 16384 + rank * 16384 + 8192, t128, f0 + 64, kb * 64, bars + 8 * (B4F + st), 3);
                    } else {
                        mbar_expect_tx(bars + 8 * (B4F + st), 16384 + 24576);
                        tma_load_2d(dst, &tm.h2, kb * 64, m0, bars + 8 * (B4F + st));
#pragma unroll 1
                        for (int c = 0; c < 3; c++)
                            tma_load_2d_mc(dst + 16384 + rank * 12288 + c * 4096, t64, f0 + 128 + c * 32, kb * 64, bars + 8 * (B4F + st), 3);
                    }
                    if (++st == 4) { st = 0; ph ^= 1; }
                }
            }
            {
                const int mt5 = p * 2 + (j >> 2), n0 = (j & 3) * 160;
                const int nkb = rank == 0 ? 14 : 13;
                const unsigned long long ord = rank == 0
                    ? (0ull | 1ull << 5 | 4ull << 10 | 7ull << 15 | 11ull << 20 | 2ull << 25 | 3ull << 30 | 5ull << 35 | 6ull << 40 | 8ull << 45 | 9ull << 50 | 10ull << 55)
                    : (14ull | 17ull << 5 | 21ull << 10 | 24ull << 15 | 15ull << 20 | 16ull << 25 | 18ull << 30 | 19ull << 35 | 20ull << 40 | 22ull << 45 | 23ull << 50 | 25ull << 55);
                const int nearly = rank == 0 ? 5 : 4;
                mbar_wait(bars + 8 * BD4, 0);
                uint32_t st = 0, ph = 1;
#pragma unroll 1
                for (int i = 0; i < nkb; i++) {
                    const int kb = i < 12 ? (int)((ord >> (5 * i)) & 31) : (rank == 0 ? i : 26);
                    if (i == 0) { flag_wait(F_A1 + mt5, (epoch + 1) * 16); fence_proxy_async_all(); }
                    if (i == nearly) { flag_wait(F_A + mt5, (epoch + 1) * 16); fence_proxy_async_all(); }
                    mbar_wait(bars + 8 * (B5E + st), ph);
                    mbar_expect_tx(bars + 8 * (B5F + st), P5_STAGE);
                    const uint32_t dst = base + st * P5_STAGE;
                    const int k0 = kb * 64;
                    tma_load_2d(dst + 16384, &tm.wd, n0, k0, bars + 8 * (B5F + st));
                    tma_load_2d(dst + 16384 + 8192, &tm.wd, n0 + 64, k0, bars + 8 * (B5F + st));
                    tma_load_2d(dst + 16384 + 16384, &tm.wd32, n0 + 128, k0, bars + 8 * (B5F + st));
                    tma_load_2d(dst, &tm.act_a, k0, mt5 * 128, bars + 8 * (B5F + st));
                    if (++st == 5) { st = 0; ph ^= 1; }
                }
            }
        }
        else if (threadIdx.x >= 320 && (threadIdx.x & 31) == 0) {
            const int hw = (threadIdx.x - 320) >> 5;
            const uint32_t stg = base + SM_STAGING + hw * 16384;
            const int r0 = m0 + hw * 64;
            auto both = [&](int b) { mbar_arrive_cluster(bars + 8 * b, 0); mbar_arrive_cluster(bars + 8 * b, 1); };
#pragma unroll 1
            for (int job = 0; job < 7; job++) {
                mbar_wait(bars + 8 * (BHS + hw), job & 1);
                if (job < 4) {
                    tma_store_2d(&tm.o_st, stg, (j * 4 + job) * 128, r0);
                    tma_store_2d(&tm.o_st, stg + 8192, (j * 4 + job) * 128 + 64, r0);
                } else if (job == 4) {
#pragma unroll 1
                    for (int c = 0; c < 5; c++)
                        tma_store_2d(&tm.part_st, base + hw * 40960 + c * 8192, (j & 1) * 320 + c * 64, (j >> 1) * S_LEN + r0);
                } else {
                    tma_store_2d(&tm.act_st64, stg, j * 216 + (job - 5) * 128, r0);
                    tma_store_2d(job == 5 ? &tm.act_st64 : &tm.act_st24, stg + 8192, j * 216 + (job - 5) * 128 + 64, r0);
                }
                tma_store_commit();
                tma_store_wait_read<0>();
                mbar_arrive(bars + 8 * (BHF + hw));
                if (job >= 2) {
                    tma_store_wait<0>();
                    if (job == 2) both(BD1A);
                    else if (job == 3) { both(BD1); flag_signal_relaxed(F_O + mt * 4 + (j >> 1)); }
                    else if (job == 4) { both(BD2); flag_signal_relaxed(F_P + mt); }
                    else if (job == 5) flag_signal_relaxed(F_A1 + mt);
                    else { both(BD4B); flag_signal_relaxed(F_A + mt); }
                }
            }
        }
        else if (threadIdx.x == 288) {
            mbar_wait(bars + 8 * B1F, 0);
            const char* pw[4] = {(const char*)wo_p, (const char*)wg_p, (const char*)wu_p, (const char*)wd_p};
#pragma unroll 1
            for (int t = 0; t < 4; t++) {
                const uint32_t bytes = t == 0 ? 40960u : 17280u;
                asm volatile("cp.async.bulk.prefetch.L2.global [%0], %1;" ::"l"(pw[t] + (size_t)blockIdx.x * bytes), "r"(bytes) : "memory");
            }
        }
        __syncwarp();
        asm volatile("barrier.cluster.arrive.relaxed.aligned; // producer\n barrier.cluster.wait.aligned;" ::: "memory");
    } else {
        reg_alloc<232>();
        const int tid = threadIdx.x & 127;
        const int warp = tid >> 5, lane = tid & 31;
        const int cw = threadIdx.x >> 5;
        const uint32_t mystage = base + SM_STAGING + wg * 16384;
        auto arrive_both = [&](uint32_t bar) {
            if (tid == 0) mbar_arrive_cluster(bar, 0);
            if (tid == 32) mbar_arrive_cluster(bar, 1);
        };
        uint32_t njobs = 0;
        auto staging_free = [&]() { if (njobs > 0) mbar_wait(bars + 8 * (BHF + wg), (njobs - 1) & 1); };
        auto submit_job = [&]() {
            fence_proxy_async();
            bar_sync(1 + wg, 128);
            if (tid == 0) mbar_arrive(bars + 8 * (BHS + wg));
            njobs++;
        };
        TS(0, 0);
        {
            if (blockIdx.x < 120) {
                float* red = reinterpret_cast<float*>(smem_raw + (base - smem_u32(smem_raw)) + SM_STAGING);
                float acc[8];
#pragma unroll
                for (int i = 0; i < 8; i++) acc[i] = 0.f;
#pragma unroll
                for (int i = 0; i < 10; i++) {
                    const float s = bf16_round(silu_mul(__uint_as_float((uint32_t)cr[i] << 16), 1.f));
                    acc[0] += s * bf16lo(w[i].x); acc[1] += s * bf16hi(w[i].x);
                    acc[2] += s * bf16lo(w[i].y); acc[3] += s * bf16hi(w[i].y);
                    acc[4] += s * bf16lo(w[i].z); acc[5] += s * bf16hi(w[i].z);
                    acc[6] += s * bf16lo(w[i].w); acc[7] += s * bf16hi(w[i].w);
                }
#pragma unroll
                for (int i = 0; i < 8; i++) {
                    acc[i] += __shfl_xor_sync(0xffffffffu, acc[i], 4);
                    acc[i] += __shfl_xor_sync(0xffffffffu, acc[i], 8);
                    acc[i] += __shfl_xor_sync(0xffffffffu, acc[i], 16);
                }
                if (lane < 4) {
#pragma unroll
                    for (int i = 0; i < 8; i++) red[cw * 32 + lane * 8 + i] = acc[i];
                }
                TS(6, 0);
                bar_sync(5, 256);
                TS(6, 1);
                if (threadIdx.x < 32) {
                    float t = 0.f;
#pragma unroll
                    for (int i = 0; i < 8; i++) t += red[i * 32 + threadIdx.x];
                    t = bf16_round(t);
                    const int chunk = blockIdx.x / 20;
                    if (chunk == 1 || chunk == 4) t = bf16_round(1.f + t);
                    g_mod[blockIdx.x * 32 + threadIdx.x] = t;
                    __syncwarp();
                    TS(6, 2);
                    if (threadIdx.x == 0) flag_signal(blockIdx.x < 40 ? F_MODAB : F_MODALL);
                    TS(6, 3);
                }
            }
            if (threadIdx.x == 0) flag_wait(F_MODAB, (epoch + 1) * 40);
            bar_sync(5, 256);
            TS(0, 1);
            ln_rows(xr, g_mod, g_mod + D_MODEL, g_h + (size_t)(m0 + j * 16 + cw * 2) * D_MODEL, lane);
            TS(6, 4);
            bar_sync(5, 256);
            TS(6, 5);
            if (threadIdx.x == 0) flag_signal(F_H + mt);
        }
        TS(0, 2);
        {
            const float cscale = 0.08838834764831845f * 1.4426950408889634f;
            uint32_t st = 0, ph = 0;
            auto wait_full = [&]() -> uint32_t {
                mbar_wait(bars + 8 * (B1F + st), ph);
                return base + st * P1_STAGE;
            };
            auto release = [&](uint32_t s) { arrive_both(bars + 8 * (B1E + s)); };
            auto advance = [&]() { if (++st == 6) { st = 0; ph ^= 1; } };
            auto turn_wait = [&]() { bar_sync(3 + wg, 256); };
            auto turn_pass = [&]() { bar_arrive(3 + (wg ^ 1), 256); };
            if (wg == 1) bar_arrive(3, 256);

            for (int hp = 0; hp < 2; hp++) {
                const int head0 = j * 4 + hp * 2;
                uint32_t q[8][4];
                {
                    float acc[128];
#pragma unroll
                    for (int i = 0; i < 128; i++) acc[i] = 0.f;
                    for (int kk2 = 0; kk2 < 5; kk2++) {
                        const uint32_t hbuf = wait_full();
                        if (kk2 == 0 && hp == 0) TS(0, 3);
                        const uint32_t sth = st;
                        advance();
#pragma unroll
                        for (int u = 0; u < 2; u++) {
                            const uint32_t wbuf = wait_full();
                            const uint32_t stw = st;
                            advance();
                            wgmma_fence();
#pragma unroll
                            for (int k = 0; k < 4; k++) {
                                uint64_t da = make_desc(hbuf + u * 16384 + wg * 8192 + k * 32, 16, 1024, 1);
                                uint64_t db = make_desc(wbuf + k * 2048, 8192, 1024, 1);
                                wgmma_ss_n256_t1(acc, da, db, 1);
                            }
                            wgmma_commit();
                            wgmma_wait<0>();
                            release(stw);
                        }
                        release(sth);
                    }
                    fence_regs(acc);
                    staging_free();
#pragma unroll
                    for (int i = 0; i < 8; i++) {
                        q[i][0] = pack_bf16(acc[8 * i + 0], acc[8 * i + 1]);
                        q[i][1] = pack_bf16(acc[8 * i + 2], acc[8 * i + 3]);
                        q[i][2] = pack_bf16(acc[8 * i + 4], acc[8 * i + 5]);
                        q[i][3] = pack_bf16(acc[8 * i + 6], acc[8 * i + 7]);
                        uint32_t b0 = pack_bf16(acc[64 + 8 * i + 0], acc[64 + 8 * i + 1]);
                        uint32_t b1 = pack_bf16(acc[64 + 8 * i + 2], acc[64 + 8 * i + 3]);
                        uint32_t b2 = pack_bf16(acc[64 + 8 * i + 4], acc[64 + 8 * i + 5]);
                        uint32_t b3 = pack_bf16(acc[64 + 8 * i + 6], acc[64 + 8 * i + 7]);
                        asm volatile("st.shared.v4.b32 [%0], {%1, %2, %3, %4};" ::"r"(mystage + (i * 128 + tid) * 16), "r"(b0), "r"(b1),
                                     "r"(b2), "r"(b3) : "memory");
                    }
                }
                float o[64], s[64], e[64];
                uint32_t pp[8][4];
                float mm0, mm1, l0, l1, a0, a1, lo0, lo1;
#pragma unroll
                for (int i = 0; i < 64; i++) { o[i] = 0.f; }

                auto issue_s = [&]() -> uint32_t {
                    const uint32_t kbuf = wait_full();
                    const uint32_t stk = st;
                    advance();
                    wgmma_fence();
#pragma unroll
                    for (int k = 0; k < 8; k++) {
                        uint64_t db = make_desc(kbuf + (k >> 2) * 16384 + (k & 3) * 32, 16, 1024, 1);
                        if (k == 0) wgmma_rs_n128_t0_z(s, q[k], db);
                        else wgmma_rs_n128_t0(s, q[k], db, 1);
                    }
                    wgmma_commit();
                    return stk;
                };
                auto issue_pv = [&](bool fresh) -> uint32_t {
                    const uint32_t vbuf = wait_full();
                    const uint32_t stv = st;
                    advance();
                    wgmma_fence();
#pragma unroll
                    for (int k = 0; k < 8; k++) {
                        uint64_t db = make_desc(vbuf + k * 2048, 16384, 1024, 1);
                        wgmma_rs_n128_t1(o, pp[k], db, (!fresh) || k != 0);
                    }
                    wgmma_commit();
                    return stv;
                };
                auto softmax = [&](bool first) {
                    float mx0 = fmaxf(s[0], s[1]), mx1 = fmaxf(s[2], s[3]);
#pragma unroll
                    for (int jj = 1; jj < 16; jj++) {
                        mx0 = fmaxf(mx0, fmaxf(s[4 * jj], s[4 * jj + 1]));
                        mx1 = fmaxf(mx1, fmaxf(s[4 * jj + 2], s[4 * jj + 3]));
                    }
                    mx0 = fmaxf(mx0, __shfl_xor_sync(0xffffffffu, mx0, 1));
                    mx0 = fmaxf(mx0, __shfl_xor_sync(0xffffffffu, mx0, 2));
                    mx1 = fmaxf(mx1, __shfl_xor_sync(0xffffffffu, mx1, 1));
                    mx1 = fmaxf(mx1, __shfl_xor_sync(0xffffffffu, mx1, 2));
                    if (first) {
                        lo0 = l0; lo1 = l1;
                        mm0 = mx0; mm1 = mx1; l0 = 0.f; l1 = 0.f; a0 = 0.f; a1 = 0.f;
                    } else {
                        float mn0 = fmaxf(mm0, mx0), mn1 = fmaxf(mm1, mx1);
                        a0 = ex2((mm0 - mn0) * cscale); a1 = ex2((mm1 - mn1) * cscale);
                        mm0 = mn0; mm1 = mn1;
                    }
                    const float mc0 = mm0 * cscale, mc1 = mm1 * cscale;
                    float r0 = 0.f, r1 = 0.f;
#pragma unroll
                    for (int jj = 0; jj < 16; jj++) {
                        e[4 * jj] = ex2(fmaf(s[4 * jj], cscale, -mc0));
                        e[4 * jj + 1] = ex2(fmaf(s[4 * jj + 1], cscale, -mc0));
                        e[4 * jj + 2] = ex2(fmaf(s[4 * jj + 2], cscale, -mc1));
                        e[4 * jj + 3] = ex2(fmaf(s[4 * jj + 3], cscale, -mc1));
                        r0 += e[4 * jj] + e[4 * jj + 1];
                        r1 += e[4 * jj + 2] + e[4 * jj + 3];
                    }
                    l0 = l0 * a0 + r0; l1 = l1 * a1 + r1;
                };
                auto convert_p = [&]() {
#pragma unroll
                    for (int i = 0; i < 8; i++) {
                        pp[i][0] = pack_bf16(e[8 * i + 0], e[8 * i + 1]);
                        pp[i][1] = pack_bf16(e[8 * i + 2], e[8 * i + 3]);
                        pp[i][2] = pack_bf16(e[8 * i + 4], e[8 * i + 5]);
                        pp[i][3] = pack_bf16(e[8 * i + 6], e[8 * i + 7]);
                    }
                };
                auto store_o = [&](float ls0, float ls1, int head, bool last) {
                    float s0 = ls0 + __shfl_xor_sync(0xffffffffu, ls0, 1); s0 += __shfl_xor_sync(0xffffffffu, s0, 2);
                    float s1 = ls1 + __shfl_xor_sync(0xffffffffu, ls1, 1); s1 += __shfl_xor_sync(0xffffffffu, s1, 2);
                    const float i0 = 1.f / s0, i1 = 1.f / s1;
                    if (last) arrive_both(bars + 8 * BD1A);
                    staging_free();
                    bar_sync(1 + wg, 128);
#pragma unroll
                    for (int jj = 0; jj < 16; jj += 2) {
                        const int mi = lane >> 3;
                        const int row = warp * 16 + (mi & 1) * 8 + (lane & 7);
                        const int grp = jj + (mi >> 1);
                        const uint32_t addr = mystage + (grp >> 3) * 8192 + row * 128 + (((grp & 7) ^ (row & 7)) << 4);
                        stmatrix_x4(addr, pack_bf16(o[4 * jj] * i0, o[4 * jj + 1] * i0), pack_bf16(o[4 * jj + 2] * i1, o[4 * jj + 3] * i1),
                                    pack_bf16(o[4 * jj + 4] * i0, o[4 * jj + 5] * i0), pack_bf16(o[4 * jj + 6] * i1, o[4 * jj + 7] * i1));
                    }
                    submit_job();
                };

                l0 = 0.f; l1 = 0.f;
                {
                    turn_wait();
                    uint32_t stk = issue_s();
                    turn_pass();
                    wgmma_wait<0>();
                    fence_regs(s);
                    release(stk);
                    softmax(true);
                    convert_p();
                }
#pragma unroll 1
                for (int t = 1; t < 8; t++) {
                    const bool first = (t == 4);
                    if (t == 4) {
#pragma unroll
                        for (int i = 0; i < 8; i++) {
                            asm volatile("ld.shared.v4.b32 {%0, %1, %2, %3}, [%4];" : "=r"(q[i][0]), "=r"(q[i][1]), "=r"(q[i][2]), "=r"(q[i][3])
                                         : "r"(mystage + (i * 128 + tid) * 16) : "memory");
                        }
                    }
                    turn_wait();
                    uint32_t stk = issue_s();
                    uint32_t stv = issue_pv(t == 1 || t == 5);
                    turn_pass();
                    wgmma_wait<1>();
                    fence_regs(s);
                    release(stk);
                    softmax(first);
                    asm volatile("{\n.reg .pred p;\nsetp.lt.f32 p, %0, 0fBF800000;\n@p st.shared.f32 [%1], %0;\n}\n" ::"f"(l0 + l1), "r"(mystage) : "memory");
                    wgmma_wait<0>();
                    fence_regs(o);
                    release(stv);
                    if (first) {
                        store_o(lo0, lo1, head0, false);
                    } else {
#pragma unroll
                        for (int jj = 0; jj < 16; jj++) {
                            o[4 * jj] *= a0; o[4 * jj + 1] *= a0; o[4 * jj + 2] *= a1; o[4 * jj + 3] *= a1;
                        }
                    }
                    convert_p();
                }
                {
                    turn_wait();
                    uint32_t stv = issue_pv(false);
                    turn_pass();
                    wgmma_wait<0>();
                    fence_regs(o);
                    release(stv);
                    store_o(l0, l1, head0 + 1, hp == 1);
                }
            }
        }
        TS(0, 4);
        {
            const int kq = j >> 1, n0 = (j & 1) * 320;
            float acc0[96], acc1[64];
            uint32_t st = 0, ph = 0, prev = 0;
            for (int i = 0; i < 16; i++) {
                mbar_wait(bars + 8 * (B2F + st), ph);
                if (i == 0) TS(0, 5);
                const uint32_t buf = base + st * P2_STAGE;
                wgmma_fence();
#pragma unroll
                for (int k = 0; k < 4; k++) {
                    uint64_t da = make_desc(buf + wg * 8192 + k * 32, 16, 1024, 1);
                    wgmma_ss_n192_t1(acc0, da, make_desc(buf + 16384 + k * 2048, 8192, 1024, 1), (i | k) != 0);
                    wgmma_ss_n128_t1(acc1, da, make_desc(buf + 16384 + 3 * 8192 + k * 2048, 8192, 1024, 1), (i | k) != 0);
                }
                wgmma_commit();
                if (i > 0) { wgmma_wait<1>(); arrive_both(bars + 8 * (B2E + prev)); }
                prev = st;
                if (++st == 4) { st = 0; ph ^= 1; }
            }
            wgmma_wait<0>();
            fence_regs(acc0); fence_regs(acc1);
            TS(0, 6);
            bar_sync(5, 256);
            staging_free();
            const uint32_t stg = base + wg * 40960;
            const int mi = lane >> 3;
            const int row = warp * 16 + (mi & 1) * 8 + (lane & 7);
#pragma unroll
            for (int jj = 0; jj < 24; jj += 2) {
                const int grp = jj + (mi >> 1);
                stmatrix_x4(stg + (grp >> 3) * 8192 + row * 128 + (((grp & 7) ^ (row & 7)) << 4),
                            pack_bf16(acc0[4 * jj], acc0[4 * jj + 1]), pack_bf16(acc0[4 * jj + 2], acc0[4 * jj + 3]),
                            pack_bf16(acc0[4 * jj + 4], acc0[4 * jj + 5]), pack_bf16(acc0[4 * jj + 6], acc0[4 * jj + 7]));
            }
#pragma unroll
            for (int jj = 0; jj < 16; jj += 2) {
                const int grp = jj + (mi >> 1);
                stmatrix_x4(stg + (3 + (grp >> 3)) * 8192 + row * 128 + (((grp & 7) ^ (row & 7)) << 4),
                            pack_bf16(acc1[4 * jj], acc1[4 * jj + 1]), pack_bf16(acc1[4 * jj + 2], acc1[4 * jj + 3]),
                            pack_bf16(acc1[4 * jj + 4], acc1[4 * jj + 5]), pack_bf16(acc1[4 * jj + 6], acc1[4 * jj + 7]));
            }
            submit_job();
        }
        TS(0, 7);
        {
            uint2 xr[2][5];
#pragma unroll
            for (int rr = 0; rr < 2; rr++)
#pragma unroll
                for (int i = 0; i < 5; i++)
                    xr[rr][i] = __ldg(reinterpret_cast<const uint2*>(x + (size_t)(m0 + j * 16 + cw * 2 + rr) * D_MODEL + (lane + 32 * i) * 4));
            if (threadIdx.x == 0) { flag_wait(F_MODALL, (epoch + 1) * 80); flag_wait(F_P + mt, (epoch + 1) * 16); }
            bar_sync(5, 256);
            TS(0, 8);
            uint2 pr[2][4][5];
            float4 gv[5];
#pragma unroll
            for (int rr = 0; rr < 2; rr++)
#pragma unroll
                for (int s = 0; s < 4; s++)
#pragma unroll
                    for (int i = 0; i < 5; i++)
                        pr[rr][s][i] = ldcg_u2(g_part + ((size_t)s * S_LEN + m0 + j * 16 + cw * 2 + rr) * D_MODEL + (lane + 32 * i) * 4);
#pragma unroll
            for (int i = 0; i < 5; i++) gv[i] = __ldcg(reinterpret_cast<const float4*>(g_mod + 2 * D_MODEL + (lane + 32 * i) * 4));
#pragma unroll
            for (int rr = 0; rr < 2; rr++) {
#pragma unroll
                for (int i = 0; i < 5; i++) {
                    float a0 = (bf16lo(pr[rr][0][i].x) + bf16lo(pr[rr][1][i].x)) + (bf16lo(pr[rr][2][i].x) + bf16lo(pr[rr][3][i].x));
                    float a1 = (bf16hi(pr[rr][0][i].x) + bf16hi(pr[rr][1][i].x)) + (bf16hi(pr[rr][2][i].x) + bf16hi(pr[rr][3][i].x));
                    float a2 = (bf16lo(pr[rr][0][i].y) + bf16lo(pr[rr][1][i].y)) + (bf16lo(pr[rr][2][i].y) + bf16lo(pr[rr][3][i].y));
                    float a3 = (bf16hi(pr[rr][0][i].y) + bf16hi(pr[rr][1][i].y)) + (bf16hi(pr[rr][2][i].y) + bf16hi(pr[rr][3][i].y));
                    xr[rr][i].x = pack_bf16(bf16lo(xr[rr][i].x) + gv[i].x * a0, bf16hi(xr[rr][i].x) + gv[i].y * a1);
                    xr[rr][i].y = pack_bf16(bf16lo(xr[rr][i].y) + gv[i].z * a2, bf16hi(xr[rr][i].y) + gv[i].w * a3);
                    *reinterpret_cast<uint2*>(g_x1 + (size_t)(m0 + j * 16 + cw * 2 + rr) * D_MODEL + (lane + 32 * i) * 4) = xr[rr][i];
                }
            }
            TS(5, 0);
            ln_rows(xr, g_mod + 3 * D_MODEL, g_mod + 4 * D_MODEL, g_h2 + (size_t)(m0 + j * 16 + cw * 2) * D_MODEL, lane);
            TS(5, 1);
            bar_sync(5, 256);
            TS(5, 2);
            if (threadIdx.x == 0) flag_signal(F_H2 + mt);
        }
        TS(0, 9);
        {
            const int f0 = j * 216;
            uint32_t st = 0, ph = 0, prev = 0;
            {
                float acc[128];
                if (wg == 1) bar_sync(6, 256);
                for (int i = 0; i < 10; i++) {
                    mbar_wait(bars + 8 * (B4F + st), ph);
                    if (i == 0) TS(0, 10);
                    const uint32_t buf = base + st * P4_STAGE;
                    wgmma_fence();
#pragma unroll
                    for (int k = 0; k < 4; k++) {
                        uint64_t da = make_desc(buf + wg * 8192 + k * 32, 16, 1024, 1);
                        uint64_t db = make_desc(buf + 16384 + k * 2048, 8192, 1024, 1);
                        wgmma_ss_n256_t1(acc, da, db, (i | k) != 0);
                    }
                    wgmma_commit();
                    if (i == 1 && wg == 0) bar_arrive(6, 256);
                    if (i > 0) { wgmma_wait<1>(); arrive_both(bars + 8 * (B4E + prev)); }
                    prev = st;
                    if (++st == 4) { st = 0; ph ^= 1; }
                }
                wgmma_wait<0>();
                arrive_both(bars + 8 * (B4E + prev));
                fence_regs(acc);
                staging_free();
#pragma unroll
                for (int jj = 0; jj < 16; jj += 2) {
                    const int mi = lane >> 3;
                    const int row = warp * 16 + (mi & 1) * 8 + (lane & 7);
                    const int grp = jj + (mi >> 1);
                    const uint32_t addr = mystage + (grp >> 3) * 8192 + row * 128 + (((grp & 7) ^ (row & 7)) << 4);
                    stmatrix_x4(addr, pack_bf16(silu_mul(acc[4 * jj], acc[64 + 4 * jj]), silu_mul(acc[4 * jj + 1], acc[64 + 4 * jj + 1])),
                                pack_bf16(silu_mul(acc[4 * jj + 2], acc[64 + 4 * jj + 2]), silu_mul(acc[4 * jj + 3], acc[64 + 4 * jj + 3])),
                                pack_bf16(silu_mul(acc[4 * jj + 4], acc[64 + 4 * jj + 4]), silu_mul(acc[4 * jj + 5], acc[64 + 4 * jj + 5])),
                                pack_bf16(silu_mul(acc[4 * jj + 6], acc[64 + 4 * jj + 6]), silu_mul(acc[4 * jj + 7], acc[64 + 4 * jj + 7])));
                }
                submit_job();
            }
            {
                float acc[92];
                for (int i = 0; i < 10; i++) {
                    mbar_wait(bars + 8 * (B4F + st), ph);
                    const uint32_t buf = base + st * P4_STAGE;
                    wgmma_fence();
#pragma unroll
                    for (int k = 0; k < 4; k++) {
                        uint64_t da = make_desc(buf + wg * 8192 + k * 32, 16, 1024, 1);
                        uint64_t db = make_desc(buf + 16384 + k * 1024, 4096, 512, 2);
                        wgmma_ss_n184_t1(acc, da, db, (i | k) != 0);
                    }
                    wgmma_commit();
                    if (i > 0) { wgmma_wait<1>(); arrive_both(bars + 8 * (B4E + prev)); }
                    prev = st;
                    if (++st == 4) { st = 0; ph ^= 1; }
                }
                wgmma_wait<0>();
                arrive_both(bars + 8 * BD4);
                fence_regs(acc);
                TS(0, 11);
                staging_free();
#pragma unroll
                for (int jj = 0; jj < 8; jj += 2) {
                    const int mi = lane >> 3;
                    const int row = warp * 16 + (mi & 1) * 8 + (lane & 7);
                    const int grp = jj + (mi >> 1);
                    const uint32_t addr = mystage + row * 128 + ((grp ^ (row & 7)) << 4);
                    stmatrix_x4(addr, pack_bf16(silu_mul(acc[4 * jj], acc[48 + 4 * jj]), silu_mul(acc[4 * jj + 1], acc[48 + 4 * jj + 1])),
                                pack_bf16(silu_mul(acc[4 * jj + 2], acc[48 + 4 * jj + 2]), silu_mul(acc[4 * jj + 3], acc[48 + 4 * jj + 3])),
                                pack_bf16(silu_mul(acc[4 * jj + 4], acc[48 + 4 * jj + 4]), silu_mul(acc[4 * jj + 5], acc[48 + 4 * jj + 5])),
                                pack_bf16(silu_mul(acc[4 * jj + 6], acc[48 + 4 * jj + 6]), silu_mul(acc[4 * jj + 7], acc[48 + 4 * jj + 7])));
                }
                {
                    const int mi = lane >> 3;
                    const int row = warp * 16 + (mi & 1) * 8 + (lane & 7);
                    const uint32_t addr = mystage + 8192 + row * 48 + (mi >> 1) * 16;
                    stmatrix_x4(addr, pack_bf16(silu_mul(acc[32], acc[80]), silu_mul(acc[33], acc[81])),
                                pack_bf16(silu_mul(acc[34], acc[82]), silu_mul(acc[35], acc[83])),
                                pack_bf16(silu_mul(acc[36], acc[84]), silu_mul(acc[37], acc[85])),
                                pack_bf16(silu_mul(acc[38], acc[86]), silu_mul(acc[39], acc[87])));
                    const uint32_t addr2 = mystage + 8192 + (warp * 16 + ((lane >> 3) & 1) * 8 + (lane & 7)) * 48 + 32;
                    asm volatile("stmatrix.sync.aligned.m8n8.x2.shared.b16 [%0], {%1, %2};" ::"r"(addr2),
                                 "r"(pack_bf16(silu_mul(acc[40], acc[88]), silu_mul(acc[41], acc[89]))),
                                 "r"(pack_bf16(silu_mul(acc[42], acc[90]), silu_mul(acc[43], acc[91]))) : "memory");
                }
                submit_job();
            }
        }
        TS(0, 12);
        {
            const int m5 = (p * 2 + (j >> 2)) * 128, n0 = (j & 3) * 160;
            const int nkb = rank == 0 ? 14 : 13;
            float accA[64], accB[16];
            uint32_t st = 0, ph = 0, prev = 0;
            const int cbase = n0 + (int)rank * 80;
            for (int i = 0; i < nkb; i++) {
                mbar_wait(bars + 8 * (B5F + st), ph);
                if (i == 0) TS(0, 13);
                const uint32_t buf = base + st * P5_STAGE;
                wgmma_fence();
#pragma unroll
                for (int k = 0; k < 4; k++) {
                    uint64_t da = make_desc(buf + wg * 8192 + k * 32, 16, 1024, 1);
                    wgmma_ss_n128_t1(accA, da, make_desc(buf + 16384 + k * 2048, 8192, 1024, 1), (i | k) != 0);
                    wgmma_ss_n32_t1(accB, da, make_desc(buf + 32768 + k * 1024, 4096, 512, 2), (i | k) != 0);
                }
                wgmma_commit();
                if (i > 0) {
                    wgmma_wait<1>();
                    if (tid == 0) mbar_arrive(bars + 8 * (B5E + prev));
                }
                prev = st;
                if (++st == 5) { st = 0; ph ^= 1; }
            }
            uint4 xv[5];
            float2 gbv[10];
#pragma unroll
            for (int it = 0; it < 5; it++) {
                const int idx = it * 256 + (int)threadIdx.x;
                const int row = idx / 10, ch = idx - row * 10;
                xv[it] = __ldcg(reinterpret_cast<const uint4*>(g_x1 + (size_t)(m5 + row) * D_MODEL + cbase + ch * 8));
            }
#pragma unroll
            for (int jj = 0; jj < 10; jj++) gbv[jj] = __ldcg(reinterpret_cast<const float2*>(g_mod + 5 * D_MODEL + cbase + jj * 8 + (lane & 3) * 2));
            wgmma_wait<0>();
            fence_regs(accA); fence_regs(accB);
            float acc[80];
#pragma unroll
            for (int i = 0; i < 64; i++) acc[i] = accA[i];
#pragma unroll
            for (int i = 0; i < 16; i++) acc[64 + i] = accB[i];
            TS(0, 14);
            constexpr uint32_t XBUF = 5 * P5_STAGE;
            mbar_wait(bars + 8 * BD4B, 0);
            TS(3, 0);
            {
                const uint32_t dst = mapa(base + XBUF, rank ^ 1) + wg * 20480 + tid * 16;
                const uint32_t rbar = mapa(bars + 8 * BX, rank ^ 1);
                if (rank == 0) {
#pragma unroll
                    for (int i = 0; i < 10; i++)
                        asm volatile("st.async.shared::cluster.mbarrier::complete_tx::bytes.v4.f32 [%0], {%1, %2, %3, %4}, [%5];" ::"r"(dst + i * 2048),
                                     "f"(acc[40 + 4 * i]), "f"(acc[40 + 4 * i + 1]), "f"(acc[40 + 4 * i + 2]), "f"(acc[40 + 4 * i + 3]), "r"(rbar) : "memory");
                } else {
#pragma unroll
                    for (int i = 0; i < 10; i++)
                        asm volatile("st.async.shared::cluster.mbarrier::complete_tx::bytes.v4.f32 [%0], {%1, %2, %3, %4}, [%5];" ::"r"(dst + i * 2048),
                                     "f"(acc[4 * i]), "f"(acc[4 * i + 1]), "f"(acc[4 * i + 2]), "f"(acc[4 * i + 3]), "r"(rbar) : "memory");
                }
            }
            TS(3, 1);
            mbar_wait(bars + 8 * BX, 0);
            TS(3, 2);
            {
                bar_sync(5, 256);
                const uint32_t tile = base;
                TS(3, 3);
#pragma unroll
                for (int jj = 0; jj < 10; jj += 2) {
                    float4 o0, o1;
                    asm volatile("ld.shared.v4.f32 {%0, %1, %2, %3}, [%4];" : "=f"(o0.x), "=f"(o0.y), "=f"(o0.z), "=f"(o0.w) : "r"(base + XBUF + wg * 20480 + tid * 16 + jj * 2048));
                    asm volatile("ld.shared.v4.f32 {%0, %1, %2, %3}, [%4];" : "=f"(o1.x), "=f"(o1.y), "=f"(o1.z), "=f"(o1.w) : "r"(base + XBUF + wg * 20480 + tid * 16 + (jj + 1) * 2048));
                    const float2 g0 = gbv[jj], g1 = gbv[jj + 1];
                    float a[8];
#pragma unroll
                    for (int ee = 0; ee < 8; ee++) a[ee] = rank == 0 ? acc[4 * jj + ee] : acc[40 + 4 * jj + ee];
                    const int mi = lane >> 3;
                    const int row = wg * 64 + warp * 16 + (mi & 1) * 8 + (lane & 7);
                    const uint32_t addr = tile + row * 176 + (jj + (mi >> 1)) * 16;
                    stmatrix_x4(addr, pack_bf16(g0.x * bf16_round(a[0] + o0.x), g0.y * bf16_round(a[1] + o0.y)),
                                pack_bf16(g0.x * bf16_round(a[2] + o0.z), g0.y * bf16_round(a[3] + o0.w)),
                                pack_bf16(g1.x * bf16_round(a[4] + o1.x), g1.y * bf16_round(a[5] + o1.y)),
                                pack_bf16(g1.x * bf16_round(a[6] + o1.z), g1.y * bf16_round(a[7] + o1.w)));
                }
                TS(3, 4);
                bar_sync(5, 256);
                TS(3, 5);
#pragma unroll
                for (int it = 0; it < 5; it++) {
                    const int idx = it * 256 + (int)threadIdx.x;
                    const int row = idx / 10, ch = idx - row * 10;
                    uint4 tv;
                    asm volatile("ld.shared.v4.b32 {%0, %1, %2, %3}, [%4];" : "=r"(tv.x), "=r"(tv.y), "=r"(tv.z), "=r"(tv.w) : "r"(tile + row * 176 + ch * 16));
                    uint4 r;
                    r.x = pack_bf16(bf16lo(xv[it].x) + bf16lo(tv.x), bf16hi(xv[it].x) + bf16hi(tv.x));
                    r.y = pack_bf16(bf16lo(xv[it].y) + bf16lo(tv.y), bf16hi(xv[it].y) + bf16hi(tv.y));
                    r.z = pack_bf16(bf16lo(xv[it].z) + bf16lo(tv.z), bf16hi(xv[it].z) + bf16hi(tv.z));
                    r.w = pack_bf16(bf16lo(xv[it].w) + bf16lo(tv.w), bf16hi(xv[it].w) + bf16hi(tv.w));
                    *reinterpret_cast<uint4*>(out + (size_t)(m5 + row) * D_MODEL + cbase + ch * 8) = r;
                }
            }
            TS(0, 15);
            if (threadIdx.x == 0) {
                const unsigned old = atomicAdd(&g_exit, 1u);
                if (old == (epoch + 1) * 128u - 1u) {
                    asm volatile("st.volatile.global.u32 [%0], %1;" ::"l"(&g_epoch), "r"(epoch + 1) : "memory");
                }
            }
            asm volatile("barrier.cluster.arrive.relaxed.aligned;\n barrier.cluster.wait.aligned;" ::: "memory");
        }
    }
}

typedef CUresult (*PFN_encodeTiled)(CUtensorMap*, CUtensorMapDataType, cuuint32_t, void*, const cuuint64_t*, const cuuint64_t*,
                                    const cuuint32_t*, const cuuint32_t*, CUtensorMapInterleave, CUtensorMapSwizzle,
                                    CUtensorMapL2promotion, CUtensorMapFloatOOBfill);

static PFN_encodeTiled get_encode() {
    static PFN_encodeTiled fn = nullptr;
    if (!fn) {
        void* p = nullptr;
        cudaDriverEntryPointQueryResult qr;
        cudaGetDriverEntryPoint("cuTensorMapEncodeTiled", &p, cudaEnableDefault, &qr);
        fn = (PFN_encodeTiled)p;
    }
    return fn;
}

static CUtensorMap make_map(const void* ptr, uint64_t rows, uint64_t cols, uint32_t box_rows, uint32_t box_cols, CUtensorMapSwizzle swz) {
    CUtensorMap m;
    cuuint64_t dims[2] = {cols, rows};
    cuuint64_t strides[1] = {cols * 2};
    cuuint32_t box[2] = {box_cols, box_rows};
    cuuint32_t es[2] = {1, 1};
    get_encode()(&m, CU_TENSOR_MAP_DATA_TYPE_BFLOAT16, 2, const_cast<void*>(ptr), dims, strides, box, es, CU_TENSOR_MAP_INTERLEAVE_NONE,
                 swz, CU_TENSOR_MAP_L2_PROMOTION_L2_256B, CU_TENSOR_MAP_FLOAT_OOB_FILL_NONE);
    return m;
}

extern "C" void kernel_launch(void* const* d_in, const int* in_sizes, int n_in, void* d_out, int out_size) {
    (void)in_sizes; (void)n_in; (void)out_size;
    const __nv_bfloat16* x = (const __nv_bfloat16*)d_in[0];
    const __nv_bfloat16* kc = (const __nv_bfloat16*)d_in[1];
    const __nv_bfloat16* vc = (const __nv_bfloat16*)d_in[2];
    const __nv_bfloat16* wq = (const __nv_bfloat16*)d_in[3];
    const __nv_bfloat16* wo = (const __nv_bfloat16*)d_in[4];
    const __nv_bfloat16* wg = (const __nv_bfloat16*)d_in[6];
    const __nv_bfloat16* wu = (const __nv_bfloat16*)d_in[7];
    const __nv_bfloat16* wd = (const __nv_bfloat16*)d_in[8];
    const __nv_bfloat16* c = (const __nv_bfloat16*)d_in[9];
    const __nv_bfloat16* wmod = (const __nv_bfloat16*)d_in[10];
    __nv_bfloat16* out = (__nv_bfloat16*)d_out;

    static bool init = false;
    static void *p_h, *p_o, *p_x1, *p_h2, *p_act, *p_part;
    if (!init) {
        cudaFuncSetAttribute(mega_kernel, cudaFuncAttributeMaxDynamicSharedMemorySize, SM_TOTAL);
        cudaGetSymbolAddress(&p_h, g_h);
        cudaGetSymbolAddress(&p_o, g_o);
        cudaGetSymbolAddress(&p_x1, g_x1);
        cudaGetSymbolAddress(&p_h2, g_h2);
        cudaGetSymbolAddress(&p_act, g_act);
        cudaGetSymbolAddress(&p_part, g_part);
        init = true;
    }
    const CUtensorMapSwizzle S128 = CU_TENSOR_MAP_SWIZZLE_128B, S64 = CU_TENSOR_MAP_SWIZZLE_64B;
    Maps tm;
    tm.h = make_map(p_h, S_LEN, D_MODEL, 128, 64, S128);
    tm.wq = make_map(wq, D_MODEL, N_HEADS * D_HEAD, 64, 64, S128);
    tm.k = make_map(kc, N_HEADS * S_KV, D_HEAD, 128, 64, S128);
    tm.v = make_map(vc, N_HEADS * S_KV, D_HEAD, 128, 64, S128);
    tm.o_st = make_map(p_o, S_LEN, N_HEADS * D_HEAD, 64, 64, S128);
    tm.o_a = make_map(p_o, S_LEN, N_HEADS * D_HEAD, 128, 64, S128);
    tm.wo = make_map(wo, N_HEADS * D_HEAD, D_MODEL, 64, 64, S128);
    tm.part_st = make_map(p_part, 4 * S_LEN, D_MODEL, 64, 64, S128);
    tm.h2 = make_map(p_h2, S_LEN, D_MODEL, 128, 64, S128);
    tm.g128 = make_map(wg, D_MODEL, D_FF, 64, 64, S128);
    tm.u128 = make_map(wu, D_MODEL, D_FF, 64, 64, S128);
    tm.g64 = make_map(wg, D_MODEL, D_FF, 64, 32, S64);
    tm.u64 = make_map(wu, D_MODEL, D_FF, 64, 32, S64);
    tm.act_st64 = make_map(p_act, S_LEN, D_FF, 64, 64, S128);
    tm.act_st24 = make_map(p_act, S_LEN, D_FF, 64, 24, CU_TENSOR_MAP_SWIZZLE_NONE);
    tm.act_a = make_map(p_act, S_LEN, D_FF, 128, 64, S128);
    tm.wd = make_map(wd, D_FF, D_MODEL, 64, 64, S128);
    tm.wd32 = make_map(wd, D_FF, D_MODEL, 64, 32, S64);

    cudaLaunchConfig_t cfg = {};
    cfg.gridDim = dim3(128);
    cfg.blockDim = dim3(384);
    cfg.dynamicSmemBytes = SM_TOTAL;
    cfg.stream = cudaStreamPerThread;
    cfg.attrs = nullptr;
    cfg.numAttrs = 0;
    cudaLaunchKernelEx(&cfg, mega_kernel, tm, x, c, wmod, out, (const void*)wo, (const void*)wg, (const void*)wu, (const void*)wd);
}
```

```cpp
#include <cuda_runtime.h>
#include <cuda_bf16.h>
#include <cuda.h>
#include <stdint.h>

__device__ __forceinline__ uint32_t smem_u32(const void* p) { return (uint32_t)__cvta_generic_to_shared(p); }

__device__ __forceinline__ void mbar_init(uint32_t bar, uint32_t count) {
    asm volatile("mbarrier.init.shared::cta.b64 [%0], %1;" ::"r"(bar), "r"(count) : "memory");
}
__device__ __forceinline__ void mbar_expect_tx(uint32_t bar, uint32_t bytes) {
    asm volatile("mbarrier.arrive.expect_tx.shared::cta.b64 _, [%0], %1;" ::"r"(bar), "r"(bytes) : "memory");
}
__device__ __forceinline__ void mbar_arrive(uint32_t bar) {
    asm volatile("mbarrier.arrive.shared::cta.b64 _, [%0];" ::"r"(bar) : "memory");
}
__device__ __forceinline__ void mbar_arrive_cluster(uint32_t bar, uint32_t cta) {
    asm volatile(
        "{\n.reg .b32 ra;\n"
        "mapa.shared::cluster.u32 ra, %0, %1;\n"
        "mbarrier.arrive.shared::cluster.b64 _, [ra];\n}\n" ::"r"(bar), "r"(cta)
        : "memory");
}
__device__ __forceinline__ bool mbar_try_wait(uint32_t bar, uint32_t parity) {
    uint32_t ok;
    asm volatile(
        "{\n.reg .pred p;\n"
        "mbarrier.try_wait.parity.shared::cta.b64 p, [%1], %2;\n"
        "selp.u32 %0, 1, 0, p;\n}\n"
        : "=r"(ok)
        : "r"(bar), "r"(parity)
        : "memory");
    return ok != 0;
}
__device__ __forceinline__ bool mbar_try_wait_cluster(uint32_t bar, uint32_t parity) {
    uint32_t ok;
    asm volatile(
        "{\n.reg .pred p;\n"
        "mbarrier.try_wait.parity.shared::cta.b64 p, [%1], %2;\n"
        "selp.u32 %0, 1, 0, p;\n}\n"
        : "=r"(ok)
        : "r"(bar), "r"(parity)
        : "memory");
    return ok != 0;
}
__device__ volatile int g_abort = 0;
__device__ __forceinline__ void mbar_wait(uint32_t bar, uint32_t parity) {
    asm volatile(
        "{\n.reg .pred p;\n.reg .u32 n;\n"
        "mov.u32 n, 0;\n"
        "WAIT_LOOP:\n"
        "mbarrier.try_wait.parity.shared::cta.b64 p, [%0], %1;\n"
        "@p bra WAIT_DONE;\n"
        "add.u32 n, n, 1;\n"
        "setp.lt.u32 p, n, 16777216;\n"
        "@p bra WAIT_LOOP;\n"
        "WAIT_DONE:\n}\n" ::"r"(bar), "r"(parity) : "memory");
}
__device__ __forceinline__ void mbar_wait_cluster(uint32_t bar, uint32_t parity) { mbar_wait(bar, parity); }
__device__ __forceinline__ void fence_mbar_init() { asm volatile("fence.mbarrier_init.release.cluster;" ::: "memory"); }
__device__ __forceinline__ void fence_proxy_async() { asm volatile("fence.proxy.async.shared::cta;" ::: "memory"); }
__device__ __forceinline__ void fence_proxy_async_all() { asm volatile("fence.proxy.async;" ::: "memory"); }
__device__ __forceinline__ void cluster_arrive() { asm volatile("barrier.cluster.arrive.release.aligned;" ::: "memory"); }
__device__ __forceinline__ void cluster_wait() { asm volatile("barrier.cluster.wait.acquire.aligned;" ::: "memory"); }
__device__ __forceinline__ void cluster_sync() { cluster_arrive(); cluster_wait(); }
__device__ __forceinline__ uint32_t cluster_ctarank() {
    uint32_t r;
    asm volatile("mov.u32 %0, %%cluster_ctarank;" : "=r"(r));
    return r;
}
__device__ __forceinline__ void bar_sync(int id, int n) { asm volatile("bar.sync %0, %1;" ::"r"(id), "r"(n) : "memory"); }
__device__ __forceinline__ void bar_arrive(int id, int n) { asm volatile("bar.arrive %0, %1;" ::"r"(id), "r"(n) : "memory"); }
__device__ __forceinline__ void pdl_wait() { asm volatile("griddepcontrol.wait;" ::: "memory"); }
__device__ __forceinline__ void pdl_launch() { asm volatile("griddepcontrol.launch_dependents;" ::: "memory"); }

__device__ __forceinline__ void tma_prefetch_desc(const CUtensorMap* m) {
    asm volatile("prefetch.tensormap [%0];" ::"l"(m) : "memory");
}
__device__ __forceinline__ void tma_load_2d(uint32_t dst, const CUtensorMap* m, int c0, int c1, uint32_t bar) {
    asm volatile(
        "cp.async.bulk.tensor.2d.shared::cluster.global.mbarrier::complete_tx::bytes [%0], [%1, {%3, %4}], [%2];"
        ::"r"(dst), "l"(m), "r"(bar), "r"(c0), "r"(c1)
        : "memory");
}
__device__ __forceinline__ void tma_load_2d_mc(uint32_t dst, const CUtensorMap* m, int c0, int c1, uint32_t bar, uint16_t mask) {
    asm volatile(
        "cp.async.bulk.tensor.2d.shared::cluster.global.mbarrier::complete_tx::bytes.multicast::cluster [%0], [%1, {%3, %4}], [%2], %5;"
        ::"r"(dst), "l"(m), "r"(bar), "r"(c0), "r"(c1), "h"(mask)
        : "memory");
}
__device__ __forceinline__ void tma_store_2d(const CUtensorMap* m, uint32_t src, int c0, int c1) {
    asm volatile("cp.async.bulk.tensor.2d.global.shared::cta.bulk_group [%0, {%2, %3}], [%1];"
                 ::"l"(m), "r"(src), "r"(c0), "r"(c1)
                 : "memory");
}
__device__ __forceinline__ void tma_store_commit() { asm volatile("cp.async.bulk.commit_group;" ::: "memory"); }
template <int N> __device__ __forceinline__ void tma_store_wait_read() {
    asm volatile("cp.async.bulk.wait_group.read %0;" ::"n"(N) : "memory");
}
template <int N> __device__ __forceinline__ void tma_store_wait() {
    asm volatile("cp.async.bulk.wait_group %0;" ::"n"(N) : "memory");
}

__device__ __forceinline__ void wgmma_fence() { asm volatile("wgmma.fence.sync.aligned;" ::: "memory"); }
__device__ __forceinline__ void wgmma_commit() { asm volatile("wgmma.commit_group.sync.aligned;" ::: "memory"); }
template <int N> __device__ __forceinline__ void wgmma_wait() {
    asm volatile("wgmma.wait_group.sync.aligned %0;" ::"n"(N) : "memory");
}
template <int R> __device__ __forceinline__ void reg_alloc() { asm volatile("setmaxnreg.inc.sync.aligned.u32 %0;" ::"n"(R)); }
template <int R> __device__ __forceinline__ void reg_dealloc() { asm volatile("setmaxnreg.dec.sync.aligned.u32 %0;" ::"n"(R)); }

template <int N> __device__ __forceinline__ void fence_regs(float (&r)[N]) {
#pragma unroll
    for (int i = 0; i < N; i++) asm volatile("" : "+f"(r[i])::"memory");
}
template <int N> __device__ __forceinline__ void fence_regs_u(uint32_t (&r)[N][4]) {
#pragma unroll
    for (int i = 0; i < N; i++) {
#pragma unroll
        for (int j = 0; j < 4; j++) asm volatile("" : "+r"(r[i][j])::"memory");
    }
}

__device__ __forceinline__ uint64_t make_desc(uint32_t addr, uint32_t lbo_bytes, uint32_t sbo_bytes, uint32_t swz) {
    return (uint64_t)((addr & 0x3FFFF) >> 4) | ((uint64_t)(lbo_bytes >> 4) << 16) | ((uint64_t)(sbo_bytes >> 4) << 32) |
           ((uint64_t)swz << 62);
}

__device__ __forceinline__ uint32_t pack_bf16(float lo, float hi) {
    uint32_t r;
    asm("cvt.rn.bf16x2.f32 %0, %1, %2;" : "=r"(r) : "f"(hi), "f"(lo));
    return r;
}
__device__ __forceinline__ float bf16_round(float x) { return __bfloat162float(__float2bfloat16_rn(x)); }
__device__ __forceinline__ float bf16lo(uint32_t v) { return __uint_as_float(v << 16); }
__device__ __forceinline__ float bf16hi(uint32_t v) { return __uint_as_float(v & 0xffff0000u); }
__device__ __forceinline__ float ex2(float x) {
    float y;
    asm("ex2.approx.ftz.f32 %0, %1;" : "=f"(y) : "f"(x));
    return y;
}
__device__ __forceinline__ void stmatrix_x4(uint32_t addr, uint32_t r0, uint32_t r1, uint32_t r2, uint32_t r3) {
    asm volatile("stmatrix.sync.aligned.m8n8.x4.shared.b16 [%0], {%1, %2, %3, %4};" ::"r"(addr), "r"(r0), "r"(r1), "r"(r2), "r"(r3)
                 : "memory");
}
__device__ __forceinline__ uint32_t mapa(uint32_t addr, uint32_t cta) {
    uint32_t r;
    asm volatile("mapa.shared::cluster.u32 %0, %1, %2;" : "=r"(r) : "r"(addr), "r"(cta));
    return r;
}
__device__ __forceinline__ void st_cluster_v2(uint32_t addr, float a, float b) {
    asm volatile("st.shared::cluster.v2.f32 [%0], {%1, %2};" ::"r"(addr), "f"(a), "f"(b) : "memory");
}
__device__ __forceinline__ void wgmma_ss_n256_t1(float (&d)[128], uint64_t descA, uint64_t descB, int scaleD) {
    asm volatile("{\n.reg .pred p;\n"
        "setp.ne.b32 p, %130, 0;\n"
        "wgmma.mma_async.sync.aligned.m64n256k16.f32.bf16.bf16 "
        "{%0, %1, %2, %3, %4, %5, %6, %7, %8, %9, %10, %11, %12, %13, %14, %15, "
        "%16, %17, %18, %19, %20, %21, %22, %23, %24, %25, %26, %27, %28, %29, %30, %31, "
        "%32, %33, %34, %35, %36, %37, %38, %39, %40, %41, %42, %43, %44, %45, %46, %47, "
        "%48, %49, %50, %51, %52, %53, %54, %55, %56, %57, %58, %59, %60, %61, %62, %63, "
        "%64, %65, %66, %67, %68, %69, %70, %71, %72, %73, %74, %75, %76, %77, %78, %79, "
        "%80, %81, %82, %83, %84, %85, %86, %87, %88, %89, %90, %91, %92, %93, %94, %95, "
        "%96, %97, %98, %99, %100, %101, %102, %103, %104, %105, %106, %107, %108, %109, %110, %111, "
        "%112, %113, %114, %115, %116, %117, %118, %119, %120, %121, %122, %123, %124, %125, %126, %127}, "
        "%128, %129, p, 1, 1, 0, 1;\n}\n"
        :
          "+f"(d[0]), "+f"(d[1]), "+f"(d[2]), "+f"(d[3]), "+f"(d[4]), "+f"(d[5]), "+f"(d[6]), "+f"(d[7]),
          "+f"(d[8]), "+f"(d[9]), "+f"(d[10]), "+f"(d[11]), "+f"(d[12]), "+f"(d[13]), "+f"(d[14]), "+f"(d[15]),
          "+f"(d[16]), "+f"(d[17]), "+f"(d[18]), "+f"(d[19]), "+f"(d[20]), "+f"(d[21]), "+f"(d[22]), "+f"(d[23]),
          "+f"(d[24]), "+f"(d[25]), "+f"(d[26]), "+f"(d[27]), "+f"(d[28]), "+f"(d[29]), "+f"(d[30]), "+f"(d[31]),
          "+f"(d[32]), "+f"(d[33]), "+f"(d[34]), "+f"(d[35]), "+f"(d[36]), "+f"(d[37]), "+f"(d[38]), "+f"(d[39]),
          "+f"(d[40]), "+f"(d[41]), "+f"(d[42]), "+f"(d[43]), "+f"(d[44]), "+f"(d[45]), "+f"(d[46]), "+f"(d[47]),
          "+f"(d[48]), "+f"(d[49]), "+f"(d[50]), "+f"(d[51]), "+f"(d[52]), "+f"(d[53]), "+f"(d[54]), "+f"(d[55]),
          "+f"(d[56]), "+f"(d[57]), "+f"(d[58]), "+f"(d[59]), "+f"(d[60]), "+f"(d[61]), "+f"(d[62]), "+f"(d[63]),
          "+f"(d[64]), "+f"(d[65]), "+f"(d[66]), "+f"(d[67]), "+f"(d[68]), "+f"(d[69]), "+f"(d[70]), "+f"(d[71]),
          "+f"(d[72]), "+f"(d[73]), "+f"(d[74]), "+f"(d[75]), "+f"(d[76]), "+f"(d[77]), "+f"(d[78]), "+f"(d[79]),
          "+f"(d[80]), "+f"(d[81]), "+f"(d[82]), "+f"(d[83]), "+f"(d[84]), "+f"(d[85]), "+f"(d[86]), "+f"(d[87]),
          "+f"(d[88]), "+f"(d[89]), "+f"(d[90]), "+f"(d[91]), "+f"(d[92]), "+f"(d[93]), "+f"(d[94]), "+f"(d[95]),
          "+f"(d[96]), "+f"(d[97]), "+f"(d[98]), "+f"(d[99]), "+f"(d[100]), "+f"(d[101]), "+f"(d[102]), "+f"(d[103]),
          "+f"(d[104]), "+f"(d[105]), "+f"(d[106]), "+f"(d[107]), "+f"(d[108]), "+f"(d[109]), "+f"(d[110]), "+f"(d[111]),
          "+f"(d[112]), "+f"(d[113]), "+f"(d[114]), "+f"(d[115]), "+f"(d[116]), "+f"(d[117]), "+f"(d[118]), "+f"(d[119]),
          "+f"(d[120]), "+f"(d[121]), "+f"(d[122]), "+f"(d[123]), "+f"(d[124]), "+f"(d[125]), "+f"(d[126]), "+f"(d[127])
        : "l"(descA), "l"(descB), "r"(scaleD));
}

__device__ __forceinline__ void wgmma_rs_n128_t0(float (&d)[64], const uint32_t (&a)[4], uint64_t descB, int scaleD) {
    asm volatile("{\n.reg .pred p;\n"
        "setp.ne.b32 p, %69, 0;\n"
        "wgmma.mma_async.sync.aligned.m64n128k16.f32.bf16.bf16 "
        "{%0, %1, %2, %3, %4, %5, %6, %7, %8, %9, %10, %11, %12, %13, %14, %15, "
        "%16, %17, %18, %19, %20, %21, %22, %23, %24, %25, %26, %27, %28, %29, %30, %31, "
        "%32, %33, %34, %35, %36, %37, %38, %39, %40, %41, %42, %43, %44, %45, %46, %47, "
        "%48, %49, %50, %51, %52, %53, %54, %55, %56, %57, %58, %59, %60, %61, %62, %63}, "
        "{%64, %65, %66, %67}, %68, p, 1, 1, 0;\n}\n"
        :
          "+f"(d[0]), "+f"(d[1]), "+f"(d[2]), "+f"(d[3]), "+f"(d[4]), "+f"(d[5]), "+f"(d[6]), "+f"(d[7]),
          "+f"(d[8]), "+f"(d[9]), "+f"(d[10]), "+f"(d[11]), "+f"(d[12]), "+f"(d[13]), "+f"(d[14]), "+f"(d[15]),
          "+f"(d[16]), "+f"(d[17]), "+f"(d[18]), "+f"(d[19]), "+f"(d[20]), "+f"(d[21]), "+f"(d[22]), "+f"(d[23]),
          "+f"(d[24]), "+f"(d[25]), "+f"(d[26]), "+f"(d[27]), "+f"(d[28]), "+f"(d[29]), "+f"(d[30]), "+f"(d[31]),
          "+f"(d[32]), "+f"(d[33]), "+f"(d[34]), "+f"(d[35]), "+f"(d[36]), "+f"(d[37]), "+f"(d[38]), "+f"(d[39]),
          "+f"(d[40]), "+f"(d[41]), "+f"(d[42]), "+f"(d[43]), "+f"(d[44]), "+f"(d[45]), "+f"(d[46]), "+f"(d[47]),
          "+f"(d[48]), "+f"(d[49]), "+f"(d[50]), "+f"(d[51]), "+f"(d[52]), "+f"(d[53]), "+f"(d[54]), "+f"(d[55]),
          "+f"(d[56]), "+f"(d[57]), "+f"(d[58]), "+f"(d[59]), "+f"(d[60]), "+f"(d[61]), "+f"(d[62]), "+f"(d[63])
        : "r"(a[0]), "r"(a[1]), "r"(a[2]), "r"(a[3]), "l"(descB), "r"(scaleD));
}

__device__ __forceinline__ void wgmma_rs_n128_t0_z(float (&d)[64], const uint32_t (&a)[4], uint64_t descB) {
    asm volatile("{\n.reg .pred p;\n"
        "setp.ne.b32 p, 0, 0;\n"
        "wgmma.mma_async.sync.aligned.m64n128k16.f32.bf16.bf16 "
        "{%0, %1, %2, %3, %4, %5, %6, %7, %8, %9, %10, %11, %12, %13, %14, %15, "
        "%16, %17, %18, %19, %20, %21, %22, %23, %24, %25, %26, %27, %28, %29, %30, %31, "
        "%32, %33, %34, %35, %36, %37, %38, %39, %40, %41, %42, %43, %44, %45, %46, %47, "
        "%48, %49, %50, %51, %52, %53, %54, %55, %56, %57, %58, %59, %60, %61, %62, %63}, "
        "{%64, %65, %66, %67}, %68, p, 1, 1, 0;\n}\n"
        :
          "=f"(d[0]), "=f"(d[1]), "=f"(d[2]), "=f"(d[3]), "=f"(d[4]), "=f"(d[5]), "=f"(d[6]), "=f"(d[7]),
          "=f"(d[8]), "=f"(d[9]), "=f"(d[10]), "=f"(d[11]), "=f"(d[12]), "=f"(d[13]), "=f"(d[14]), "=f"(d[15]),
          "=f"(d[16]), "=f"(d[17]), "=f"(d[18]), "=f"(d[19]), "=f"(d[20]), "=f"(d[21]), "=f"(d[22]), "=f"(d[23]),
          "=f"(d[24]), "=f"(d[25]), "=f"(d[26]), "=f"(d[27]), "=f"(d[28]), "=f"(d[29]), "=f"(d[30]), "=f"(d[31]),
          "=f"(d[32]), "=f"(d[33]), "=f"(d[34]), "=f"(d[35]), "=f"(d[36]), "=f"(d[37]), "=f"(d[38]), "=f"(d[39]),
          "=f"(d[40]), "=f"(d[41]), "=f"(d[42]), "=f"(d[43]), "=f"(d[44]), "=f"(d[45]), "=f"(d[46]), "=f"(d[47]),
          "=f"(d[48]), "=f"(d[49]), "=f"(d[50]), "=f"(d[51]), "=f"(d[52]), "=f"(d[53]), "=f"(d[54]), "=f"(d[55]),
          "=f"(d[56]), "=f"(d[57]), "=f"(d[58]), "=f"(d[59]), "=f"(d[60]), "=f"(d[61]), "=f"(d[62]), "=f"(d[63])
        : "r"(a[0]), "r"(a[1]), "r"(a[2]), "r"(a[3]), "l"(descB));
}

__device__ __forceinline__ void wgmma_rs_n128_t1(float (&d)[64], const uint32_t (&a)[4], uint64_t descB, int scaleD) {
    asm volatile("{\n.reg .pred p;\n"
        "setp.ne.b32 p, %69, 0;\n"
        "wgmma.mma_async.sync.aligned.m64n128k16.f32.bf16.bf16 "
        "{%0, %1, %2, %3, %4, %5, %6, %7, %8, %9, %10, %11, %12, %13, %14, %15, "
        "%16, %17, %18, %19, %20, %21, %22, %23, %24, %25, %26, %27, %28, %29, %30, %31, "
        "%32, %33, %34, %35, %36, %37, %38, %39, %40, %41, %42, %43, %44, %45, %46, %47, "
        "%48, %49, %50, %51, %52, %53, %54, %55, %56, %57, %58, %59, %60, %61, %62, %63}, "
        "{%64, %65, %66, %67}, %68, p, 1, 1, 1;\n}\n"
        :
          "+f"(d[0]), "+f"(d[1]), "+f"(d[2]), "+f"(d[3]), "+f"(d[4]), "+f"(d[5]), "+f"(d[6]), "+f"(d[7]),
          "+f"(d[8]), "+f"(d[9]), "+f"(d[10]), "+f"(d[11]), "+f"(d[12]), "+f"(d[13]), "+f"(d[14]), "+f"(d[15]),
          "+f"(d[16]), "+f"(d[17]), "+f"(d[18]), "+f"(d[19]), "+f"(d[20]), "+f"(d[21]), "+f"(d[22]), "+f"(d[23]),
          "+f"(d[24]), "+f"(d[25]), "+f"(d[26]), "+f"(d[27]), "+f"(d[28]), "+f"(d[29]), "+f"(d[30]), "+f"(d[31]),
          "+f"(d[32]), "+f"(d[33]), "+f"(d[34]), "+f"(d[35]), "+f"(d[36]), "+f"(d[37]), "+f"(d[38]), "+f"(d[39]),
          "+f"(d[40]), "+f"(d[41]), "+f"(d[42]), "+f"(d[43]), "+f"(d[44]), "+f"(d[45]), "+f"(d[46]), "+f"(d[47]),
          "+f"(d[48]), "+f"(d[49]), "+f"(d[50]), "+f"(d[51]), "+f"(d[52]), "+f"(d[53]), "+f"(d[54]), "+f"(d[55]),
          "+f"(d[56]), "+f"(d[57]), "+f"(d[58]), "+f"(d[59]), "+f"(d[60]), "+f"(d[61]), "+f"(d[62]), "+f"(d[63])
        : "r"(a[0]), "r"(a[1]), "r"(a[2]), "r"(a[3]), "l"(descB), "r"(scaleD));
}

__device__ __forceinline__ void wgmma_ss_n184_t1(float (&d)[92], uint64_t descA, uint64_t descB, int scaleD) {
    asm volatile("{\n.reg .pred p;\n"
        "setp.ne.b32 p, %94, 0;\n"
        "wgmma.mma_async.sync.aligned.m64n184k16.f32.bf16.bf16 "
        "{%0, %1, %2, %3, %4, %5, %6, %7, %8, %9, %10, %11, %12, %13, %14, %15, "
        "%16, %17, %18, %19, %20, %21, %22, %23, %24, %25, %26, %27, %28, %29, %30, %31, "
        "%32, %33, %34, %35, %36, %37, %38, %39, %40, %41, %42, %43, %44, %45, %46, %47, "
        "%48, %49, %50, %51, %52, %53, %54, %55, %56, %57, %58, %59, %60, %61, %62, %63, "
        "%64, %65, %66, %67, %68, %69, %70, %71, %72, %73, %74, %75, %76, %77, %78, %79, "
        "%80, %81, %82, %83, %84, %85, %86, %87, %88, %89, %90, %91}, "
        "%92, %93, p, 1, 1, 0, 1;\n}\n"
        :
          "+f"(d[0]), "+f"(d[1]), "+f"(d[2]), "+f"(d[3]), "+f"(d[4]), "+f"(d[5]), "+f"(d[6]), "+f"(d[7]),
          "+f"(d[8]), "+f"(d[9]), "+f"(d[10]), "+f"(d[11]), "+f"(d[12]), "+f"(d[13]), "+f"(d[14]), "+f"(d[15]),
          "+f"(d[16]), "+f"(d[17]), "+f"(d[18]), "+f"(d[19]), "+f"(d[20]), "+f"(d[21]), "+f"(d[22]), "+f"(d[23]),
          "+f"(d[24]), "+f"(d[25]), "+f"(d[26]), "+f"(d[27]), "+f"(d[28]), "+f"(d[29]), "+f"(d[30]), "+f"(d[31]),
          "+f"(d[32]), "+f"(d[33]), "+f"(d[34]), "+f"(d[35]), "+f"(d[36]), "+f"(d[37]), "+f"(d[38]), "+f"(d[39]),
          "+f"(d[40]), "+f"(d[41]), "+f"(d[42]), "+f"(d[43]), "+f"(d[44]), "+f"(d[45]), "+f"(d[46]), "+f"(d[47]),
          "+f"(d[48]), "+f"(d[49]), "+f"(d[50]), "+f"(d[51]), "+f"(d[52]), "+f"(d[53]), "+f"(d[54]), "+f"(d[55]),
          "+f"(d[56]), "+f"(d[57]), "+f"(d[58]), "+f"(d[59]), "+f"(d[60]), "+f"(d[61]), "+f"(d[62]), "+f"(d[63]),
          "+f"(d[64]), "+f"(d[65]), "+f"(d[66]), "+f"(d[67]), "+f"(d[68]), "+f"(d[69]), "+f"(d[70]), "+f"(d[71]),
          "+f"(d[72]), "+f"(d[73]), "+f"(d[74]), "+f"(d[75]), "+f"(d[76]), "+f"(d[77]), "+f"(d[78]), "+f"(d[79]),
          "+f"(d[80]), "+f"(d[81]), "+f"(d[82]), "+f"(d[83]), "+f"(d[84]), "+f"(d[85]), "+f"(d[86]), "+f"(d[87]),
          "+f"(d[88]), "+f"(d[89]), "+f"(d[90]), "+f"(d[91])
        : "l"(descA), "l"(descB), "r"(scaleD));
}

__device__ __forceinline__ void wgmma_ss_n192_t1(float (&d)[96], uint64_t descA, uint64_t descB, int scaleD) {
    asm volatile("{\n.reg .pred p;\n"
        "setp.ne.b32 p, %98, 0;\n"
        "wgmma.mma_async.sync.aligned.m64n192k16.f32.bf16.bf16 "
        "{%0, %1, %2, %3, %4, %5, %6, %7, %8, %9, %10, %11, %12, %13, %14, %15, "
        "%16, %17, %18, %19, %20, %21, %22, %23, %24, %25, %26, %27, %28, %29, %30, %31, "
        "%32, %33, %34, %35, %36, %37, %38, %39, %40, %41, %42, %43, %44, %45, %46, %47, "
        "%48, %49, %50, %51, %52, %53, %54, %55, %56, %57, %58, %59, %60, %61, %62, %63, "
        "%64, %65, %66, %67, %68, %69, %70, %71, %72, %73, %74, %75, %76, %77, %78, %79, "
        "%80, %81, %82, %83, %84, %85, %86, %87, %88, %89, %90, %91, %92, %93, %94, %95}, "
        "%96, %97, p, 1, 1, 0, 1;\n}\n"
        :
          "+f"(d[0]), "+f"(d[1]), "+f"(d[2]), "+f"(d[3]), "+f"(d[4]), "+f"(d[5]), "+f"(d[6]), "+f"(d[7]),
          "+f"(d[8]), "+f"(d[9]), "+f"(d[10]), "+f"(d[11]), "+f"(d[12]), "+f"(d[13]), "+f"(d[14]), "+f"(d[15]),
          "+f"(d[16]), "+f"(d[17]), "+f"(d[18]), "+f"(d[19]), "+f"(d[20]), "+f"(d[21]), "+f"(d[22]), "+f"(d[23]),
          "+f"(d[24]), "+f"(d[25]), "+f"(d[26]), "+f"(d[27]), "+f"(d[28]), "+f"(d[29]), "+f"(d[30]), "+f"(d[31]),
          "+f"(d[32]), "+f"(d[33]), "+f"(d[34]), "+f"(d[35]), "+f"(d[36]), "+f"(d[37]), "+f"(d[38]), "+f"(d[39]),
          "+f"(d[40]), "+f"(d[41]), "+f"(d[42]), "+f"(d[43]), "+f"(d[44]), "+f"(d[45]), "+f"(d[46]), "+f"(d[47]),
          "+f"(d[48]), "+f"(d[49]), "+f"(d[50]), "+f"(d[51]), "+f"(d[52]), "+f"(d[53]), "+f"(d[54]), "+f"(d[55]),
          "+f"(d[56]), "+f"(d[57]), "+f"(d[58]), "+f"(d[59]), "+f"(d[60]), "+f"(d[61]), "+f"(d[62]), "+f"(d[63]),
          "+f"(d[64]), "+f"(d[65]), "+f"(d[66]), "+f"(d[67]), "+f"(d[68]), "+f"(d[69]), "+f"(d[70]), "+f"(d[71]),
          "+f"(d[72]), "+f"(d[73]), "+f"(d[74]), "+f"(d[75]), "+f"(d[76]), "+f"(d[77]), "+f"(d[78]), "+f"(d[79]),
          "+f"(d[80]), "+f"(d[81]), "+f"(d[82]), "+f"(d[83]), "+f"(d[84]), "+f"(d[85]), "+f"(d[86]), "+f"(d[87]),
          "+f"(d[88]), "+f"(d[89]), "+f"(d[90]), "+f"(d[91]), "+f"(d[92]), "+f"(d[93]), "+f"(d[94]), "+f"(d[95])
        : "l"(descA), "l"(descB), "r"(scaleD));
}

__device__ __forceinline__ void wgmma_ss_n128_t1(float (&d)[64], uint64_t descA, uint64_t descB, int scaleD) {
    asm volatile("{\n.reg .pred p;\n"
        "setp.ne.b32 p, %66, 0;\n"
        "wgmma.mma_async.sync.aligned.m64n128k16.f32.bf16.bf16 "
        "{%0, %1, %2, %3, %4, %5, %6, %7, %8, %9, %10, %11, %12, %13, %14, %15, "
        "%16, %17, %18, %19, %20, %21, %22, %23, %24, %25, %26, %27, %28, %29, %30, %31, "
        "%32, %33, %34, %35, %36, %37, %38, %39, %40, %41, %42, %43, %44, %45, %46, %47, "
        "%48, %49, %50, %51, %52, %53, %54, %55, %56, %57, %58, %59, %60, %61, %62, %63}, "
        "%64, %65, p, 1, 1, 0, 1;\n}\n"
        :
          "+f"(d[0]), "+f"(d[1]), "+f"(d[2]), "+f"(d[3]), "+f"(d[4]), "+f"(d[5]), "+f"(d[6]), "+f"(d[7]),
          "+f"(d[8]), "+f"(d[9]), "+f"(d[10]), "+f"(d[11]), "+f"(d[12]), "+f"(d[13]), "+f"(d[14]), "+f"(d[15]),
          "+f"(d[16]), "+f"(d[17]), "+f"(d[18]), "+f"(d[19]), "+f"(d[20]), "+f"(d[21]), "+f"(d[22]), "+f"(d[23]),
          "+f"(d[24]), "+f"(d[25]), "+f"(d[26]), "+f"(d[27]), "+f"(d[28]), "+f"(d[29]), "+f"(d[30]), "+f"(d[31]),
          "+f"(d[32]), "+f"(d[33]), "+f"(d[34]), "+f"(d[35]), "+f"(d[36]), "+f"(d[37]), "+f"(d[38]), "+f"(d[39]),
          "+f"(d[40]), "+f"(d[41]), "+f"(d[42]), "+f"(d[43]), "+f"(d[44]), "+f"(d[45]), "+f"(d[46]), "+f"(d[47]),
          "+f"(d[48]), "+f"(d[49]), "+f"(d[50]), "+f"(d[51]), "+f"(d[52]), "+f"(d[53]), "+f"(d[54]), "+f"(d[55]),
          "+f"(d[56]), "+f"(d[57]), "+f"(d[58]), "+f"(d[59]), "+f"(d[60]), "+f"(d[61]), "+f"(d[62]), "+f"(d[63])
        : "l"(descA), "l"(descB), "r"(scaleD));
}

__device__ __forceinline__ void wgmma_ss_n32_t1(float (&d)[16], uint64_t descA, uint64_t descB, int scaleD) {
    asm volatile("{\n.reg .pred p;\n"
        "setp.ne.b32 p, %18, 0;\n"
        "wgmma.mma_async.sync.aligned.m64n32k16.f32.bf16.bf16 "
        "{%0, %1, %2, %3, %4, %5, %6, %7, %8, %9, %10, %11, %12, %13, %14, %15}, "
        "%16, %17, p, 1, 1, 0, 1;\n}\n"
        :
          "+f"(d[0]), "+f"(d[1]), "+f"(d[2]), "+f"(d[3]), "+f"(d[4]), "+f"(d[5]), "+f"(d[6]), "+f"(d[7]),
          "+f"(d[8]), "+f"(d[9]), "+f"(d[10]), "+f"(d[11]), "+f"(d[12]), "+f"(d[13]), "+f"(d[14]), "+f"(d[15])
        : "l"(descA), "l"(descB), "r"(scaleD));
}

constexpr int S_LEN = 2048;
constexpr int D_MODEL = 640;
constexpr int N_HEADS = 32;
constexpr int D_HEAD = 128;
constexpr int S_KV = 2048;
constexpr int WIN = 512;
constexpr int D_FF = 1728;
constexpr float LN_EPS = 1e-5f;

#define TS(kid, slot)

__device__ float g_mod[6 * D_MODEL];
__device__ __align__(1024) __nv_bfloat16 g_h[S_LEN * D_MODEL];
__device__ __align__(1024) __nv_bfloat16 g_o[S_LEN * N_HEADS * D_HEAD];
__device__ __align__(1024) __nv_bfloat16 g_part[4 * S_LEN * D_MODEL];
__device__ __align__(1024) __nv_bfloat16 g_x1[S_LEN * D_MODEL];
__device__ __align__(1024) __nv_bfloat16 g_h2[S_LEN * D_MODEL];
__device__ __align__(1024) __nv_bfloat16 g_act[S_LEN * D_FF];

constexpr int F_MODAB = 0, F_MODALL = 1, F_H = 2, F_P = 18, F_H2 = 34, F_A = 50, F_O = 66, F_A1 = 130, F_COUNT = 146;
__device__ unsigned g_flags[F_COUNT * 32];
__device__ unsigned g_epoch;
__device__ unsigned g_exit;

__device__ __forceinline__ void flag_signal(int f) {
    asm volatile("red.release.gpu.global.add.u32 [%0], 1;" ::"l"(g_flags + f * 32) : "memory");
}
__device__ __forceinline__ void flag_signal_relaxed(int f) {
    asm volatile("fence.proxy.async;" ::: "memory");
    asm volatile("red.release.gpu.global.add.u32 [%0], 1;" ::"l"(g_flags + f * 32) : "memory");
}
__device__ __forceinline__ void flag_wait(int f, unsigned target) {
    unsigned n = 0;
    while (true) {
        unsigned v;
        asm volatile("ld.acquire.gpu.global.u32 %0, [%1];" : "=r"(v) : "l"(g_flags + f * 32) : "memory");
        if ((int)(v - target) >= 0) break;
        if ((++n & 0xfffu) == 0) {
            if (n > (1u << 24)) g_abort = 1;
            if (g_abort) break;
        }
    }
}

struct Maps {
    CUtensorMap h, wq, k, v, o_st, o_a, wo, part_st, h2, g128, u128, g64, u64, act_st64, act_st24, act_a, wd, wd32;
};

constexpr int SM_DATA = 229376;
constexpr int SM_STAGING = 196608;
constexpr int SM_TOTAL = SM_DATA + 1024 + 512;
constexpr int B1F = 0, B1E = 6, B2F = 12, B2E = 16, B4F = 20, B4E = 24, B5F = 28, B5E = 33, BD1 = 38, BD2 = 39, BD4 = 40, BD1A = 41, BX = 42, BD4B = 43, BHS = 44, BHF = 46;
constexpr int P1_STAGE = 32768, P2_STAGE = 57344, P4_STAGE = 49152, P5_STAGE = 36864;

__device__ __forceinline__ float rcp_approx(float x) { float y; asm("rcp.approx.ftz.f32 %0, %1;" : "=f"(y) : "f"(x)); return y; }
__device__ __forceinline__ float silu_mul(float g, float u) { return g * rcp_approx(1.f + ex2(-1.4426950408889634f * g)) * u; }
__device__ __forceinline__ uint2 ldcg_u2(const void* p) { return __ldcg(reinterpret_cast<const uint2*>(p)); }

__device__ __forceinline__ void ln_rows_impl(uint2 a0, uint2 a1, uint2 a2, uint2 a3, uint2 a4, uint2 b0, uint2 b1, uint2 b2, uint2 b3, uint2 b4,
                                          const float* __restrict__ shift, const float* __restrict__ scale1p,
                                          __nv_bfloat16* __restrict__ dst, int lane) {
    const uint2 xr[2][5] = {{a0, a1, a2, a3, a4}, {b0, b1, b2, b3, b4}};
    float4 sh[5], sc[5];
#pragma unroll
    for (int i = 0; i < 5; i++) {
        sh[i] = __ldcg(reinterpret_cast<const float4*>(shift + (lane + 32 * i) * 4));
        sc[i] = __ldcg(reinterpret_cast<const float4*>(scale1p + (lane + 32 * i) * 4));
    }
    float mean[2], rstd[2];
#pragma unroll
    for (int rr = 0; rr < 2; rr++) {
        float s = 0.f;
#pragma unroll
        for (int i = 0; i < 5; i++) s += (bf16lo(xr[rr][i].x) + bf16hi(xr[rr][i].x)) + (bf16lo(xr[rr][i].y) + bf16hi(xr[rr][i].y));
#pragma unroll
        for (int o = 16; o > 0; o >>= 1) s += __shfl_xor_sync(0xffffffffu, s, o);
        mean[rr] = s * (1.f / D_MODEL);
    }
#pragma unroll
    for (int rr = 0; rr < 2; rr++) {
        float q = 0.f;
#pragma unroll
        for (int i = 0; i < 5; i++) {
            const float d0 = bf16lo(xr[rr][i].x) - mean[rr], d1 = bf16hi(xr[rr][i].x) - mean[rr];
            const float d2 = bf16lo(xr[rr][i].y) - mean[rr], d3 = bf16hi(xr[rr][i].y) - mean[rr];
            q += (d0 * d0 + d1 * d1) + (d2 * d2 + d3 * d3);
        }
#pragma unroll
        for (int o = 16; o > 0; o >>= 1) q += __shfl_xor_sync(0xffffffffu, q, o);
        rstd[rr] = rsqrtf(q * (1.f / D_MODEL) + LN_EPS);
    }
#pragma unroll
    for (int rr = 0; rr < 2; rr++) {
#pragma unroll
        for (int i = 0; i < 5; i++) {
            uint2 u;
            u.x = pack_bf16((bf16lo(xr[rr][i].x) - mean[rr]) * rstd[rr] * sc[i].x + sh[i].x, (bf16hi(xr[rr][i].x) - mean[rr]) * rstd[rr] * sc[i].y + sh[i].y);
            u.y = pack_bf16((bf16lo(xr[rr][i].y) - mean[rr]) * rstd[rr] * sc[i].z + sh[i].z, (bf16hi(xr[rr][i].y) - mean[rr]) * rstd[rr] * sc[i].w + sh[i].w);
            *reinterpret_cast<uint2*>(dst + (size_t)rr * D_MODEL + (lane + 32 * i) * 4) = u;
        }
    }
}

__device__ __forceinline__ void ln_rows(const uint2 (&xr)[2][5], const float* shift, const float* scale1p, __nv_bfloat16* dst, int lane) {
    ln_rows_impl(xr[0][0], xr[0][1], xr[0][2], xr[0][3], xr[0][4], xr[1][0], xr[1][1], xr[1][2], xr[1][3], xr[1][4], shift, scale1p, dst, lane);
}

__global__ void __cluster_dims__(2, 1, 1) __launch_bounds__(384, 1)
mega_kernel(const __grid_constant__ Maps tm, const __nv_bfloat16* __restrict__ x, const __nv_bfloat16* __restrict__ cvec,
            const __nv_bfloat16* __restrict__ w_mod, __nv_bfloat16* __restrict__ out, const void* wo_p, const void* wg_p,
            const void* wu_p, const void* wd_p) {
    extern __shared__ uint8_t smem_raw[];
    const uint32_t base = (smem_u32(smem_raw) + 1023u) & ~1023u;
    const uint32_t bars = base + SM_DATA;
    const uint32_t rank = cluster_ctarank();
    const int cid = blockIdx.x >> 1;
    const int p = cid & 7, j = cid >> 3;
    const int mt = p * 2 + (int)rank;
    const int m0 = mt * 128;
    const int wg = threadIdx.x >> 7;
    unsigned epoch;
    asm volatile("ld.volatile.global.u32 %0, [%1];" : "=r"(epoch) : "l"(&g_epoch));

    uint2 xr[2][5];
    uint4 w[10];
    unsigned short cr[10];
    if (wg < 2) {
        const int cw = threadIdx.x >> 5, lane = threadIdx.x & 31;
        const int mb = blockIdx.x < 120 ? blockIdx.x : 0;
#pragma unroll
        for (int i = 0; i < 10; i++) cr[i] = __ldg(reinterpret_cast<const unsigned short*>(cvec) + cw * 80 + i * 8 + (lane >> 2));
#pragma unroll
        for (int i = 0; i < 10; i++)
            w[i] = __ldg(reinterpret_cast<const uint4*>(w_mod + (size_t)(cw * 80 + i * 8 + (lane >> 2)) * (6 * D_MODEL) + mb * 32 + (lane & 3) * 8));
#pragma unroll
        for (int rr = 0; rr < 2; rr++)
#pragma unroll
            for (int i = 0; i < 5; i++)
                xr[rr][i] = __ldg(reinterpret_cast<const uint2*>(x + (size_t)(m0 + j * 16 + cw * 2 + rr) * D_MODEL + (lane + 32 * i) * 4));
    }

    if (threadIdx.x == 0) {
        for (int i = 0; i < 6; i++) { mbar_init(bars + 8 * (B1F + i), 1); mbar_init(bars + 8 * (B1E + i), 4); }
        for (int i = 0; i < 4; i++) { mbar_init(bars + 8 * (B2F + i), 1); mbar_init(bars + 8 * (B2E + i), 4); }
        for (int i = 0; i < 4; i++) { mbar_init(bars + 8 * (B4F + i), 1); mbar_init(bars + 8 * (B4E + i), 4); }
        for (int i = 0; i < 5; i++) { mbar_init(bars + 8 * (B5F + i), 1); mbar_init(bars + 8 * (B5E + i), 2); }
        mbar_init(bars + 8 * BD1, 4); mbar_init(bars + 8 * BD2, 4); mbar_init(bars + 8 * BD4, 4); mbar_init(bars + 8 * BD1A, 8);
        for (int i = 0; i < 2; i++) { mbar_init(bars + 8 * (BHS + i), 1); mbar_init(bars + 8 * (BHF + i), 1); }
        mbar_init(bars + 8 * BX, 1); mbar_init(bars + 8 * BD4B, 4);
        mbar_expect_tx(bars + 8 * BX, 40960);
        fence_mbar_init();
    }
    __syncthreads();
    cluster_sync();

    if (wg == 2) {
        reg_dealloc<40>();
        if (threadIdx.x == 256) {
            {
                uint32_t st = 0, ph = 1;
                bool first = true;
#pragma unroll 1
                for (int hp = 0; hp < 2; hp++) {
                    const int head0 = j * 4 + hp * 2;
                    if (first) {
#pragma unroll 1
                        for (int s = 1; s < 6; s++) {
                            if (s == 3) continue;
                            const int kb = s < 3 ? s - 1 : s - 2;
                            mbar_expect_tx(bars + 8 * (B1F + s), P1_STAGE);
#pragma unroll 1
                            for (int c = 0; c < 2; c++) {
                                const int chunk = 2 * (int)rank + c;
                                tma_load_2d_mc(base + s * P1_STAGE + chunk * 8192, &tm.wq, head0 * 128 + chunk * 64, kb * 64, bars + 8 * (B1F + s), 3);
                            }
                        }
                        flag_wait(F_H + mt, (epoch + 1) * 8);
                        fence_proxy_async_all();
#pragma unroll 1
                        for (int s = 0; s < 6; s += 3) {
                            mbar_expect_tx(bars + 8 * (B1F + s), P1_STAGE);
                            tma_load_2d(base + s * P1_STAGE, &tm.h, (s / 3 * 2) * 64, m0, bars + 8 * (B1F + s));
                            tma_load_2d(base + s * P1_STAGE + 16384, &tm.h, (s / 3 * 2 + 1) * 64, m0, bars + 8 * (B1F + s));
                        }
                        ph = 0;
                    }
#pragma unroll 1
                    for (int kk2 = first ? 2 : 0; kk2 < 5; kk2++) {
                        mbar_wait(bars + 8 * (B1E + st), ph);
                        mbar_expect_tx(bars + 8 * (B1F + st), P1_STAGE);
                        tma_load_2d(base + st * P1_STAGE, &tm.h, (2 * kk2) * 64, m0, bars + 8 * (B1F + st));
                        tma_load_2d(base + st * P1_STAGE + 16384, &tm.h, (2 * kk2 + 1) * 64, m0, bars + 8 * (B1F + st));
                        if (++st == 6) { st = 0; ph ^= 1; }
#pragma unroll 1
                        for (int u = 0; u < 2; u++) {
                            mbar_wait(bars + 8 * (B1E + st), ph);
                            mbar_expect_tx(bars + 8 * (B1F + st), P1_STAGE);
                            const int kb = 2 * kk2 + u;
#pragma unroll 1
                            for (int c = 0; c < 2; c++) {
                                const int chunk = 2 * (int)rank + c;
                                tma_load_2d_mc(base + st * P1_STAGE + chunk * 8192, &tm.wq, head0 * 128 + chunk * 64, kb * 64, bars + 8 * (B1F + st), 3);
                            }
                            if (++st == 6) { st = 0; ph ^= 1; }
                        }
                    }
                    first = false;
#pragma unroll 1
                    for (int t = 0; t <= 8; t++) {
                        if (t < 8) {
                            mbar_wait(bars + 8 * (B1E + st), ph);
                            mbar_expect_tx(bars + 8 * (B1F + st), P1_STAGE);
                            const int row = (head0 + (t >> 2)) * S_KV + (S_KV - WIN) + (t & 3) * 128;
                            tma_load_2d_mc(base + st * P1_STAGE + rank * 16384, &tm.k, rank * 64, row, bars + 8 * (B1F + st), 3);
                            if (++st == 6) { st = 0; ph ^= 1; }
                        }
                        if (t > 0) {
                            mbar_wait(bars + 8 * (B1E + st), ph);
                            mbar_expect_tx(bars + 8 * (B1F + st), P1_STAGE);
                            const int tv = t - 1;
                            const int row = (head0 + (tv >> 2)) * S_KV + (S_KV - WIN) + (tv & 3) * 128;
                            tma_load_2d_mc(base + st * P1_STAGE + rank * 16384, &tm.v, rank * 64, row, bars + 8 * (B1F + st), 3);
                            if (++st == 6) { st = 0; ph ^= 1; }
                        }
                    }
                }
            }
            {
                const int kq = j >> 1, n0 = (j & 1) * 320;
                uint32_t st = 0, ph = 1;
#pragma unroll 1
                for (int i = 0; i < 16; i++) {
                    if (i == 0) mbar_wait(bars + 8 * BD1A, 0);
                    if (i == 3) mbar_wait(bars + 8 * BD1, 0);
                    if (i == 6) { flag_wait(F_O + mt * 4 + kq, (epoch + 1) * 4); fence_proxy_async_all(); }
                    mbar_wait(bars + 8 * (B2E + st), ph);
                    mbar_expect_tx(bars + 8 * (B2F + st), P2_STAGE);
                    const uint32_t dst = base + st * P2_STAGE;
                    const int k0 = kq * 1024 + ((i + (j & 1) * 8) & 15) * 64;
                    tma_load_2d(dst, &tm.o_a, k0, m0, bars + 8 * (B2F + st));
#pragma unroll 1
                    for (int c = 0; c < 5; c++)
                        if (((c + i) & 1) == (int)rank) tma_load_2d_mc(dst + 16384 + c * 8192, &tm.wo, n0 + c * 64, k0, bars + 8 * (B2F + st), 3);
                    if (++st == 4) { st = 0; ph ^= 1; }
                }
            }
            {
                const int f0 = j * 216;
                const CUtensorMap* t128 = rank == 0 ? &tm.g128 : &tm.u128;
                const CUtensorMap* t64 = rank == 0 ? &tm.g64 : &tm.u64;
                mbar_wait(bars + 8 * BD2, 0);
#pragma unroll 1
                for (int i = 0; i < 4; i++) {
                    mbar_expect_tx(bars + 8 * (B4F + i), 16384 + 32768);
                    const uint32_t dst = base + i * P4_STAGE;
                    tma_load_2d_mc(dst + 16384 + rank * 16384, t128, f0, i * 64, bars + 8 * (B4F + i), 3);
                    tma_load_2d_mc(dst + 16384 + rank * 16384 + 8192, t128, f0 + 64, i * 64, bars + 8 * (B4F + i), 3);
                }
                flag_wait(F_H2 + mt, (epoch + 1) * 8);
                fence_proxy_async_all();
#pragma unroll 1
                for (int i = 0; i < 4; i++) tma_load_2d(base + i * P4_STAGE, &tm.h2, i * 64, m0, bars + 8 * (B4F + i));
                uint32_t st = 0, ph = 0;
#pragma unroll 1
                for (int i = 4; i < 20; i++) {
                    const int kb = i < 10 ? i : i - 10;
                    mbar_wait(bars + 8 * (B4E + st), ph);
                    const uint32_t dst = base + st * P4_STAGE;
                    if (i < 10) {
                        mbar_expect_tx(bars + 8 * (B4F + st), 16384 + 32768);
                        tma_load_2d(dst, &tm.h2, kb * 64, m0, bars + 8 * (B4F + st));
                        tma_load_2d_mc(dst + 16384 + rank * 16384, t128, f0, kb * 64, bars + 8 * (B4F + st), 3);
                        tma_load_2d_mc(dst + 16384 + rank * 16384 + 8192, t128, f0 + 64, kb * 64, bars + 8 * (B4F + st), 3);
                    } else {
                        mbar_expect_tx(bars + 8 * (B4F + st), 16384 + 24576);
                        tma_load_2d(dst, &tm.h2, kb * 64, m0, bars + 8 * (B4F + st));
#pragma unroll 1
                        for (int c = 0; c < 3; c++)
                            tma_load_2d_mc(dst + 16384 + rank * 12288 + c * 4096, t64, f0 + 128 + c * 32, kb * 64, bars + 8 * (B4F + st), 3);
                    }
                    if (++st == 4) { st = 0; ph ^= 1; }
                }
            }
            {
                const int mt5 = p * 2 + (j >> 2), n0 = (j & 3) * 160;
                const int nkb = rank == 0 ? 14 : 13;
                const unsigned long long ord = rank == 0
                    ? (0ull | 1ull << 5 | 4ull << 10 | 7ull << 15 | 11ull << 20 | 2ull << 25 | 3ull << 30 | 5ull << 35 | 6ull << 40 | 8ull << 45 | 9ull << 50 | 10ull << 55)
                    : (14ull | 17ull << 5 | 21ull << 10 | 24ull << 15 | 15ull << 20 | 16ull << 25 | 18ull << 30 | 19ull << 35 | 20ull << 40 | 22ull << 45 | 23ull << 50 | 25ull << 55);
                const int nearly = rank == 0 ? 5 : 4;
                mbar_wait(bars + 8 * BD4, 0);
                uint32_t st = 0, ph = 1;
#pragma unroll 1
                for (int i = 0; i < nkb; i++) {
                    const int kb = i < 12 ? (int)((ord >> (5 * i)) & 31) : (rank == 0 ? i : 26);
                    if (i == 0) { flag_wait(F_A1 + mt5, (epoch + 1) * 16); fence_proxy_async_all(); }
                    if (i == nearly) { flag_wait(F_A + mt5, (epoch + 1) * 16); fence_proxy_async_all(); }
                    mbar_wait(bars + 8 * (B5E + st), ph);
                    mbar_expect_tx(bars + 8 * (B5F + st), P5_STAGE);
                    const uint32_t dst = base + st * P5_STAGE;
                    const int k0 = kb * 64;
                    tma_load_2d(dst + 16384, &tm.wd, n0, k0, bars + 8 * (B5F + st));
                    tma_load_2d(dst + 16384 + 8192, &tm.wd, n0 + 64, k0, bars + 8 * (B5F + st));
                    tma_load_2d(dst + 16384 + 16384, &tm.wd32, n0 + 128, k0, bars + 8 * (B5F + st));
                    tma_load_2d(dst, &tm.act_a, k0, mt5 * 128, bars + 8 * (B5F + st));
                    if (++st == 5) { st = 0; ph ^= 1; }
                }
            }
        }
        else if (threadIdx.x >= 320 && (threadIdx.x & 31) == 0) {
            const int hw = (threadIdx.x - 320) >> 5;
            const uint32_t stg = base + SM_STAGING + hw * 16384;
            const int r0 = m0 + hw * 64;
            auto both = [&](int b) { mbar_arrive_cluster(bars + 8 * b, 0); mbar_arrive_cluster(bars + 8 * b, 1); };
#pragma unroll 1
            for (int job = 0; job < 7; job++) {
                mbar_wait(bars + 8 * (BHS + hw), job & 1);
                if (job < 4) {
                    tma_store_2d(&tm.o_st, stg, (j * 4 + job) * 128, r0);
                    tma_store_2d(&tm.o_st, stg + 8192, (j * 4 + job) * 128 + 64, r0);
                } else if (job == 4) {
#pragma unroll 1
                    for (int c = 0; c < 5; c++)
                        tma_store_2d(&tm.part_st, base + hw * 40960 + c * 8192, (j & 1) * 320 + c * 64, (j >> 1) * S_LEN + r0);
                } else {
                    tma_store_2d(&tm.act_st64, stg, j * 216 + (job - 5) * 128, r0);
                    tma_store_2d(job == 5 ? &tm.act_st64 : &tm.act_st24, stg + 8192, j * 216 + (job - 5) * 128 + 64, r0);
                }
                tma_store_commit();
                tma_store_wait_read<0>();
                mbar_arrive(bars + 8 * (BHF + hw));
                if (job == 3) both(BD1);
                if (job >= 2) {
                    tma_store_wait<0>();
                    if (job == 2) { fence_proxy_async_all(); __threadfence(); both(BD1A); }
                    else if (job == 3) flag_signal_relaxed(F_O + mt * 4 + (j >> 1));
                    else if (job == 4) { both(BD2); flag_signal_relaxed(F_P + mt); }
                    else if (job == 5) flag_signal_relaxed(F_A1 + mt);
                    else { both(BD4B); flag_signal_relaxed(F_A + mt); }
                }
            }
        }
        else if (threadIdx.x == 288) {
            mbar_wait(bars + 8 * B1F, 0);
            const char* pw[4] = {(const char*)wo_p, (const char*)wg_p, (const char*)wu_p, (const char*)wd_p};
#pragma unroll 1
            for (int t = 0; t < 4; t++) {
                const uint32_t bytes = t == 0 ? 40960u : 17280u;
                asm volatile("cp.async.bulk.prefetch.L2.global [%0], %1;" ::"l"(pw[t] + (size_t)blockIdx.x * bytes), "r"(bytes) : "memory");
            }
        }
        __syncwarp();
        asm volatile("barrier.cluster.arrive.relaxed.aligned; // producer\n barrier.cluster.wait.aligned;" ::: "memory");
    } else {
        reg_alloc<232>();
        const int tid = threadIdx.x & 127;
        const int warp = tid >> 5, lane = tid & 31;
        const int cw = threadIdx.x >> 5;
        const uint32_t mystage = base + SM_STAGING + wg * 16384;
        auto arrive_both = [&](uint32_t bar) {
            if (tid == 0) mbar_arrive_cluster(bar, 0);
            if (tid == 32) mbar_arrive_cluster(bar, 1);
        };
        uint32_t njobs = 0;
        auto staging_free = [&]() { if (njobs > 0) mbar_wait(bars + 8 * (BHF + wg), (njobs - 1) & 1); };
        auto submit_job = [&]() {
            fence_proxy_async();
            bar_sync(1 + wg, 128);
            if (tid == 0) mbar_arrive(bars + 8 * (BHS + wg));
            njobs++;
        };
        TS(0, 0);
        {
            if (blockIdx.x < 120) {
                float* red = reinterpret_cast<float*>(smem_raw + (base - smem_u32(smem_raw)) + SM_STAGING);
                float acc[8];
#pragma unroll
                for (int i = 0; i < 8; i++) acc[i] = 0.f;
#pragma unroll
                for (int i = 0; i < 10; i++) {
                    const float s = bf16_round(silu_mul(__uint_as_float((uint32_t)cr[i] << 16), 1.f));
                    acc[0] += s * bf16lo(w[i].x); acc[1] += s * bf16hi(w[i].x);
                    acc[2] += s * bf16lo(w[i].y); acc[3] += s * bf16hi(w[i].y);
                    acc[4] += s * bf16lo(w[i].z); acc[5] += s * bf16hi(w[i].z);
                    acc[6] += s * bf16lo(w[i].w); acc[7] += s * bf16hi(w[i].w);
                }
#pragma unroll
                for (int i = 0; i < 8; i++) {
                    acc[i] += __shfl_xor_sync(0xffffffffu, acc[i], 4);
                    acc[i] += __shfl_xor_sync(0xffffffffu, acc[i], 8);
                    acc[i] += __shfl_xor_sync(0xffffffffu, acc[i], 16);
                }
                if (lane < 4) {
#pragma unroll
                    for (int i = 0; i < 8; i++) red[cw * 32 + lane * 8 + i] = acc[i];
                }
                TS(6, 0);
                bar_sync(5, 256);
                TS(6, 1);
                if (threadIdx.x < 32) {
                    float t = 0.f;
#pragma unroll
                    for (int i = 0; i < 8; i++) t += red[i * 32 + threadIdx.x];
                    t = bf16_round(t);
                    const int chunk = blockIdx.x / 20;
                    if (chunk == 1 || chunk == 4) t = bf16_round(1.f + t);
                    g_mod[blockIdx.x * 32 + threadIdx.x] = t;
                    __syncwarp();
                    TS(6, 2);
                    if (threadIdx.x == 0) flag_signal(blockIdx.x < 40 ? F_MODAB : F_MODALL);
                    TS(6, 3);
                }
            }
            if (threadIdx.x == 0) flag_wait(F_MODAB, (epoch + 1) * 40);
            bar_sync(5, 256);
            TS(0, 1);
            ln_rows(xr, g_mod, g_mod + D_MODEL, g_h + (size_t)(m0 + j * 16 + cw * 2) * D_MODEL, lane);
            TS(6, 4);
            bar_sync(5, 256);
            TS(6, 5);
            if (threadIdx.x == 0) flag_signal(F_H + mt);
        }
        TS(0, 2);
        {
            const float cscale = 0.08838834764831845f * 1.4426950408889634f;
            uint32_t st = 0, ph = 0;
            auto wait_full = [&]() -> uint32_t {
                mbar_wait(bars + 8 * (B1F + st), ph);
                return base + st * P1_STAGE;
            };
            auto release = [&](uint32_t s) { arrive_both(bars + 8 * (B1E + s)); };
            auto advance = [&]() { if (++st == 6) { st = 0; ph ^= 1; } };
            auto turn_wait = [&]() { bar_sync(3 + wg, 256); };
            auto turn_pass = [&]() { bar_arrive(3 + (wg ^ 1), 256); };
            if (wg == 1) bar_arrive(3, 256);

            for (int hp = 0; hp < 2; hp++) {
                const int head0 = j * 4 + hp * 2;
                uint32_t q[8][4];
                {
                    float acc[128];
#pragma unroll
                    for (int i = 0; i < 128; i++) acc[i] = 0.f;
                    for (int kk2 = 0; kk2 < 5; kk2++) {
                        const uint32_t hbuf = wait_full();
                        if (kk2 == 0 && hp == 0) TS(0, 3);
                        const uint32_t sth = st;
                        advance();
#pragma unroll
                        for (int u = 0; u < 2; u++) {
                            const uint32_t wbuf = wait_full();
                            const uint32_t stw = st;
                            advance();
                            wgmma_fence();
#pragma unroll
                            for (int k = 0; k < 4; k++) {
                                uint64_t da = make_desc(hbuf + u * 16384 + wg * 8192 + k * 32, 16, 1024, 1);
                                uint64_t db = make_desc(wbuf + k * 2048, 8192, 1024, 1);
                                wgmma_ss_n256_t1(acc, da, db, 1);
                            }
                            wgmma_commit();
                            wgmma_wait<0>();
                            release(stw);
                        }
                        release(sth);
                    }
                    fence_regs(acc);
                    staging_free();
#pragma unroll
                    for (int i = 0; i < 8; i++) {
                        q[i][0] = pack_bf16(acc[8 * i + 0], acc[8 * i + 1]);
                        q[i][1] = pack_bf16(acc[8 * i + 2], acc[8 * i + 3]);
                        q[i][2] = pack_bf16(acc[8 * i + 4], acc[8 * i + 5]);
                        q[i][3] = pack_bf16(acc[8 * i + 6], acc[8 * i + 7]);
                        uint32_t b0 = pack_bf16(acc[64 + 8 * i + 0], acc[64 + 8 * i + 1]);
                        uint32_t b1 = pack_bf16(acc[64 + 8 * i + 2], acc[64 + 8 * i + 3]);
                        uint32_t b2 = pack_bf16(acc[64 + 8 * i + 4], acc[64 + 8 * i + 5]);
                        uint32_t b3 = pack_bf16(acc[64 + 8 * i + 6], acc[64 + 8 * i + 7]);
                        asm volatile("st.shared.v4.b32 [%0], {%1, %2, %3, %4};" ::"r"(mystage + (i * 128 + tid) * 16), "r"(b0), "r"(b1),
                                     "r"(b2), "r"(b3) : "memory");
                    }
                }
                float o[64], s[64], e[64];
                uint32_t pp[8][4];
                float mm0, mm1, l0, l1, a0, a1, lo0, lo1;
#pragma unroll
                for (int i = 0; i < 64; i++) { o[i] = 0.f; }

                auto issue_s = [&]() -> uint32_t {
                    const uint32_t kbuf = wait_full();
                    const uint32_t stk = st;
                    advance();
                    wgmma_fence();
#pragma unroll
                    for (int k = 0; k < 8; k++) {
                        uint64_t db = make_desc(kbuf + (k >> 2) * 16384 + (k & 3) * 32, 16, 1024, 1);
                        if (k == 0) wgmma_rs_n128_t0_z(s, q[k], db);
                        else wgmma_rs_n128_t0(s, q[k], db, 1);
                    }
                    wgmma_commit();
                    return stk;
                };
                auto issue_pv = [&](bool fresh) -> uint32_t {
                    const uint32_t vbuf = wait_full();
                    const uint32_t stv = st;
                    advance();
                    wgmma_fence();
#pragma unroll
                    for (int k = 0; k < 8; k++) {
                        uint64_t db = make_desc(vbuf + k * 2048, 16384, 1024, 1);
                        wgmma_rs_n128_t1(o, pp[k], db, (!fresh) || k != 0);
                    }
                    wgmma_commit();
                    return stv;
                };
                auto softmax = [&](bool first) {
                    float mx0 = fmaxf(s[0], s[1]), mx1 = fmaxf(s[2], s[3]);
#pragma unroll
                    for (int jj = 1; jj < 16; jj++) {
                        mx0 = fmaxf(mx0, fmaxf(s[4 * jj], s[4 * jj + 1]));
                        mx1 = fmaxf(mx1, fmaxf(s[4 * jj + 2], s[4 * jj + 3]));
                    }
                    mx0 = fmaxf(mx0, __shfl_xor_sync(0xffffffffu, mx0, 1));
                    mx0 = fmaxf(mx0, __shfl_xor_sync(0xffffffffu, mx0, 2));
                    mx1 = fmaxf(mx1, __shfl_xor_sync(0xffffffffu, mx1, 1));
                    mx1 = fmaxf(mx1, __shfl_xor_sync(0xffffffffu, mx1, 2));
                    if (first) {
                        lo0 = l0; lo1 = l1;
                        mm0 = mx0; mm1 = mx1; l0 = 0.f; l1 = 0.f; a0 = 0.f; a1 = 0.f;
                    } else {
                        float mn0 = fmaxf(mm0, mx0), mn1 = fmaxf(mm1, mx1);
                        a0 = ex2((mm0 - mn0) * cscale); a1 = ex2((mm1 - mn1) * cscale);
                        mm0 = mn0; mm1 = mn1;
                    }
                    const float mc0 = mm0 * cscale, mc1 = mm1 * cscale;
                    float r0 = 0.f, r1 = 0.f;
#pragma unroll
                    for (int jj = 0; jj < 16; jj++) {
                        e[4 * jj] = ex2(fmaf(s[4 * jj], cscale, -mc0));
                        e[4 * jj + 1] = ex2(fmaf(s[4 * jj + 1], cscale, -mc0));
                        e[4 * jj + 2] = ex2(fmaf(s[4 * jj + 2], cscale, -mc1));
                        e[4 * jj + 3] = ex2(fmaf(s[4 * jj + 3], cscale, -mc1));
                        r0 += e[4 * jj] + e[4 * jj + 1];
                        r1 += e[4 * jj + 2] + e[4 * jj + 3];
                    }
                    l0 = l0 * a0 + r0; l1 = l1 * a1 + r1;
                };
                auto convert_p = [&]() {
#pragma unroll
                    for (int i = 0; i < 8; i++) {
                        pp[i][0] = pack_bf16(e[8 * i + 0], e[8 * i + 1]);
                        pp[i][1] = pack_bf16(e[8 * i + 2], e[8 * i + 3]);
                        pp[i][2] = pack_bf16(e[8 * i + 4], e[8 * i + 5]);
                        pp[i][3] = pack_bf16(e[8 * i + 6], e[8 * i + 7]);
                    }
                };
                auto store_o = [&](float ls0, float ls1, int head, bool last) {
                    float s0 = ls0 + __shfl_xor_sync(0xffffffffu, ls0, 1); s0 += __shfl_xor_sync(0xffffffffu, s0, 2);
                    float s1 = ls1 + __shfl_xor_sync(0xffffffffu, ls1, 1); s1 += __shfl_xor_sync(0xffffffffu, s1, 2);
                    const float i0 = 1.f / s0, i1 = 1.f / s1;
                    if (last) arrive_both(bars + 8 * BD1A);
                    staging_free();
                    bar_sync(1 + wg, 128);
#pragma unroll
                    for (int jj = 0; jj < 16; jj += 2) {
                        const int mi = lane >> 3;
                        const int row = warp * 16 + (mi & 1) * 8 + (lane & 7);
                        const int grp = jj + (mi >> 1);
                        const uint32_t addr = mystage + (grp >> 3) * 8192 + row * 128 + (((grp & 7) ^ (row & 7)) << 4);
                        stmatrix_x4(addr, pack_bf16(o[4 * jj] * i0, o[4 * jj + 1] * i0), pack_bf16(o[4 * jj + 2] * i1, o[4 * jj + 3] * i1),
                                    pack_bf16(o[4 * jj + 4] * i0, o[4 * jj + 5] * i0), pack_bf16(o[4 * jj + 6] * i1, o[4 * jj + 7] * i1));
                    }
                    submit_job();
                };

                l0 = 0.f; l1 = 0.f;
                {
                    turn_wait();
                    uint32_t stk = issue_s();
                    turn_pass();
                    wgmma_wait<0>();
                    fence_regs(s);
                    release(stk);
                    softmax(true);
                    convert_p();
                }
#pragma unroll 1
                for (int t = 1; t < 8; t++) {
                    const bool first = (t == 4);
                    if (t == 4) {
#pragma unroll
                        for (int i = 0; i < 8; i++) {
                            asm volatile("ld.shared.v4.b32 {%0, %1, %2, %3}, [%4];" : "=r"(q[i][0]), "=r"(q[i][1]), "=r"(q[i][2]), "=r"(q[i][3])
                                         : "r"(mystage + (i * 128 + tid) * 16) : "memory");
                        }
                    }
                    turn_wait();
                    uint32_t stk = issue_s();
                    uint32_t stv = issue_pv(t == 1 || t == 5);
                    turn_pass();
                    wgmma_wait<1>();
                    fence_regs(s);
                    release(stk);
                    softmax(first);
                    asm volatile("{\n.reg .pred p;\nsetp.lt.f32 p, %0, 0fBF800000;\n@p st.shared.f32 [%1], %0;\n}\n" ::"f"(l0 + l1), "r"(mystage) : "memory");
                    wgmma_wait<0>();
                    fence_regs(o);
                    release(stv);
                    if (first) {
                        store_o(lo0, lo1, head0, false);
                    } else {
#pragma unroll
                        for (int jj = 0; jj < 16; jj++) {
                            o[4 * jj] *= a0; o[4 * jj + 1] *= a0; o[4 * jj + 2] *= a1; o[4 * jj + 3] *= a1;
                        }
                    }
                    convert_p();
                }
                {
                    turn_wait();
                    uint32_t stv = issue_pv(false);
                    turn_pass();
                    wgmma_wait<0>();
                    fence_regs(o);
                    release(stv);
                    store_o(l0, l1, head0 + 1, hp == 1);
                }
            }
        }
        TS(0, 4);
        {
            const int kq = j >> 1, n0 = (j & 1) * 320;
            float acc0[96], acc1[64];
            uint32_t st = 0, ph = 0, prev = 0;
            for (int i = 0; i < 16; i++) {
                mbar_wait(bars + 8 * (B2F + st), ph);
                if (i == 0) TS(0, 5);
                const uint32_t buf = base + st * P2_STAGE;
                wgmma_fence();
#pragma unroll
                for (int k = 0; k < 4; k++) {
                    uint64_t da = make_desc(buf + wg * 8192 + k * 32, 16, 1024, 1);
                    wgmma_ss_n192_t1(acc0, da, make_desc(buf + 16384 + k * 2048, 8192, 1024, 1), (i | k) != 0);
                    wgmma_ss_n128_t1(acc1, da, make_desc(buf + 16384 + 3 * 8192 + k * 2048, 8192, 1024, 1), (i | k) != 0);
                }
                wgmma_commit();
                if (i > 0) { wgmma_wait<1>(); arrive_both(bars + 8 * (B2E + prev)); }
                prev = st;
                if (++st == 4) { st = 0; ph ^= 1; }
            }
            wgmma_wait<0>();
            fence_regs(acc0); fence_regs(acc1);
            TS(0, 6);
            bar_sync(5, 256);
            staging_free();
            const uint32_t stg = base + wg * 40960;
            const int mi = lane >> 3;
            const int row = warp * 16 + (mi & 1) * 8 + (lane & 7);
#pragma unroll
            for (int jj = 0; jj < 24; jj += 2) {
                const int grp = jj + (mi >> 1);
                stmatrix_x4(stg + (grp >> 3) * 8192 + row * 128 + (((grp & 7) ^ (row & 7)) << 4),
                            pack_bf16(acc0[4 * jj], acc0[4 * jj + 1]), pack_bf16(acc0[4 * jj + 2], acc0[4 * jj + 3]),
                            pack_bf16(acc0[4 * jj + 4], acc0[4 * jj + 5]), pack_bf16(acc0[4 * jj + 6], acc0[4 * jj + 7]));
            }
#pragma unroll
            for (int jj = 0; jj < 16; jj += 2) {
                const int grp = jj + (mi >> 1);
                stmatrix_x4(stg + (3 + (grp >> 3)) * 8192 + row * 128 + (((grp & 7) ^ (row & 7)) << 4),
                            pack_bf16(acc1[4 * jj], acc1[4 * jj + 1]), pack_bf16(acc1[4 * jj + 2], acc1[4 * jj + 3]),
                            pack_bf16(acc1[4 * jj + 4], acc1[4 * jj + 5]), pack_bf16(acc1[4 * jj + 6], acc1[4 * jj + 7]));
            }
            submit_job();
        }
        TS(0, 7);
        {
            uint2 xr[2][5];
#pragma unroll
            for (int rr = 0; rr < 2; rr++)
#pragma unroll
                for (int i = 0; i < 5; i++)
                    xr[rr][i] = __ldg(reinterpret_cast<const uint2*>(x + (size_t)(m0 + j * 16 + cw * 2 + rr) * D_MODEL + (lane + 32 * i) * 4));
            if (threadIdx.x == 0) { flag_wait(F_MODALL, (epoch + 1) * 80); flag_wait(F_P + mt, (epoch + 1) * 16); }
            bar_sync(5, 256);
            TS(0, 8);
            uint2 pr[2][4][5];
            float4 gv[5];
#pragma unroll
            for (int rr = 0; rr < 2; rr++)
#pragma unroll
                for (int s = 0; s < 4; s++)
#pragma unroll
                    for (int i = 0; i < 5; i++)
                        pr[rr][s][i] = ldcg_u2(g_part + ((size_t)s * S_LEN + m0 + j * 16 + cw * 2 + rr) * D_MODEL + (lane + 32 * i) * 4);
#pragma unroll
            for (int i = 0; i < 5; i++) gv[i] = __ldcg(reinterpret_cast<const float4*>(g_mod + 2 * D_MODEL + (lane + 32 * i) * 4));
#pragma unroll
            for (int rr = 0; rr < 2; rr++) {
#pragma unroll
                for (int i = 0; i < 5; i++) {
                    float a0 = (bf16lo(pr[rr][0][i].x) + bf16lo(pr[rr][1][i].x)) + (bf16lo(pr[rr][2][i].x) + bf16lo(pr[rr][3][i].x));
                    float a1 = (bf16hi(pr[rr][0][i].x) + bf16hi(pr[rr][1][i].x)) + (bf16hi(pr[rr][2][i].x) + bf16hi(pr[rr][3][i].x));
                    float a2 = (bf16lo(pr[rr][0][i].y) + bf16lo(pr[rr][1][i].y)) + (bf16lo(pr[rr][2][i].y) + bf16lo(pr[rr][3][i].y));
                    float a3 = (bf16hi(pr[rr][0][i].y) + bf16hi(pr[rr][1][i].y)) + (bf16hi(pr[rr][2][i].y) + bf16hi(pr[rr][3][i].y));
                    xr[rr][i].x = pack_bf16(bf16lo(xr[rr][i].x) + gv[i].x * a0, bf16hi(xr[rr][i].x) + gv[i].y * a1);
                    xr[rr][i].y = pack_bf16(bf16lo(xr[rr][i].y) + gv[i].z * a2, bf16hi(xr[rr][i].y) + gv[i].w * a3);
                    *reinterpret_cast<uint2*>(g_x1 + (size_t)(m0 + j * 16 + cw * 2 + rr) * D_MODEL + (lane + 32 * i) * 4) = xr[rr][i];
                }
            }
            TS(5, 0);
            ln_rows(xr, g_mod + 3 * D_MODEL, g_mod + 4 * D_MODEL, g_h2 + (size_t)(m0 + j * 16 + cw * 2) * D_MODEL, lane);
            TS(5, 1);
            bar_sync(5, 256);
            TS(5, 2);
            if (threadIdx.x == 0) flag_signal(F_H2 + mt);
        }
        TS(0, 9);
        {
            const int f0 = j * 216;
            uint32_t st = 0, ph = 0, prev = 0;
            {
                float acc[128];
                if (wg == 1) bar_sync(6, 256);
                for (int i = 0; i < 10; i++) {
                    mbar_wait(bars + 8 * (B4F + st), ph);
                    if (i == 0) TS(0, 10);
                    const uint32_t buf = base + st * P4_STAGE;
                    wgmma_fence();
#pragma unroll
                    for (int k = 0; k < 4; k++) {
                        uint64_t da = make_desc(buf + wg * 8192 + k * 32, 16, 1024, 1);
                        uint64_t db = make_desc(buf + 16384 + k * 2048, 8192, 1024, 1);
                        wgmma_ss_n256_t1(acc, da, db, (i | k) != 0);
                    }
                    wgmma_commit();
                    if (i == 1 && wg == 0) bar_arrive(6, 256);
                    if (i > 0) { wgmma_wait<1>(); arrive_both(bars + 8 * (B4E + prev)); }
                    prev = st;
                    if (++st == 4) { st = 0; ph ^= 1; }
                }
                wgmma_wait<0>();
                arrive_both(bars + 8 * (B4E + prev));
                fence_regs(acc);
                staging_free();
#pragma unroll
                for (int jj = 0; jj < 16; jj += 2) {
                    const int mi = lane >> 3;
                    const int row = warp * 16 + (mi & 1) * 8 + (lane & 7);
                    const int grp = jj + (mi >> 1);
                    const uint32_t addr = mystage + (grp >> 3) * 8192 + row * 128 + (((grp & 7) ^ (row & 7)) << 4);
                    stmatrix_x4(addr, pack_bf16(silu_mul(acc[4 * jj], acc[64 + 4 * jj]), silu_mul(acc[4 * jj + 1], acc[64 + 4 * jj + 1])),
                                pack_bf16(silu_mul(acc[4 * jj + 2], acc[64 + 4 * jj + 2]), silu_mul(acc[4 * jj + 3], acc[64 + 4 * jj + 3])),
                                pack_bf16(silu_mul(acc[4 * jj + 4], acc[64 + 4 * jj + 4]), silu_mul(acc[4 * jj + 5], acc[64 + 4 * jj + 5])),
                                pack_bf16(silu_mul(acc[4 * jj + 6], acc[64 + 4 * jj + 6]), silu_mul(acc[4 * jj + 7], acc[64 + 4 * jj + 7])));
                }
                submit_job();
            }
            {
                float acc[92];
                for (int i = 0; i < 10; i++) {
                    mbar_wait(bars + 8 * (B4F + st), ph);
                    const uint32_t buf = base + st * P4_STAGE;
                    wgmma_fence();
#pragma unroll
                    for (int k = 0; k < 4; k++) {
                        uint64_t da = make_desc(buf + wg * 8192 + k * 32, 16, 1024, 1);
                        uint64_t db = make_desc(buf + 16384 + k * 1024, 4096, 512, 2);
                        wgmma_ss_n184_t1(acc, da, db, (i | k) != 0);
                    }
                    wgmma_commit();
                    if (i > 0) { wgmma_wait<1>(); arrive_both(bars + 8 * (B4E + prev)); }
                    prev = st;
                    if (++st == 4) { st = 0; ph ^= 1; }
                }
                wgmma_wait<0>();
                arrive_both(bars + 8 * BD4);
                fence_regs(acc);
                TS(0, 11);
                staging_free();
#pragma unroll
                for (int jj = 0; jj < 8; jj += 2) {
                    const int mi = lane >> 3;
                    const int row = warp * 16 + (mi & 1) * 8 + (lane & 7);
                    const int grp = jj + (mi >> 1);
                    const uint32_t addr = mystage + row * 128 + ((grp ^ (row & 7)) << 4);
                    stmatrix_x4(addr, pack_bf16(silu_mul(acc[4 * jj], acc[48 + 4 * jj]), silu_mul(acc[4 * jj + 1], acc[48 + 4 * jj + 1])),
                                pack_bf16(silu_mul(acc[4 * jj + 2], acc[48 + 4 * jj + 2]), silu_mul(acc[4 * jj + 3], acc[48 + 4 * jj + 3])),
                                pack_bf16(silu_mul(acc[4 * jj + 4], acc[48 + 4 * jj + 4]), silu_mul(acc[4 * jj + 5], acc[48 + 4 * jj + 5])),
                                pack_bf16(silu_mul(acc[4 * jj + 6], acc[48 + 4 * jj + 6]), silu_mul(acc[4 * jj + 7], acc[48 + 4 * jj + 7])));
                }
                {
                    const int mi = lane >> 3;
                    const int row = warp * 16 + (mi & 1) * 8 + (lane & 7);
                    const uint32_t addr = mystage + 8192 + row * 48 + (mi >> 1) * 16;
                    stmatrix_x4(addr, pack_bf16(silu_mul(acc[32], acc[80]), silu_mul(acc[33], acc[81])),
                                pack_bf16(silu_mul(acc[34], acc[82]), silu_mul(acc[35], acc[83])),
                                pack_bf16(silu_mul(acc[36], acc[84]), silu_mul(acc[37], acc[85])),
                                pack_bf16(silu_mul(acc[38], acc[86]), silu_mul(acc[39], acc[87])));
                    const uint32_t addr2 = mystage + 8192 + (warp * 16 + ((lane >> 3) & 1) * 8 + (lane & 7)) * 48 + 32;
                    asm volatile("stmatrix.sync.aligned.m8n8.x2.shared.b16 [%0], {%1, %2};" ::"r"(addr2),
                                 "r"(pack_bf16(silu_mul(acc[40], acc[88]), silu_mul(acc[41], acc[89]))),
                                 "r"(pack_bf16(silu_mul(acc[42], acc[90]), silu_mul(acc[43], acc[91]))) : "memory");
                }
                submit_job();
            }
        }
        TS(0, 12);
        {
            const int m5 = (p * 2 + (j >> 2)) * 128, n0 = (j & 3) * 160;
            const int nkb = rank == 0 ? 14 : 13;
            float accA[64], accB[16];
            uint32_t st = 0, ph = 0, prev = 0;
            const int cbase = n0 + (int)rank * 80;
            for (int i = 0; i < nkb; i++) {
                mbar_wait(bars + 8 * (B5F + st), ph);
                if (i == 0) TS(0, 13);
                const uint32_t buf = base + st * P5_STAGE;
                wgmma_fence();
#pragma unroll
                for (int k = 0; k < 4; k++) {
                    uint64_t da = make_desc(buf + wg * 8192 + k * 32, 16, 1024, 1);
                    wgmma_ss_n128_t1(accA, da, make_desc(buf + 16384 + k * 2048, 8192, 1024, 1), (i | k) != 0);
                    wgmma_ss_n32_t1(accB, da, make_desc(buf + 32768 + k * 1024, 4096, 512, 2), (i | k) != 0);
                }
                wgmma_commit();
                if (i > 0) {
                    wgmma_wait<1>();
                    if (tid == 0) mbar_arrive(bars + 8 * (B5E + prev));
                }
                prev = st;
                if (++st == 5) { st = 0; ph ^= 1; }
            }
            uint4 xv[5];
            float2 gbv[10];
#pragma unroll
            for (int it = 0; it < 5; it++) {
                const int idx = it * 256 + (int)threadIdx.x;
                const int row = idx / 10, ch = idx - row * 10;
                xv[it] = __ldcg(reinterpret_cast<const uint4*>(g_x1 + (size_t)(m5 + row) * D_MODEL + cbase + ch * 8));
            }
#pragma unroll
            for (int jj = 0; jj < 10; jj++) gbv[jj] = __ldcg(reinterpret_cast<const float2*>(g_mod + 5 * D_MODEL + cbase + jj * 8 + (lane & 3) * 2));
            wgmma_wait<0>();
            fence_regs(accA); fence_regs(accB);
            float acc[80];
#pragma unroll
            for (int i = 0; i < 64; i++) acc[i] = accA[i];
#pragma unroll
            for (int i = 0; i < 16; i++) acc[64 + i] = accB[i];
            TS(0, 14);
            constexpr uint32_t XBUF = 5 * P5_STAGE;
            mbar_wait(bars + 8 * BD4B, 0);
            TS(3, 0);
            {
                const uint32_t dst = mapa(base + XBUF, rank ^ 1) + wg * 20480 + tid * 16;
                const uint32_t rbar = mapa(bars + 8 * BX, rank ^ 1);
                if (rank == 0) {
#pragma unroll
                    for (int i = 0; i < 10; i++)
                        asm volatile("st.async.shared::cluster.mbarrier::complete_tx::bytes.v4.f32 [%0], {%1, %2, %3, %4}, [%5];" ::"r"(dst + i * 2048),
                                     "f"(acc[40 + 4 * i]), "f"(acc[40 + 4 * i + 1]), "f"(acc[40 + 4 * i + 2]), "f"(acc[40 + 4 * i + 3]), "r"(rbar) : "memory");
                } else {
#pragma unroll
                    for (int i = 0; i < 10; i++)
                        asm volatile("st.async.shared::cluster.mbarrier::complete_tx::bytes.v4.f32 [%0], {%1, %2, %3, %4}, [%5];" ::"r"(dst + i * 2048),
                                     "f"(acc[4 * i]), "f"(acc[4 * i + 1]), "f"(acc[4 * i + 2]), "f"(acc[4 * i + 3]), "r"(rbar) : "memory");
                }
            }
            TS(3, 1);
            mbar_wait(bars + 8 * BX, 0);
            TS(3, 2);
            {
                bar_sync(5, 256);
                const uint32_t tile = base;
                TS(3, 3);
#pragma unroll
                for (int jj = 0; jj < 10; jj += 2) {
                    float4 o0, o1;
                    asm volatile("ld.shared.v4.f32 {%0, %1, %2, %3}, [%4];" : "=f"(o0.x), "=f"(o0.y), "=f"(o0.z), "=f"(o0.w) : "r"(base + XBUF + wg * 20480 + tid * 16 + jj * 2048));
                    asm volatile("ld.shared.v4.f32 {%0, %1, %2, %3}, [%4];" : "=f"(o1.x), "=f"(o1.y), "=f"(o1.z), "=f"(o1.w) : "r"(base + XBUF + wg * 20480 + tid * 16 + (jj + 1) * 2048));
                    const float2 g0 = gbv[jj], g1 = gbv[jj + 1];
                    float a[8];
#pragma unroll
                    for (int ee = 0; ee < 8; ee++) a[ee] = rank == 0 ? acc[4 * jj + ee] : acc[40 + 4 * jj + ee];
                    const int mi = lane >> 3;
                    const int row = wg * 64 + warp * 16 + (mi & 1) * 8 + (lane & 7);
                    const uint32_t addr = tile + row * 176 + (jj + (mi >> 1)) * 16;
                    stmatrix_x4(addr, pack_bf16(g0.x * bf16_round(a[0] + o0.x), g0.y * bf16_round(a[1] + o0.y)),
                                pack_bf16(g0.x * bf16_round(a[2] + o0.z), g0.y * bf16_round(a[3] + o0.w)),
                                pack_bf16(g1.x * bf16_round(a[4] + o1.x), g1.y * bf16_round(a[5] + o1.y)),
                                pack_bf16(g1.x * bf16_round(a[6] + o1.z), g1.y * bf16_round(a[7] + o1.w)));
                }
                TS(3, 4);
                bar_sync(5, 256);
                TS(3, 5);
#pragma unroll
                for (int it = 0; it < 5; it++) {
                    const int idx = it * 256 + (int)threadIdx.x;
                    const int row = idx / 10, ch = idx - row * 10;
                    uint4 tv;
                    asm volatile("ld.shared.v4.b32 {%0, %1, %2, %3}, [%4];" : "=r"(tv.x), "=r"(tv.y), "=r"(tv.z), "=r"(tv.w) : "r"(tile + row * 176 + ch * 16));
                    uint4 r;
                    r.x = pack_bf16(bf16lo(xv[it].x) + bf16lo(tv.x), bf16hi(xv[it].x) + bf16hi(tv.x));
                    r.y = pack_bf16(bf16lo(xv[it].y) + bf16lo(tv.y), bf16hi(xv[it].y) + bf16hi(tv.y));
                    r.z = pack_bf16(bf16lo(xv[it].z) + bf16lo(tv.z), bf16hi(xv[it].z) + bf16hi(tv.z));
                    r.w = pack_bf16(bf16lo(xv[it].w) + bf16lo(tv.w), bf16hi(xv[it].w) + bf16hi(tv.w));
                    *reinterpret_cast<uint4*>(out + (size_t)(m5 + row) * D_MODEL + cbase + ch * 8) = r;
                }
            }
            TS(0, 15);
            if (threadIdx.x == 0) {
                const unsigned old = atomicAdd(&g_exit, 1u);
                if (old == (epoch + 1) * 128u - 1u) {
                    asm volatile("st.volatile.global.u32 [%0], %1;" ::"l"(&g_epoch), "r"(epoch + 1) : "memory");
                }
            }
            asm volatile("barrier.cluster.arrive.relaxed.aligned;\n barrier.cluster.wait.aligned;" ::: "memory");
        }
    }
}

typedef CUresult (*PFN_encodeTiled)(CUtensorMap*, CUtensorMapDataType, cuuint32_t, void*, const cuuint64_t*, const cuuint64_t*,
                                    const cuuint32_t*, const cuuint32_t*, CUtensorMapInterleave, CUtensorMapSwizzle,
                                    CUtensorMapL2promotion, CUtensorMapFloatOOBfill);

static PFN_encodeTiled get_encode() {
    static PFN_encodeTiled fn = nullptr;
    if (!fn) {
        void* p = nullptr;
        cudaDriverEntryPointQueryResult qr;
        cudaGetDriverEntryPoint("cuTensorMapEncodeTiled", &p, cudaEnableDefault, &qr);
        fn = (PFN_encodeTiled)p;
    }
    return fn;
}

static CUtensorMap make_map(const void* ptr, uint64_t rows, uint64_t cols, uint32_t box_rows, uint32_t box_cols, CUtensorMapSwizzle swz) {
    CUtensorMap m;
    cuuint64_t dims[2] = {cols, rows};
    cuuint64_t strides[1] = {cols * 2};
    cuuint32_t box[2] = {box_cols, box_rows};
    cuuint32_t es[2] = {1, 1};
    get_encode()(&m, CU_TENSOR_MAP_DATA_TYPE_BFLOAT16, 2, const_cast<void*>(ptr), dims, strides, box, es, CU_TENSOR_MAP_INTERLEAVE_NONE,
                 swz, CU_TENSOR_MAP_L2_PROMOTION_L2_256B, CU_TENSOR_MAP_FLOAT_OOB_FILL_NONE);
    return m;
}

extern "C" void kernel_launch(void* const* d_in, const int* in_sizes, int n_in, void* d_out, int out_size) {
    (void)in_sizes; (void)n_in; (void)out_size;
    const __nv_bfloat16* x = (const __nv_bfloat16*)d_in[0];
    const __nv_bfloat16* kc = (const __nv_bfloat16*)d_in[1];
    const __nv_bfloat16* vc = (const __nv_bfloat16*)d_in[2];
    const __nv_bfloat16* wq = (const __nv_bfloat16*)d_in[3];
    const __nv_bfloat16* wo = (const __nv_bfloat16*)d_in[4];
    const __nv_bfloat16* wg = (const __nv_bfloat16*)d_in[6];
    const __nv_bfloat16* wu = (const __nv_bfloat16*)d_in[7];
    const __nv_bfloat16* wd = (const __nv_bfloat16*)d_in[8];
    const __nv_bfloat16* c = (const __nv_bfloat16*)d_in[9];
    const __nv_bfloat16* wmod = (const __nv_bfloat16*)d_in[10];
    __nv_bfloat16* out = (__nv_bfloat16*)d_out;

    static bool init = false;
    static void *p_h, *p_o, *p_x1, *p_h2, *p_act, *p_part;
    if (!init) {
        cudaFuncSetAttribute(mega_kernel, cudaFuncAttributeMaxDynamicSharedMemorySize, SM_TOTAL);
        cudaGetSymbolAddress(&p_h, g_h);
        cudaGetSymbolAddress(&p_o, g_o);
        cudaGetSymbolAddress(&p_x1, g_x1);
        cudaGetSymbolAddress(&p_h2, g_h2);
        cudaGetSymbolAddress(&p_act, g_act);
        cudaGetSymbolAddress(&p_part, g_part);
        init = true;
    }
    const CUtensorMapSwizzle S128 = CU_TENSOR_MAP_SWIZZLE_128B, S64 = CU_TENSOR_MAP_SWIZZLE_64B;
    Maps tm;
    tm.h = make_map(p_h, S_LEN, D_MODEL, 128, 64, S128);
    tm.wq = make_map(wq, D_MODEL, N_HEADS * D_HEAD, 64, 64, S128);
    tm.k = make_map(kc, N_HEADS * S_KV, D_HEAD, 128, 64, S128);
    tm.v = make_map(vc, N_HEADS * S_KV, D_HEAD, 128, 64, S128);
    tm.o_st = make_map(p_o, S_LEN, N_HEADS * D_HEAD, 64, 64, S128);
    tm.o_a = make_map(p_o, S_LEN, N_HEADS * D_HEAD, 128, 64, S128);
    tm.wo = make_map(wo, N_HEADS * D_HEAD, D_MODEL, 64, 64, S128);
    tm.part_st = make_map(p_part, 4 * S_LEN, D_MODEL, 64, 64, S128);
    tm.h2 = make_map(p_h2, S_LEN, D_MODEL, 128, 64, S128);
    tm.g128 = make_map(wg, D_MODEL, D_FF, 64, 64, S128);
    tm.u128 = make_map(wu, D_MODEL, D_FF, 64, 64, S128);
    tm.g64 = make_map(wg, D_MODEL, D_FF, 64, 32, S64);
    tm.u64 = make_map(wu, D_MODEL, D_FF, 64, 32, S64);
    tm.act_st64 = make_map(p_act, S_LEN, D_FF, 64, 64, S128);
    tm.act_st24 = make_map(p_act, S_LEN, D_FF, 64, 24, CU_TENSOR_MAP_SWIZZLE_NONE);
    tm.act_a = make_map(p_act, S_LEN, D_FF, 128, 64, S128);
    tm.wd = make_map(wd, D_FF, D_MODEL, 64, 64, S128);
    tm.wd32 = make_map(wd, D_FF, D_MODEL, 64, 32, S64);

    cudaLaunchConfig_t cfg = {};
    cfg.gridDim = dim3(128);
    cfg.blockDim = dim3(384);
    cfg.dynamicSmemBytes = SM_TOTAL;
    cfg.stream = cudaStreamPerThread;
    cfg.attrs = nullptr;
    cfg.numAttrs = 0;
    cudaLaunchKernelEx(&cfg, mega_kernel, tm, x, c, wmod, out, (const void*)wo, (const void*)wg, (const void*)wu, (const void*)wd);
}
```
